```python
import torch

def _softmax(x, axis=-1):
    return torch.softmax(x, dim=axis)

def _gelu(x):
    return torch.nn.functional.gelu(x, approximate='tanh')

def _silu(x):
    return torch.nn.functional.silu(x)

def _sigmoid(x):
    return torch.sigmoid(x)

def _layernorm(x, axis=-1, eps=1e-05):
    m = x.mean(dim=axis, keepdim=True)
    v = x.var(dim=axis, keepdim=True, unbiased=False)
    return (x - m) / torch.sqrt(v + eps)

def _scatter_add(tgt, idx, src, axis=0):
    return tgt.clone().index_add_(axis, idx, src)

def _segment_sum(src, seg, n):
    out = torch.zeros((n,) + src.shape[1:], dtype=src.dtype)
    return out.index_add_(0, seg, src)

def _pad(x, pw):
    flat = tuple((v for pair in reversed(pw) for v in pair))
    return torch.nn.functional.pad(x, flat)
kernel_name = 'adaLN_cond__spectral_fnet__moe_arch_mod__prompt'

def setup_inputs():

    _w = lambda a: (lambda t: t.to(torch.bfloat16) if t.is_floating_point() else t)(torch.as_tensor(a))

    def _A_setup():
        B, S, D = (1, 2048, 1024)
        ns = torch.arange(S)[:, None] * torch.arange(S)[None, :]
        nd = torch.arange(D)[:, None] * torch.arange(D)[None, :]
        Ws_re = torch.cos(-2.0 * torch.pi * ns / S).to(float)
        Ws_im = torch.sin(-2.0 * torch.pi * ns / S).to(float)
        Wd_re = torch.cos(-2.0 * torch.pi * nd / D).to(float)
        Wd_im = torch.sin(-2.0 * torch.pi * nd / D).to(float)
        return {'x': _w((lambda *s: torch.randn(*s, dtype=torch.bfloat16) * 0.1)(B, S, D)), 'dft_seq_re': _w(Ws_re), 'dft_seq_im': _w(Ws_im), 'dft_hid_re': _w(Wd_re), 'dft_hid_im': _w(Wd_im)}
    _A_in = _A_setup()

    def _B_setup():
        B, S, D, F, C = (1, 2048, 1024, 3584, 2)
        return {'x': _w((lambda *s: torch.randn(*s, dtype=torch.bfloat16) * 0.1)(B, S, D)), 'w_r': _w((lambda *s: torch.randn(*s, dtype=torch.bfloat16) * 1.6)(D)), 'w_gate': _w((lambda *s: torch.randn(*s, dtype=torch.bfloat16) * 0.8)(D, F)), 'w_up': _w((lambda *s: torch.randn(*s, dtype=torch.bfloat16) * 0.8)(D, F)), 'w_down': _w((lambda *s: torch.randn(*s, dtype=torch.bfloat16) * 0.8)(F, D))}
    _B_in = _B_setup()
    return {'A_x': _A_in['x'], 'A_dft_seq_re': _A_in['dft_seq_re'], 'A_dft_seq_im': _A_in['dft_seq_im'], 'A_dft_hid_re': _A_in['dft_hid_re'], 'A_dft_hid_im': _A_in['dft_hid_im'], 'B_x': _B_in['x'], 'B_w_r': _B_in['w_r'], 'B_w_gate': _B_in['w_gate'], 'B_w_up': _B_in['w_up'], 'B_w_down': _B_in['w_down'], 'c': _w((lambda *s: torch.randn(*s, dtype=torch.bfloat16) * 0.1)(1, 1024) * 8.0), 'w_mod': _w((lambda *s: torch.randn(*s, dtype=torch.bfloat16) * 0.1)(1024, 6 * 1024) * 1024 ** (-0.5) * 8.0)}

def reference(A_x, A_dft_seq_re, A_dft_seq_im, A_dft_hid_re, A_dft_hid_im, B_x, B_w_r, B_w_gate, B_w_up, B_w_down, c, w_mod):

    def _A_ref(x, dft_seq_re, dft_seq_im, dft_hid_re, dft_hid_im):
        a = torch.einsum('bsd,ed->bse', x, dft_hid_re)
        b = torch.einsum('bsd,ed->bse', x, dft_hid_im)
        y = torch.einsum('ts,bse->bte', dft_seq_re, a) - torch.einsum('ts,bse->bte', dft_seq_im, b)
        return y

    def _B_ref(x, w_r, w_gate, w_up, w_down):
        B, S, D = x.shape
        C = 2
        r = x @ w_r
        idx = torch.argsort(-r, axis=-1)[:, :C]
        idx_e = (lambda x, n, axis: torch.repeat_interleave(x, n, dim=axis))(idx.reshape(B, C, 1), D, axis=2)
        x_sel = (lambda x, i, axis: torch.take_along_dim(x, i, dim=axis))(x, idx_e, axis=1)
        g = _silu(x_sel @ w_gate)
        u = x_sel @ w_up
        y = g * u @ w_down
        r_sel = _sigmoid((lambda x, i, axis: torch.take_along_dim(x, i, dim=axis))(r, idx, axis=1))
        y = y * r_sel.reshape(B, C, 1)
        b_off = (torch.arange(B) * S).reshape(B, 1)
        flat_idx = (idx + b_off).reshape(B * C)
        zero = (x * 0.0).reshape(B * S, D)
        upd = _scatter_add(zero, flat_idx, y.reshape(B * C, D), axis=0)
        return x + upd.reshape(B, S, D)
    x = A_x
    mod = (_silu(c) @ w_mod).reshape(c.shape[0], 6, 1, -1)
    sa, ca, ga, sb, cb, gb = (mod[:, 0].clone(), mod[:, 1].clone(), mod[:, 2].clone(), mod[:, 3].clone(), mod[:, 4].clone(), mod[:, 5].clone())
    h = _layernorm(x, axis=-1) * (1 + ca) + sa
    x = x + ga * _A_ref(h, A_dft_seq_re, A_dft_seq_im, A_dft_hid_re, A_dft_hid_im)
    h = _layernorm(x, axis=-1) * (1 + cb) + sb
    x = x + gb * _B_ref(h, B_w_r, B_w_gate, B_w_up, B_w_down)
    return x
```

```cpp
#include <cuda_runtime.h>
#include <cuda_bf16.h>
#include <cuda.h>
#include <stdint.h>

#define DEVINL __device__ __forceinline__

namespace fk {

constexpr int S_ = 2048, D_ = 1024, F_ = 3584;
constexpr int NCTA = 128;
constexpr int NMOE = 112;
constexpr int SLOT = 16384;
constexpr int STAGE = 3 * SLOT;
constexpr int SPARE = 4 * STAGE;
constexpr int MISC = SPARE + 32768;
constexpr int SMEM_BYTES = MISC + 3072;
constexpr int BAR_OFF = MISC;
constexpr int CST_OFF = MISC + 384;
constexpr int SEL_OFF = MISC + 400;
constexpr int TOP_OFF = MISC + 416;
constexpr int T1_OFF = MISC + 512;
constexpr int RS_OFF = T1_OFF + 2048;
constexpr int GA_OFF = T1_OFF;
constexpr int W_OFF = GA_OFF + 1024;
constexpr int RECV_OFF = SLOT;
constexpr int GH_OFF = SPARE + 16384;
constexpr int TA_OFF = GH_OFF + 2048;
constexpr int TS_OFF = TA_OFF + 512;
constexpr int PART_OFF = GH_OFF + 4096;
constexpr int SCR_OFF = GH_OFF + 8192;
constexpr int OUT_OFF = 3 * STAGE;
constexpr int OUT_LD = 528;
enum { B_FULL = 0, B_EMPTY = 4, B_PRDY = 8  , B_WM = 16  , B_XR = 24  , B_STAG = 26, B_T1 = 27, B_MODOK = 28,
       B_WB = 29, B_WT = 30, B_X = 31, B_T2 = 32, B_PEER = 33, B_RECV = 34, B_GU = 35, B_XDONE = 36, B_DN = 37, B_T3 = 38, B_SEL = 39, B_NUM = 40 };

__host__ __device__ constexpr int bar_count(int i) {
  return (i >= B_EMPTY && i < B_PRDY) ? 3 : (i >= B_PRDY && i < B_WM) || i == B_WT ? 4 : (i == B_T1 || i == B_GU || i == B_DN || i == B_MODOK) ? 2 : 1;
}

#define FK_RING 4
#define FK_ROWDLY 200
#define FK_ROW0DLY 400
#define FK_WS0DLY 500
#define FK_WSDLY 300
#define FK_X2DLY 2500
#define FK_PF_SLEEP 400
#define FK_PF1 8
constexpr int SPIN_LIMIT = 1 << 22;
constexpr uint32_t SENT = 0xFFFFFFFFu;

struct Maps {
  CUtensorMap ws[2];
  CUtensorMap n;
  CUtensorMap p;
  CUtensorMap ps;
  CUtensorMap wd[2];
  CUtensorMap x;
  CUtensorMap wg, wu;
  CUtensorMap wdn;
  CUtensorMap wm;
};
struct Mail;
struct Ptrs { const char* x; char* n; unsigned* cnt; Mail* mail; uint32_t* mod; const char *c, *ws_re, *ws_im, *wd_re, *wd_im, *wr, *wg, *wu, *wdn; char* out; };

__device__ __align__(1024) __nv_bfloat16 g_n[S_ * D_];
__device__ __align__(1024) __nv_bfloat16 g_P[2 * S_ * D_];
__device__ __align__(128) uint32_t g_mod[3 * D_];
__device__ __align__(128) unsigned g_cnt[11 * 32];
struct Mail {
  uint4 stats[32 * 4 * 64];
  uint4 cand[128 * 32];
  uint4 rowh[64 * 128];
  uint4 rowx[64 * 128];
  uint4 part[128 * NMOE * 4];
  uint2 rs[2 * 16 * 128];
  unsigned flagP[512 * 8];
};
static_assert(sizeof(Mail) % (16 * NCTA) == 0, "mail size");
constexpr int MAIL_PER_CTA = sizeof(Mail) / 16 / NCTA;
__device__ __align__(1024) Mail g_mail;

#define SPIN_FAIL(what) __trap()
DEVINL uint32_t smem_u32(const void* p) { return (uint32_t)__cvta_generic_to_shared(p); }
DEVINL void mbar_init(uint32_t bar, uint32_t cnt) { asm volatile("mbarrier.init.shared::cta.b64 [%0], %1;" ::"r"(bar), "r"(cnt) : "memory"); }
DEVINL void mbar_expect_tx(uint32_t bar, uint32_t bytes) { asm volatile("mbarrier.arrive.expect_tx.shared::cta.b64 _, [%0], %1;" ::"r"(bar), "r"(bytes) : "memory"); }
DEVINL void mbar_arrive(uint32_t bar) { asm volatile("mbarrier.arrive.shared::cta.b64 _, [%0];" ::"r"(bar) : "memory"); }
DEVINL void mbar_wait(uint32_t bar, uint32_t parity) {
  asm volatile("{\n.reg .pred p;\n.reg .u32 c;\nmov.u32 c, 0;\n"
               "LW:\nmbarrier.try_wait.parity.shared::cta.b64 p, [%0], %1;\n@p bra LD;\n"
               "add.u32 c, c, 1;\nsetp.lt.u32 p, c, 4194304;\n@p bra LW;\ntrap;\nLD:\n}" ::"r"(bar), "r"(parity) : "memory");
}
DEVINL void mbar_wait_cluster(uint32_t bar, uint32_t parity) {
  asm volatile("{\n.reg .pred p;\n.reg .u32 c;\nmov.u32 c, 0;\n"
               "LW:\nmbarrier.try_wait.parity.acquire.cluster.shared::cta.b64 p, [%0], %1;\n@p bra LD;\n"
               "add.u32 c, c, 1;\nsetp.lt.u32 p, c, 4194304;\n@p bra LW;\ntrap;\nLD:\n}" ::"r"(bar), "r"(parity) : "memory");
}
DEVINL void fence_async_smem() { asm volatile("fence.proxy.async.shared::cta;" ::: "memory"); }
DEVINL void fence_async_global() { asm volatile("fence.proxy.async.global;" ::: "memory"); }
DEVINL void fence_gpu() { asm volatile("fence.acq_rel.gpu;" ::: "memory"); }
template <int ID, int N> DEVINL void named_bar() { asm volatile("bar.sync %0, %1;" ::"n"(ID), "n"(N) : "memory"); }
template <int ID, int N> DEVINL void named_arrive() { asm volatile("bar.arrive %0, %1;" ::"n"(ID), "n"(N) : "memory"); }

DEVINL void tma_2d(uint32_t dst, const CUtensorMap* m, int x, int y, uint32_t bar) {
  asm volatile("cp.async.bulk.tensor.2d.shared::cluster.global.mbarrier::complete_tx::bytes [%0], [%1, {%3, %4}], [%2];"
               ::"r"(dst), "l"(m), "r"(bar), "r"(x), "r"(y) : "memory");
}
DEVINL void tma_2d_hint(uint32_t dst, const CUtensorMap* m, int x, int y, uint32_t bar, uint64_t pol) {
  asm volatile("cp.async.bulk.tensor.2d.shared::cluster.global.mbarrier::complete_tx::bytes.L2::cache_hint [%0], [%1, {%3, %4}], [%2], %5;"
               ::"r"(dst), "l"(m), "r"(bar), "r"(x), "r"(y), "l"(pol) : "memory");
}
DEVINL void tma_3d(uint32_t dst, const CUtensorMap* m, int x, int y, int z, uint32_t bar) {
  asm volatile("cp.async.bulk.tensor.3d.shared::cluster.global.mbarrier::complete_tx::bytes [%0], [%1, {%3, %4, %5}], [%2];"
               ::"r"(dst), "l"(m), "r"(bar), "r"(x), "r"(y), "r"(z) : "memory");
}
DEVINL void tma_store_2d(const CUtensorMap* m, uint32_t src, int x, int y) {
  asm volatile("cp.async.bulk.tensor.2d.global.shared::cta.bulk_group [%0, {%2, %3}], [%1];" ::"l"(m), "r"(src), "r"(x), "r"(y) : "memory");
}
DEVINL void bulk_load(uint32_t dst, const void* src, uint32_t bytes, uint32_t bar) {
  asm volatile("cp.async.bulk.shared::cluster.global.mbarrier::complete_tx::bytes [%0], [%1], %2, [%3];" ::"r"(dst), "l"(src), "r"(bytes), "r"(bar) : "memory");
}
DEVINL void bulk_store(void* dst, uint32_t src, uint32_t bytes) {
  asm volatile("cp.async.bulk.global.shared::cta.bulk_group [%0], [%1], %2;" ::"l"(dst), "r"(src), "r"(bytes) : "memory");
}
DEVINL void pf_bulk(const void* p, uint32_t bytes) { asm volatile("cp.async.bulk.prefetch.L2.global [%0], %1;" ::"l"(p), "r"(bytes) : "memory"); }
DEVINL void bulk_commit() { asm volatile("cp.async.bulk.commit_group;" ::: "memory"); }
template <int N> DEVINL void bulk_wait() { asm volatile("cp.async.bulk.wait_group %0;" ::"n"(N) : "memory"); }
template <int N> DEVINL void bulk_wait_read() { asm volatile("cp.async.bulk.wait_group.read %0;" ::"n"(N) : "memory"); }
DEVINL void prefetch_tmap(const CUtensorMap* m) { asm volatile("prefetch.tensormap [%0];" ::"l"(m) : "memory"); }

DEVINL void wg_fence() { asm volatile("wgmma.fence.sync.aligned;" ::: "memory"); }
DEVINL void wg_commit() { asm volatile("wgmma.commit_group.sync.aligned;" ::: "memory"); }
template <int N> DEVINL void wg_wait() { asm volatile("wgmma.wait_group.sync.aligned %0;" ::"n"(N) : "memory"); }

DEVINL uint64_t make_desc(uint32_t addr, uint32_t lbo, uint32_t sbo) {
  return (uint64_t)((addr & 0x3FFFF) >> 4) | ((uint64_t)(lbo >> 4) << 16) | ((uint64_t)(sbo >> 4) << 32) | ((uint64_t)1 << 62);
}

#define R8(a, o) "+f"(a[o]), "+f"(a[o + 1]), "+f"(a[o + 2]), "+f"(a[o + 3]), "+f"(a[o + 4]), "+f"(a[o + 5]), "+f"(a[o + 6]), "+f"(a[o + 7])
#define R128(a) R8(a, 0), R8(a, 8), R8(a, 16), R8(a, 24), R8(a, 32), R8(a, 40), R8(a, 48), R8(a, 56), \
                R8(a, 64), R8(a, 72), R8(a, 80), R8(a, 88), R8(a, 96), R8(a, 104), R8(a, 112), R8(a, 120)
template <int TB>
DEVINL void wgmma_n256(float (&d)[128], uint64_t da, uint64_t db, int scale_d) {
  asm volatile(
      "{\n.reg .pred p;\nsetp.ne.b32 p, %130, 0;\n"
      "wgmma.mma_async.sync.aligned.m64n256k16.f32.bf16.bf16 "
      "{%0, %1, %2, %3, %4, %5, %6, %7, %8, %9, %10, %11, %12, %13, %14, %15, "
      "%16, %17, %18, %19, %20, %21, %22, %23, %24, %25, %26, %27, %28, %29, %30, %31, "
      "%32, %33, %34, %35, %36, %37, %38, %39, %40, %41, %42, %43, %44, %45, %46, %47, "
      "%48, %49, %50, %51, %52, %53, %54, %55, %56, %57, %58, %59, %60, %61, %62, %63, "
      "%64, %65, %66, %67, %68, %69, %70, %71, %72, %73, %74, %75, %76, %77, %78, %79, "
      "%80, %81, %82, %83, %84, %85, %86, %87, %88, %89, %90, %91, %92, %93, %94, %95, "
      "%96, %97, %98, %99, %100, %101, %102, %103, %104, %105, %106, %107, %108, %109, %110, %111, "
      "%112, %113, %114, %115, %116, %117, %118, %119, %120, %121, %122, %123, %124, %125, %126, %127}, "
      "%128, %129, p, 1, 1, 0, %131;\n}\n"
      : R128(d)
      : "l"(da), "l"(db), "r"(scale_d), "n"(TB));
}
DEVINL void reg_fence128(float (&a)[128]) {
#pragma unroll
  for (int i = 0; i < 128; i++) asm volatile("" : "+f"(a[i])::"memory");
}

DEVINL uint32_t pack_bf16(float lo, float hi) {
  uint32_t r;
  asm("cvt.rn.bf16x2.f32 %0, %1, %2;" : "=r"(r) : "f"(hi), "f"(lo));
  return r;
}
DEVINL float bf_lo(uint32_t w) { return __uint_as_float(w << 16); }
DEVINL float bf_hi(uint32_t w) { return __uint_as_float(w & 0xFFFF0000u); }
DEVINL float round_bf16(float v) { return __bfloat162float(__float2bfloat16_rn(v)); }
DEVINL float sigmoid_f(float v) { float r; asm("rcp.approx.ftz.f32 %0, %1;" : "=f"(r) : "f"(1.f + __expf(-v))); return r; }
DEVINL float silu_f(float v) { return v * sigmoid_f(v); }
DEVINL void stsm_x4(uint32_t addr, uint32_t r0, uint32_t r1, uint32_t r2, uint32_t r3) {
  asm volatile("stmatrix.sync.aligned.m8n8.x4.shared.b16 [%0], {%1, %2, %3, %4};" ::"r"(addr), "r"(r0), "r"(r1), "r"(r2), "r"(r3) : "memory");
}
DEVINL void ldsm_x4(uint32_t addr, uint32_t& r0, uint32_t& r1, uint32_t& r2, uint32_t& r3) {
  asm volatile("ldmatrix.sync.aligned.m8n8.x4.shared.b16 {%0, %1, %2, %3}, [%4];" : "=r"(r0), "=r"(r1), "=r"(r2), "=r"(r3) : "r"(addr) : "memory");
}
DEVINL void ldsm_x4_t(uint32_t addr, uint32_t& r0, uint32_t& r1, uint32_t& r2, uint32_t& r3) {
  asm volatile("ldmatrix.sync.aligned.m8n8.x4.trans.shared.b16 {%0, %1, %2, %3}, [%4];" : "=r"(r0), "=r"(r1), "=r"(r2), "=r"(r3) : "r"(addr) : "memory");
}
DEVINL void mma_16816(float (&c)[4], uint32_t a0, uint32_t a1, uint32_t a2, uint32_t a3, uint32_t b0, uint32_t b1) {
  asm("mma.sync.aligned.m16n8k16.row.col.f32.bf16.bf16.f32 {%0, %1, %2, %3}, {%4, %5, %6, %7}, {%8, %9}, {%0, %1, %2, %3};"
      : "+f"(c[0]), "+f"(c[1]), "+f"(c[2]), "+f"(c[3]) : "r"(a0), "r"(a1), "r"(a2), "r"(a3), "r"(b0), "r"(b1));
}
DEVINL void mma_1688(float (&c)[4], uint32_t a0, uint32_t a1, uint32_t b0) {
  asm("mma.sync.aligned.m16n8k8.row.col.f32.bf16.bf16.f32 {%0, %1, %2, %3}, {%4, %5}, {%6}, {%0, %1, %2, %3};"
      : "+f"(c[0]), "+f"(c[1]), "+f"(c[2]), "+f"(c[3]) : "r"(a0), "r"(a1), "r"(b0));
}
DEVINL float4 lds128(uint32_t a) { float4 v; asm volatile("ld.shared.v4.f32 {%0, %1, %2, %3}, [%4];" : "=f"(v.x), "=f"(v.y), "=f"(v.z), "=f"(v.w) : "r"(a)); return v; }
DEVINL uint4 lds128u(uint32_t a) { uint4 v; asm volatile("ld.shared.v4.u32 {%0, %1, %2, %3}, [%4];" : "=r"(v.x), "=r"(v.y), "=r"(v.z), "=r"(v.w) : "r"(a)); return v; }
DEVINL float2 lds64(uint32_t a) { float2 v; asm volatile("ld.shared.v2.f32 {%0, %1}, [%2];" : "=f"(v.x), "=f"(v.y) : "r"(a)); return v; }
DEVINL float lds32(uint32_t a) { float v; asm volatile("ld.shared.f32 %0, [%1];" : "=f"(v) : "r"(a)); return v; }
DEVINL float lds16f(uint32_t a) { uint32_t v; asm volatile("ld.shared.u16 %0, [%1];" : "=r"(v) : "r"(a)); return __uint_as_float(v << 16); }
DEVINL uint32_t lds32u(uint32_t a) { uint32_t v; asm volatile("ld.shared.u32 %0, [%1];" : "=r"(v) : "r"(a)); return v; }
DEVINL void sts128(uint32_t a, float x, float y, float z, float w) { asm volatile("st.shared.v4.f32 [%0], {%1, %2, %3, %4};" ::"r"(a), "f"(x), "f"(y), "f"(z), "f"(w) : "memory"); }
DEVINL void sts128u(uint32_t a, uint32_t x, uint32_t y, uint32_t z, uint32_t w) { asm volatile("st.shared.v4.u32 [%0], {%1, %2, %3, %4};" ::"r"(a), "r"(x), "r"(y), "r"(z), "r"(w) : "memory"); }
DEVINL void sts64(uint32_t a, float x, float y) { asm volatile("st.shared.v2.f32 [%0], {%1, %2};" ::"r"(a), "f"(x), "f"(y) : "memory"); }
DEVINL void sts32(uint32_t a, float v) { asm volatile("st.shared.f32 [%0], %1;" ::"r"(a), "f"(v) : "memory"); }
DEVINL void sts32u(uint32_t a, uint32_t v) { asm volatile("st.shared.u32 [%0], %1;" ::"r"(a), "r"(v) : "memory"); }

DEVINL uint4 ld_msg(const uint4* p) {
  unsigned long long a, b;
  asm volatile("{\n.reg .b128 r;\nld.relaxed.gpu.global.b128 r, [%2];\nmov.b128 {%0, %1}, r;\n}" : "=l"(a), "=l"(b) : "l"(p) : "memory");
  return make_uint4((uint32_t)a, (uint32_t)(a >> 32), (uint32_t)b, (uint32_t)(b >> 32));
}
DEVINL void st_msg(uint4* p, uint32_t x, uint32_t y, uint32_t z, uint32_t w) {
  unsigned long long a = (unsigned long long)x | ((unsigned long long)y << 32), b = (unsigned long long)z | ((unsigned long long)w << 32);
  asm volatile("{\n.reg .b128 r;\nmov.b128 r, {%1, %2};\nst.relaxed.gpu.global.b128 [%0], r;\n}" ::"l"(p), "l"(a), "l"(b) : "memory");
}
DEVINL uint2 ld_msg8(const void* p) {
  unsigned long long a;
  asm volatile("ld.relaxed.gpu.global.b64 %0, [%1];" : "=l"(a) : "l"(p) : "memory");
  return make_uint2((uint32_t)a, (uint32_t)(a >> 32));
}
DEVINL void st_msg8(uint2* p, uint32_t x, uint32_t y) {
  asm volatile("st.relaxed.gpu.global.b64 [%0], %1;" ::"l"(p), "l"((unsigned long long)x | ((unsigned long long)y << 32)) : "memory");
}
DEVINL unsigned ld_rlx(const void* p) { unsigned v; asm volatile("ld.relaxed.gpu.global.u32 %0, [%1];" : "=r"(v) : "l"(p) : "memory"); return v; }
DEVINL void st_rlx(unsigned* p, unsigned v) { asm volatile("st.relaxed.gpu.global.u32 [%0], %1;" ::"l"(p), "r"(v) : "memory"); }
DEVINL void red_add(unsigned* p, unsigned v) { asm volatile("red.relaxed.gpu.global.add.u32 [%0], %1;" ::"l"(p), "r"(v) : "memory"); }
DEVINL void red_add_release(unsigned* p, unsigned v) { asm volatile("red.release.gpu.global.add.u32 [%0], %1;" ::"l"(p), "r"(v) : "memory"); }
DEVINL uint4 ldg_nc(const void* p) {
  uint4 v;
  asm volatile("ld.global.nc.L1::no_allocate.v4.u32 {%0, %1, %2, %3}, [%4];" : "=r"(v.x), "=r"(v.y), "=r"(v.z), "=r"(v.w) : "l"(p));
  return v;
}
DEVINL void stg128(void* p, uint4 v) { asm volatile("st.global.v4.u32 [%0], {%1, %2, %3, %4};" ::"l"(p), "r"(v.x), "r"(v.y), "r"(v.z), "r"(v.w) : "memory"); }
DEVINL void delay_until(uint32_t c0, uint32_t cycles) { while ((uint32_t)clock() - c0 < cycles) {} }

#define TRACE(id)
#define TRACE_CLK(id)

DEVINL void prefetch_piece(const Ptrs& pp, int b, int i) {
  if (i < 4) pf_bulk((b < 64 ? pp.wd_re : pp.wd_im) + (size_t)(b & 63) * 32768 + i * 8192, 8192);
  else if (i < 12) pf_bulk((i < 8 ? pp.wg : pp.wu) + (size_t)512 * F_ * 2 + (size_t)b * 28672 + (i & 3) * 7168, 7168);
  else pf_bulk(pp.wdn + (size_t)b * 57344 + (i - 12) * 8192, 8192);
}

DEVINL uint32_t fkey(float v) { const uint32_t u = __float_as_uint(v); return (u & 0x80000000u) ? ~u : (u | 0x80000000u); }
DEVINL float fkey_inv(uint32_t k) { return __uint_as_float((k & 0x80000000u) ? (k & 0x7FFFFFFFu) : ~k); }
DEVINL uint32_t redux_max(uint32_t v) { uint32_t r; asm volatile("redux.sync.max.u32 %0, %1, 0xffffffff;" : "=r"(r) : "r"(v)); return r; }
DEVINL void warp_top2(uint32_t ka, int ia, uint32_t kb, int ib, uint32_t& k1, int& i1, uint32_t& k2, int& i2) {
  const int lane = threadIdx.x & 31;
  k1 = redux_max(ka);
  const int l1 = __ffs(__ballot_sync(~0u, ka == k1)) - 1;
  const uint32_t kc = lane == l1 ? kb : ka;
  const int ic = lane == l1 ? ib : ia;
  k2 = redux_max(kc);
  const int l2 = __ffs(__ballot_sync(~0u, kc == k2)) - 1;
  i1 = __shfl_sync(~0u, ia, l1);
  i2 = __shfl_sync(~0u, ic, l2);
}

DEVINL void ln_row(uint4 (&w)[4]) {
  float v[32];
#pragma unroll
  for (int i = 0; i < 4; i++) {
    v[8 * i + 0] = bf_lo(w[i].x); v[8 * i + 1] = bf_hi(w[i].x); v[8 * i + 2] = bf_lo(w[i].y); v[8 * i + 3] = bf_hi(w[i].y);
    v[8 * i + 4] = bf_lo(w[i].z); v[8 * i + 5] = bf_hi(w[i].z); v[8 * i + 6] = bf_lo(w[i].w); v[8 * i + 7] = bf_hi(w[i].w);
  }
  float s[4] = {0.f, 0.f, 0.f, 0.f}, q[4] = {0.f, 0.f, 0.f, 0.f};
#pragma unroll
  for (int i = 0; i < 32; i++) { s[i & 3] += v[i]; q[i & 3] = fmaf(v[i], v[i], q[i & 3]); }
  float sum = (s[0] + s[1]) + (s[2] + s[3]), sq = (q[0] + q[1]) + (q[2] + q[3]);
#pragma unroll
  for (int o = 16; o; o >>= 1) { sum += __shfl_xor_sync(~0u, sum, o); sq += __shfl_xor_sync(~0u, sq, o); }
  const float mean = sum * (1.f / D_);
  const float rstd = rsqrtf(fmaxf(fmaf(-mean, mean, sq * (1.f / D_)), 0.f) + 1e-5f), nmr = -mean * rstd;
#pragma unroll
  for (int i = 0; i < 4; i++) {
    w[i].x = pack_bf16(fmaf(v[8 * i], rstd, nmr), fmaf(v[8 * i + 1], rstd, nmr)); w[i].y = pack_bf16(fmaf(v[8 * i + 2], rstd, nmr), fmaf(v[8 * i + 3], rstd, nmr));
    w[i].z = pack_bf16(fmaf(v[8 * i + 4], rstd, nmr), fmaf(v[8 * i + 5], rstd, nmr)); w[i].w = pack_bf16(fmaf(v[8 * i + 6], rstd, nmr), fmaf(v[8 * i + 7], rstd, nmr));
  }
}
DEVINL float sum8(uint4 u) { return ((bf_lo(u.x) + bf_hi(u.x)) + (bf_lo(u.y) + bf_hi(u.y))) + ((bf_lo(u.z) + bf_hi(u.z)) + (bf_lo(u.w) + bf_hi(u.w))); }

template <int R> DEVINL void take_box(uint32_t (&wf)[128], uint32_t box, int lane) {
  const int kr = (lane & 7) + (lane >> 4) * 8;
  const uint32_t base = box + kr * 64, sw = (uint32_t)((kr >> 1) & 3), hb = (uint32_t)((lane >> 3) & 1);
#pragma unroll
  for (int mt = 0; mt < 2; mt++) {
    const uint32_t ad = base + (((mt * 2 + hb) ^ sw) << 4);
#pragma unroll
    for (int ks = 0; ks < 8; ks++) {
      const int o = (ks * 4 + R * 2 + mt) * 4;
      ldsm_x4_t(ad + ks * 1024, wf[o], wf[o + 1], wf[o + 2], wf[o + 3]);
    }
  }
}
DEVINL void gate_up(const Ptrs& pp, uint32_t (&wf)[128], uint32_t sb, int ksl, int lane) {
  const uint4 sel = lds128u(sb + SEL_OFF);
  const int gq = lane >> 2, q4 = lane & 3;
  const int bA = (int)sel.x >> 6, bB = (int)sel.y >> 6;
  const uint4* src = &pp.mail->rowh[((gq & 1) ? bB * 2 + (bA == bB ? 1 : 0) : bA * 2) * 128 + ksl * 16 + q4];
  uint4 bf[4];
  int it = 0;
  while (true) {
#pragma unroll
    for (int u = 0; u < 4; u++) bf[u] = ld_msg(src + u * 4);
    if (__all_sync(~0u, bf[0].x != SENT && bf[1].x != SENT && bf[2].x != SENT && bf[3].x != SENT)) break;
    if (++it > SPIN_LIMIT) SPIN_FAIL(0x207);
  }
  if (lane == 0 && ksl == 4) TRACE(20);
  float acc[8][4];
#pragma unroll
  for (int i = 0; i < 8; i++) { acc[i][0] = acc[i][1] = acc[i][2] = acc[i][3] = 0.f; }
#pragma unroll
  for (int u = 0; u < 4; u++)
#pragma unroll
    for (int mt = 0; mt < 4; mt++) {
      const int o = (2 * u * 4 + mt) * 4;
      mma_16816(acc[mt], wf[o], wf[o + 1], wf[o + 2], wf[o + 3], bf[u].x, bf[u].y);
      mma_16816(acc[4 + mt], wf[o + 16], wf[o + 17], wf[o + 18], wf[o + 19], bf[u].z, bf[u].w);
    }
  if (q4 == 0) {
    const uint32_t pb = sb + PART_OFF + ksl * 512 + gq * 8;
#pragma unroll
    for (int mt = 0; mt < 4; mt++) {
      sts64(pb + mt * 128, acc[mt][0] + acc[4 + mt][0], acc[mt][1] + acc[4 + mt][1]);
      sts64(pb + mt * 128 + 64, acc[mt][2] + acc[4 + mt][2], acc[mt][3] + acc[4 + mt][3]);
    }
  }
  named_arrive<4, 384>();
}

template <int TB, int G0, int G1>
DEVINL void gemm_phase(float (&acc)[128], uint32_t sb, int cw, bool lag, bool elect) {
  const uint32_t bars = sb + BAR_OFF;
#pragma unroll 1
  for (int g = G0; g < G1; g++) {
    const int s = g & 3;
    mbar_wait(bars + (B_FULL + s) * 8, (g >> 2) & 1);
    const bool hold = lag && g == G1 - 2;
    if (hold) {
      wg_wait<0>();
      if (elect) mbar_arrive(bars + (B_EMPTY + ((g - 1) & 3)) * 8);
      mbar_wait(bars + B_STAG * 8, TB ? 0 : 1);
    }
    const uint32_t sa = sb + s * STAGE;
    const uint64_t da = make_desc(sa + cw * 8192, 16, 1024), db = make_desc(sa + SLOT, TB ? 8192 : 16, 1024);
    constexpr int KB = TB ? 128 : 2;
    wg_fence();
    wgmma_n256<TB>(acc, da, db, g > G0);
    wgmma_n256<TB>(acc, da + 2, db + KB, 1);
    wg_commit();
    wg_wait<1>();
    if (elect && g > G0 && !hold) mbar_arrive(bars + (B_EMPTY + ((g - 1) & 3)) * 8);
    wg_fence();
    wgmma_n256<TB>(acc, da + 4, db + 2 * KB, 1);
    wgmma_n256<TB>(acc, da + 6, db + 3 * KB, 1);
    wg_commit();
  }
  if (!lag) { wg_wait<1>(); if (elect) mbar_arrive(bars + B_STAG * 8); }
}
DEVINL void gemm_finish(float (&acc)[128], uint32_t sb, bool elect) {
  wg_wait<0>();
  reg_fence128(acc);
  if (elect) mbar_arrive(sb + BAR_OFF + (B_EMPTY + 3) * 8);
}

__global__ void __launch_bounds__(384, 1)
fused_kernel(const Ptrs pp, const __grid_constant__ Maps maps) {
  extern __shared__ __align__(1024) uint8_t smem_raw[];
  const uint32_t c0 = (uint32_t)clock();
  if (threadIdx.x == 0) TRACE(0);
  const uint32_t sb = smem_u32(smem_raw);
  const int tid = threadIdx.x, lane = tid & 31;
  const int warp = __shfl_sync(~0u, tid >> 5, 0);
  const int b = blockIdx.x;
  const int j = b & 1, m4 = (b >> 1) & 3, t = b >> 3;
  const int blk = t * 2 + j;
  const uint32_t bars = sb + BAR_OFF;
  auto BAR = [&](int i) { return bars + i * 8; };

  uint4 xr[4];
  const uint4* xsrc = reinterpret_cast<const uint4*>(pp.x + (size_t)((warp - 4) * 128 + b) * (2 * D_)) + lane;
  if (warp == 4) {
#pragma unroll
    for (int i = 0; i < 4; i++) xr[i] = ldg_nc(xsrc + 32 * i);
  }
  uint32_t tag = ld_rlx(&pp.cnt[10 * 32]);

  if (warp < 4) {
    if (lane == 0) {
      if (warp == 0) {
        prefetch_tmap(&maps.ws[j]); prefetch_tmap(&maps.n);
        if (sb & 1023) __trap();
#pragma unroll
        for (int i = 0; i < 10; i++) mbar_init(BAR(i), bar_count(i));
      } else if (warp == 1) {
#pragma unroll
        for (int i = 10; i < 20; i++) mbar_init(BAR(i), bar_count(i));
      } else if (warp == 2) {
#pragma unroll
        for (int i = 20; i < 30; i++) mbar_init(BAR(i), bar_count(i));
      } else {
#pragma unroll
        for (int i = 30; i < B_NUM; i++) mbar_init(BAR(i), bar_count(i));
        mbar_expect_tx(BAR(B_RECV), 32768);
      }
      asm volatile("fence.mbarrier_init.release.cluster;" ::: "memory");
    }
    named_bar<6, 128>();
    named_arrive<0, 384>();
    asm volatile("barrier.cluster.arrive.relaxed.aligned;" ::: "memory");
    uint64_t pol_first;
    asm volatile("createpolicy.fractional.L2::evict_first.b64 %0, 1.0;" : "=l"(pol_first));
    const bool moe = b < NMOE;
    if (warp == 0) {
      delay_until(c0, FK_WS0DLY);
      const uint32_t c1 = (uint32_t)clock();
      if (lane == 0) {
        mbar_expect_tx(BAR(B_FULL), STAGE);
        tma_2d_hint(sb, &maps.ws[j], 0, t * 128, BAR(B_FULL), pol_first);
      }
      const unsigned* cnt = &pp.cnt[(lane < 9 ? lane : 0) * 32];
      asm volatile("add.u32 %0, %0, 1;" : "+r"(tag)::"memory");
      const unsigned tgt = tag * (lane == 8 ? 256u : 128u);
      unsigned ready = 0;
      int nA = 1;
#pragma unroll 1
      for (int g = 0; g < 32; g++) {
        const int s = g & 3, need = g < 16 ? g >> 1 : 8;
        if (g >= 4) {
          mbar_wait(BAR(B_EMPTY + s), ((g >> 2) - 1) & 1);
          if (lane == 0) {
            mbar_expect_tx(BAR(B_FULL + s), STAGE);
            tma_2d_hint(sb + s * STAGE, &maps.ws[j], g * 64, t * 128, BAR(B_FULL + s), pol_first);
            if (g >= 28) mbar_arrive(BAR(B_EMPTY + s));
          }
        }
        int it = 0;
        while ((nA <= g && g < 4) || !((ready >> need) & 1)) {
          if (nA < 4 && (uint32_t)clock() - c1 >= (uint32_t)nA * FK_WSDLY) {
            if (lane == 0) {
              mbar_expect_tx(BAR(B_FULL + nA), STAGE);
              tma_2d_hint(sb + nA * STAGE, &maps.ws[j], nA * 64, t * 128, BAR(B_FULL + nA), pol_first);
            }
            nA++;
          }
          ready = __ballot_sync(~0u, (int)(ld_rlx(cnt) - tgt) >= 0);
          if (++it > SPIN_LIMIT) SPIN_FAIL(0x201);
        }
        if (it) fence_async_global();
        if (lane == 0) {
          if (g == 0) TRACE(2);
          tma_3d(sb + s * STAGE + SLOT, &maps.n, 0, g * 64, m4 * 4, BAR(B_FULL + s));
          if (g == 3) { prefetch_tmap(&maps.p); prefetch_tmap(&maps.wd[j]); prefetch_tmap(&maps.ps); }
        }
        __syncwarp();
      }
    } else if (warp == 1) {
      asm volatile("add.u32 %0, %0, 1;" : "+r"(tag)::"memory");
      const uint32_t rb = sb + (m4 * 32 + lane) * 128;
      float a0 = 0.f, a1 = 0.f;
#pragma unroll 1
      for (int g = 0; g < 28; g++) {
        const int s = g & 3;
        mbar_wait(BAR(B_FULL + s), (g >> 2) & 1);
        uint4 u[8];
#pragma unroll
        for (int c = 0; c < 8; c++) u[c] = lds128u(rb + s * STAGE + (uint32_t)((c ^ (lane & 7)) << 4));
#pragma unroll
        for (int c = 0; c < 8; c += 2) { a0 += sum8(u[c]); a1 += sum8(u[c + 1]); }
        asm volatile("" ::"f"(a0), "f"(a1) : "memory");
        __syncwarp();
        if (lane == 0) mbar_arrive(BAR(B_EMPTY + s));
      }
      mbar_wait(BAR(B_MODOK), 0);
      a0 += lds32(sb + RS_OFF + 256 + lane * 4);
      __syncwarp();
      uint2* rsp = &pp.mail->rs[(j * 16 + t) * 128 + lane];
      st_msg8(rsp + m4 * 32, __float_as_uint(a0 + a1), tag);
      uint2 m[4]; int it = 0;
      while (true) {
#pragma unroll
        for (int i = 0; i < 4; i++) m[i] = ld_msg8(rsp + 32 * i);
        if (__all_sync(~0u, m[0].y == tag && m[1].y == tag && m[2].y == tag && m[3].y == tag)) break;
        if (++it > SPIN_LIMIT) SPIN_FAIL(0x208);
      }
#pragma unroll
      for (int i = 0; i < 4; i++) sts32u(sb + RS_OFF + (lane + 32 * i) * 4, m[i].x);
      __syncwarp();
      if (lane == 0) { mbar_arrive(BAR(B_T1)); TRACE(11); }
    } else {
      const int kh = warp - 2;
      asm volatile("add.u32 %0, %0, 1;" : "+r"(tag)::"memory");
      const uint32_t reg = sb + SPARE + kh * 16384;
      {
        const size_t roff = (size_t)((8 + kh * 4) * 128 + b) * (2 * D_);
        delay_until(c0, FK_X2DLY);
        if (lane == 0) {
          mbar_expect_tx(BAR(B_XR + kh), 8192);
#pragma unroll 1
          for (int i = 0; i < 4; i++) bulk_load(reg + i * 2048, pp.x + roff + (size_t)i * (128 * 2 * D_), 2048, BAR(B_XR + kh));
          prefetch_tmap(&maps.wm);
        }
#pragma unroll 1
        for (int i = 0; i < 2; i++) {
          const uint4 cw4 = ldg_nc(pp.c + (kh * 64 + lane + 32 * i) * 16);
          sts128u(sb + T1_OFF + (kh * 64 + lane + 32 * i) * 16, pack_bf16(silu_f(bf_lo(cw4.x)), silu_f(bf_hi(cw4.x))), pack_bf16(silu_f(bf_lo(cw4.y)), silu_f(bf_hi(cw4.y))),
                  pack_bf16(silu_f(bf_lo(cw4.z)), silu_f(bf_hi(cw4.z))), pack_bf16(silu_f(bf_lo(cw4.w)), silu_f(bf_hi(cw4.w))));
        }
        mbar_wait(BAR(B_XR + kh), 0);
#pragma unroll 1
        for (int r = 0; r < 4; r++) {
          uint4 w[4];
#pragma unroll
          for (int i = 0; i < 4; i++) w[i] = lds128u(reg + r * 2048 + lane * 16 + i * 512);
          ln_row(w);
#pragma unroll
          for (int i = 0; i < 4; i++) sts128u(reg + r * 2048 + lane * 16 + i * 512, w[i].x, w[i].y, w[i].z, w[i].w);
          fence_async_smem();
          __syncwarp();
          if (lane == 0) bulk_store(pp.n + roff + (size_t)r * (128 * 2 * D_), reg + r * 2048, 2048);
        }
        if (lane == 0) {
          bulk_commit(); bulk_wait<0>();
          red_add(&pp.cnt[8 * 32], 1);
          if (kh == 0) TRACE(28);
          mbar_wait(BAR(B_EMPTY), 0);
#pragma unroll 1
          for (int i = 0; i < FK_RING; i++) {
            mbar_expect_tx(BAR(B_WM + kh * 4 + i), 3072);
            tma_2d_hint(reg + i * 3072, &maps.wm, b * 48, kh * 512 + i * 32, BAR(B_WM + kh * 4 + i), pol_first);
          }
        }
        __syncwarp();
      }
      {
        uint4* mb = reinterpret_cast<uint4*>(pp.mail) + (size_t)b * MAIL_PER_CTA;
#pragma unroll 1
        for (int i = tid - 64; i < MAIL_PER_CTA; i += 64) stg128(mb + i, make_uint4(SENT, SENT, SENT, SENT));
      }
      {
        const int rr = lane / 6;
        const uint32_t woff = lane < 24 ? lane * 16 : 0, sbase = sb + T1_OFF + kh * 1024 + (rr & 3) * 2;
        float acc[8];
#pragma unroll
        for (int i = 0; i < 8; i++) acc[i] = 0.f;
        int sl = 0, ph = 0;
#pragma unroll 1
        for (int c = 0; c < 16; c++) {
          mbar_wait(BAR(B_WM + kh * 4 + sl), ph);
          uint4 v[8]; float sv[8];
#pragma unroll
          for (int u = 0; u < 8; u++) { v[u] = lds128u(reg + sl * 3072 + woff + u * 384); sv[u] = lds16f(sbase + (c * 32 + u * 4) * 2); }
#pragma unroll
          for (int u = 0; u < 8; u++) {
            const float sc = sv[u];
            acc[0] = fmaf(sc, bf_lo(v[u].x), acc[0]); acc[1] = fmaf(sc, bf_hi(v[u].x), acc[1]);
            acc[2] = fmaf(sc, bf_lo(v[u].y), acc[2]); acc[3] = fmaf(sc, bf_hi(v[u].y), acc[3]);
            acc[4] = fmaf(sc, bf_lo(v[u].z), acc[4]); acc[5] = fmaf(sc, bf_hi(v[u].z), acc[5]);
            acc[6] = fmaf(sc, bf_lo(v[u].w), acc[6]); acc[7] = fmaf(sc, bf_hi(v[u].w), acc[7]);
          }
          asm volatile("" ::"f"(acc[0]), "f"(acc[7]) : "memory");
          __syncwarp();
          if (lane == 0 && c + FK_RING < 16) {
            mbar_expect_tx(BAR(B_WM + kh * 4 + sl), 3072);
            tma_2d_hint(reg + sl * 3072, &maps.wm, b * 48, kh * 512 + (c + FK_RING) * 32, BAR(B_WM + kh * 4 + sl), pol_first);
          }
          if (++sl == FK_RING) { sl = 0; ph ^= 1; }
        }
#pragma unroll
        for (int i = 0; i < 8; i++) { acc[i] += __shfl_down_sync(~0u, acc[i], 12); acc[i] += __shfl_down_sync(~0u, acc[i], 6); }
        if (kh == 0 && lane < 6) { sts128(sb + RS_OFF + lane * 32, acc[0], acc[1], acc[2], acc[3]); sts128(sb + RS_OFF + lane * 32 + 16, acc[4], acc[5], acc[6], acc[7]); }
        named_bar<5, 64>();
        if (kh == 1 && lane < 6) {
          const float4 p0 = lds128(sb + RS_OFF + lane * 32), p1 = lds128(sb + RS_OFF + lane * 32 + 16);
          stg128(pp.mod + b * 24 + lane * 4, make_uint4(pack_bf16(acc[0] + p0.x, acc[1] + p0.y), pack_bf16(acc[2] + p0.z, acc[3] + p0.w),
                                                       pack_bf16(acc[4] + p1.x, acc[5] + p1.y), pack_bf16(acc[6] + p1.z, acc[7] + p1.w)));
        }
        __syncwarp();
        if (lane == 0) { red_add_release(&pp.cnt[9 * 32], 1); if (kh) TRACE(9); }
      }
      if (kh == 0) {
        if (lane == 0) {
          if (moe) {
            mbar_expect_tx(BAR(B_WB), 32768);
#pragma unroll 1
            for (int i = 0; i < 4; i++) { tma_2d_hint(sb + SPARE + i * 8192, &maps.wg, b * 32, i * 128, BAR(B_WB), pol_first); __nanosleep(FK_PF_SLEEP); }
          } else mbar_arrive(BAR(B_WB));
        }
        __syncwarp();
        const char* wsrc = (j ? pp.ws_im : pp.ws_re) + (size_t)(t * 128 + m4 * 32) * (2 * S_) + 28 * 128 + lane * 16;
#pragma unroll 1
        for (int r0 = 0; r0 < 32; r0 += 8) {
          uint4 e[8]; float v[8];
#pragma unroll
          for (int i = 0; i < 8; i++) e[i] = ldg_nc(wsrc + (size_t)(r0 + i) * (2 * S_));
#pragma unroll
          for (int i = 0; i < 8; i++) v[i] = sum8(e[i]);
#pragma unroll
          for (int i = 0; i < 4; i++) v[i] = ((lane & 16) ? v[4 + i] : v[i]) + __shfl_xor_sync(~0u, (lane & 16) ? v[i] : v[4 + i], 16);
#pragma unroll
          for (int i = 0; i < 2; i++) v[i] = ((lane & 8) ? v[2 + i] : v[i]) + __shfl_xor_sync(~0u, (lane & 8) ? v[i] : v[2 + i], 8);
          v[0] = ((lane & 4) ? v[1] : v[0]) + __shfl_xor_sync(~0u, (lane & 4) ? v[0] : v[1], 4);
          v[0] += __shfl_xor_sync(~0u, v[0], 2); v[0] += __shfl_xor_sync(~0u, v[0], 1);
          if (!(lane & 3)) sts32(sb + RS_OFF + 256 + (r0 + (lane >> 2)) * 4, v[0]);
        }
        __syncwarp();
        if (lane == 0) { mbar_arrive(BAR(B_MODOK)); TRACE(57); }
      } else {
        const unsigned tgt = tag * 256u; int it = 0;
        while ((int)(ld_rlx(&pp.cnt[9 * 32]) - tgt) < 0) { __nanosleep(100); if (++it > SPIN_LIMIT) SPIN_FAIL(0x204); }
        if (lane == 0) { mbar_arrive(BAR(B_MODOK)); TRACE(10); }
        const float sgn = j ? -1.f : 1.f;
        float c1 = 0.f, c2 = 0.f;
#pragma unroll 1
        for (int i = 0; i < 4; i++) {
          const int p = lane + 32 * i;
          const uint32_t sa = ld_rlx(pp.mod + m4 * 128 + p), ca = ld_rlx(pp.mod + 512 + m4 * 128 + p);
          const uint4 sv = ld_msg(reinterpret_cast<const uint4*>(pp.mod + 1536) + p), cv = ld_msg(reinterpret_cast<const uint4*>(pp.mod + 2048) + p);
          const uint4 wr = ldg_nc(pp.wr + p * 16);
          sts128(sb + T1_OFF + p * 16, sgn * round_bf16(1.f + bf_lo(ca)), sgn * round_bf16(1.f + bf_hi(ca)), sgn * bf_lo(sa), sgn * bf_hi(sa));
          const uint32_t s4[4] = {sv.x, sv.y, sv.z, sv.w}, c4[4] = {cv.x, cv.y, cv.z, cv.w}, w4[4] = {wr.x, wr.y, wr.z, wr.w};
#pragma unroll
          for (int u = 0; u < 4; u++) {
            c1 = fmaf(round_bf16(1.f + bf_lo(c4[u])), bf_lo(w4[u]), c1); c1 = fmaf(round_bf16(1.f + bf_hi(c4[u])), bf_hi(w4[u]), c1);
            c2 = fmaf(bf_lo(s4[u]), bf_lo(w4[u]), c2); c2 = fmaf(bf_hi(s4[u]), bf_hi(w4[u]), c2);
          }
        }
#pragma unroll
        for (int o = 16; o; o >>= 1) { c1 += __shfl_xor_sync(~0u, c1, o); c2 += __shfl_xor_sync(~0u, c2, o); }
        __syncwarp();
        if (lane == 0) {
          sts64(sb + CST_OFF, c1, c2);
          mbar_arrive(BAR(B_T1));
#pragma unroll 1
          for (int i = 0; i < FK_PF1; i++) { prefetch_piece(pp, b, i); __nanosleep(FK_PF_SLEEP); }
        }
        __syncwarp();
      }
    }
    asm volatile("barrier.cluster.wait.acquire.aligned;" ::: "memory");

    uint32_t wf[128];
    mbar_wait(BAR(B_WB), 0);
    if (moe) take_box<0>(wf, sb + SPARE + warp * 8192, lane);
    __syncwarp();
    if (lane == 0) mbar_arrive(BAR(B_WT));

    unsigned readyMask = 0, pendFlag = 0;
#pragma unroll 1
    for (int h = 0; h < 2; h++) {
      if (warp == 0) {
        const unsigned* flagAddr = &pp.mail->flagP[(((j * 16 + t) * 4 + ((m4 + 1 + ((lane & 15) >> 2)) & 3)) * 4 + (lane & 3)) * 8];
#pragma unroll 1
        for (int q = h * 8; q < h * 8 + 8; q++) {
          const int s = q & 3, k0 = ((m4 + (q >> 2)) & 3) * 256 + s * 64;
          readyMask |= __ballot_sync(~0u, pendFlag == tag);
          if (lane < 12 && (readyMask & 0xFFF) != 0xFFF) pendFlag = ld_rlx(flagAddr);
          mbar_wait(BAR(B_EMPTY + s), ((q >> 2) + 1) & 1);
          if (q >= 4) {
            int it = 0;
            while (!((readyMask >> (q - 4)) & 1)) {
              readyMask |= __ballot_sync(~0u, pendFlag == tag);
              if (lane < 12) pendFlag = ld_rlx(flagAddr);
              if (++it > SPIN_LIMIT) SPIN_FAIL(0x202);
            }
            fence_async_global();
          }
          if (lane == 0) {
            const uint32_t sa = sb + s * STAGE;
            mbar_expect_tx(BAR(B_FULL + s), q < 4 ? 2 * SLOT : STAGE);
            if (q >= 4) { tma_2d(sa, &maps.p, k0, j * S_ + t * 128, BAR(B_FULL + s)); mbar_arrive(BAR(B_EMPTY + s)); }
            tma_2d(sa + SLOT, &maps.wd[j], k0, m4 * 256, BAR(B_FULL + s));
            TRACE(32 + q);
          }
          __syncwarp();
        }
      } else if (warp == 1) {
        if (h == 0 && lane == 0) {
          unsigned* fl = &pp.mail->flagP[(((j * 16 + t) * 4 + m4) * 4) * 8];
#pragma unroll 1
          for (int i = 0; i < 8; i++) {
            const int q = i & 3, half = i < 4 ? 1 - j : j;
            mbar_wait(BAR(B_PRDY + i), 0);
            tma_store_2d(&maps.ps, sb + q * STAGE + half * 8192, m4 * 256 + q * 64, j * S_ + t * 128 + half * 64);
            if (i >= 4) bulk_commit();
          }
          bulk_wait<3>(); st_rlx(fl, tag); mbar_arrive(BAR(B_EMPTY + 0));
          TRACE(29);
          bulk_wait<2>(); st_rlx(fl + 8, tag); mbar_arrive(BAR(B_EMPTY + 1));
          bulk_wait<1>(); st_rlx(fl + 16, tag); mbar_arrive(BAR(B_EMPTY + 2));
          bulk_wait<0>(); st_rlx(fl + 24, tag); mbar_arrive(BAR(B_EMPTY + 3));
          TRACE(8);
        }
        __syncwarp();
      } else if (warp == 2) {
        if (lane == 0) {
          mbar_wait(BAR(B_WT), h);
          if (h == 0) {
            if (moe) {
              mbar_expect_tx(BAR(B_WB), 32768);
#pragma unroll 1
              for (int i = 0; i < 4; i++) { tma_2d_hint(sb + SPARE + i * 8192, &maps.wu, b * 32, i * 128, BAR(B_WB), pol_first); __nanosleep(FK_PF_SLEEP); }
            } else mbar_arrive(BAR(B_WB));
          } else {
            mbar_expect_tx(BAR(B_X), 32768);
            tma_3d(sb + SPARE, &maps.x, 0, t * 128 + (1 - j) * 64, m4 * 4, BAR(B_X));
          }
        }
        __syncwarp();
      } else {
        if (h == 0) {
          const int G = lane >> 2, q = lane & 3, p0 = m4 * 128 + G * 16 + q;
          uint32_t ga[4], hi[4], lo[4];
#pragma unroll
          for (int u = 0; u < 4; u++) {
            ga[u] = ld_rlx(pp.mod + 1024 + p0 + 4 * u);
            const uint32_t cb = ld_rlx(pp.mod + 2048 + p0 + 4 * u), wr = __ldg(reinterpret_cast<const uint32_t*>(pp.wr) + p0 + 4 * u);
            const float w0 = round_bf16(1.f + bf_lo(cb)) * bf_lo(wr), w1 = round_bf16(1.f + bf_hi(cb)) * bf_hi(wr);
            hi[u] = pack_bf16(w0, w1);
            lo[u] = pack_bf16(w0 - bf_lo(hi[u]), w1 - bf_hi(hi[u]));
          }
          mbar_wait(BAR(B_PRDY + 3), 0);
          mbar_wait(BAR(B_PRDY + 7), 0);
          sts128(sb + GA_OFF + (G * 8 + q) * 16, bf_lo(ga[0]), bf_hi(ga[0]), bf_lo(ga[1]), bf_hi(ga[1]));
          sts128(sb + GA_OFF + (G * 8 + 4 + q) * 16, bf_lo(ga[2]), bf_hi(ga[2]), bf_lo(ga[3]), bf_hi(ga[3]));
          sts128u(sb + W_OFF + G * 144 + q * 16, hi[0], hi[1], hi[2], hi[3]);
          sts128u(sb + W_OFF + G * 144 + 64 + q * 16, lo[0], lo[1], lo[2], lo[3]);
          sts32u(sb + W_OFF + G * 144 + 128 + q * 4, 0x3F803F80u);
          __syncwarp();
          if (lane == 0) mbar_arrive(BAR(B_T2));
        }
        if (lane == 0) {
          constexpr int MID = (FK_PF1 + 19) / 2;
#pragma unroll 1
          for (int i = h ? MID : FK_PF1; i < (h ? 19 : MID); i++) { prefetch_piece(pp, b, i); __nanosleep(FK_PF_SLEEP); }
          if (h) TRACE(30);
        }
        __syncwarp();
      }
      if (h == 0) {
        mbar_wait(BAR(B_WB), 1);
        if (moe) take_box<1>(wf, sb + SPARE + warp * 8192, lane);
        __syncwarp();
        if (lane == 0) mbar_arrive(BAR(B_WT));
      }
    }

    if (warp == 0) {
      if (lane == 0) {
        mbar_wait(BAR(B_EMPTY + 0), 1);
        asm volatile("{\n.reg .b32 ra;\nmapa.shared::cluster.u32 ra, %0, %1;\nmbarrier.arrive.shared::cluster.b64 _, [ra];\n}"
                     ::"r"(BAR(B_PEER)), "r"(j ^ 1) : "memory");
        if (moe) {
          mbar_expect_tx(BAR(B_GU), 16384);
          tma_2d(sb, &maps.wg, b * 32, 512, BAR(B_GU));
          tma_2d(sb + 8192, &maps.wu, b * 32, 512, BAR(B_GU));
          mbar_wait(BAR(B_EMPTY + 1), 1);
          mbar_expect_tx(BAR(B_GU), 49152);
#pragma unroll 1
          for (int i = 0; i < 6; i++) tma_2d(sb + STAGE + i * 8192, (i & 1) ? &maps.wu : &maps.wg, b * 32, 640 + (i >> 1) * 128, BAR(B_GU));
          mbar_wait(BAR(B_EMPTY + 2), 1);
          mbar_expect_tx(BAR(B_DN), 49152);
#pragma unroll 1
          for (int i = 0; i < 3; i++) tma_3d(sb + 2 * STAGE + i * SLOT, &maps.wdn, 0, b * 32, i * 4, BAR(B_DN));
          mbar_wait(BAR(B_XDONE), 0);
          mbar_expect_tx(BAR(B_DN), 16384);
          tma_3d(sb + SPARE, &maps.wdn, 0, b * 32, 12, BAR(B_DN));
        }
      }
      __syncwarp();
    } else if (warp == 1) {
      mbar_wait(BAR(B_STAG), 1);
      mbar_wait(BAR(B_EMPTY + 3), 1);
      uint4 m; int it = 0;
      while (true) {
        m = ld_msg(&pp.mail->cand[b * 32 + lane]);
        if (__all_sync(~0u, m.w == tag)) break;
        if (++it > SPIN_LIMIT) SPIN_FAIL(0x206);
      }
      uint32_t k1, k2; int i1, i2;
      warp_top2(m.x, (int)(m.z & 0xFFFF), m.y, (int)(m.z >> 16), k1, i1, k2, i2);
      if (lane == 0) {
        sts128u(sb + SEL_OFF, i1, i2, k1, k2);
        mbar_arrive(BAR(B_SEL));
        TRACE(19);
      }
    }
    mbar_wait(BAR(B_SEL), 0);
    if (moe) gate_up(pp, wf, sb, warp, lane);
    if (warp == 1) {
      const uint4 sel = lds128u(sb + SEL_OFF);
      const int bA = (int)sel.x >> 6, bB = (int)sel.y >> 6;
      const int n = (lane >> 3) & 1, col = (b >> 1) * 16 + (b & 1) * 4 + (lane & 3) + ((lane >> 4) & 1) * 8;
      const int wofs = ((n ? bB * 2 + (bA == bB ? 1 : 0) : bA * 2) * 128 + (col >> 5) * 4 + ((col >> 1) & 3)) * 4 + ((col >> 3) & 3);
      const uint32_t gbp = ld_rlx(pp.mod + 2560 + (col >> 1));
      uint32_t hp, xp; int it = 0;
      while (true) {
        hp = ld_rlx(reinterpret_cast<const uint32_t*>(pp.mail->rowh) + wofs); xp = ld_rlx(reinterpret_cast<const uint32_t*>(pp.mail->rowx) + wofs);
        if (__all_sync(~0u, hp != SENT && xp != SENT)) break;
        if (++it > SPIN_LIMIT) SPIN_FAIL(0x2ff);
      }
      const float sg = round_bf16(sigmoid_f(round_bf16(fkey_inv(n ? sel.w : sel.z))));
      const uint4* src = &pp.mail->part[(size_t)b * (NMOE * 4) + lane];
      uint4 m[14];
#pragma unroll
      for (int i = 0; i < 14; i++) m[i].x = SENT;
      it = 0;
      while (true) {
        bool ok = true;
#pragma unroll
        for (int i = 0; i < 14; i++) if (m[i].x == SENT) m[i] = ld_msg(src + 32 * i);
#pragma unroll
        for (int i = 0; i < 14; i++) ok &= m[i].x != SENT;
        if (__all_sync(~0u, ok)) break;
        if (++it > SPIN_LIMIT) SPIN_FAIL(0x20b);
      }
      if (lane == 0) TRACE(23);
      float s0 = 0.f, s1 = 0.f, s2 = 0.f, s3 = 0.f;
#pragma unroll
      for (int i = 0; i < 14; i++) { s0 += __uint_as_float(m[i].x); s1 += __uint_as_float(m[i].y); s2 += __uint_as_float(m[i].z); s3 += __uint_as_float(m[i].w); }
      const bool u4 = lane & 16, u3 = lane & 8;
      const float a0 = (u4 ? s2 : s0) + __shfl_xor_sync(~0u, u4 ? s0 : s2, 16), a1 = (u4 ? s3 : s1) + __shfl_xor_sync(~0u, u4 ? s1 : s3, 16);
      float y = (u3 ? a1 : a0) + __shfl_xor_sync(~0u, u3 ? a0 : a1, 8);
      y += __shfl_xor_sync(~0u, y, 4);
      const bool odd = col & 1;
      const float upd = round_bf16(round_bf16(y) * sg);
      const float o = fmaf(odd ? bf_hi(gbp) : bf_lo(gbp), (odd ? bf_hi(hp) : bf_lo(hp)) + upd, odd ? bf_hi(xp) : bf_lo(xp));
      if (!(lane & 4)) reinterpret_cast<__nv_bfloat16*>(pp.out)[(size_t)(n ? sel.y : sel.x) * D_ + col] = __float2bfloat16_rn(o);
      if (lane == 0) { TRACE(24); TRACE_CLK(54); if (b == 0) pp.cnt[10 * 32] = tag; }
    }
  } else {
    const int cw = (warp - 4) >> 2;
    const int wq = warp & 3;
    const int wtid = tid & 127;
    const int gq = lane >> 2, q4 = lane & 3;
    const bool lag = cw == j;
    const bool elect = wtid == 0;

    asm volatile("barrier.cluster.arrive.relaxed.aligned;" ::: "memory");
    if (warp > 4) {
      delay_until(c0, FK_ROW0DLY + (warp - 4) * FK_ROWDLY);
#pragma unroll
      for (int i = 0; i < 4; i++) xr[i] = ldg_nc(xsrc + 32 * i);
    }
    ln_row(xr);
    {
      const uint32_t stg = sb + SPARE + 8192 + cw * 16384 + wq * 2048;
#pragma unroll
      for (int i = 0; i < 4; i++) sts128u(stg + lane * 16 + i * 512, xr[i].x, xr[i].y, xr[i].z, xr[i].w);
      if (tid == 128) TRACE(31);
      fence_async_smem();
      __syncwarp();
      if (lane == 0) {
        bulk_store(pp.n + (size_t)((warp - 4) * 128 + b) * (2 * D_), stg, 2048); bulk_commit(); bulk_wait<0>();
        red_add(&pp.cnt[(warp - 4) * 32], 1);
      }
      __syncwarp();
    }
    if (tid == 128) TRACE(1);
    if (tid == 352) TRACE(55);
    named_bar<0, 384>();
    asm volatile("barrier.cluster.wait.acquire.aligned;" ::: "memory");
    asm volatile("add.u32 %0, %0, 1;" : "+r"(tag)::"memory");

    const int mrow = wq * 16 + (lane & 7) + ((lane >> 3) & 1) * 8;
    {
      float acc[128];
      gemm_phase<1, 0, 32>(acc, sb, cw, lag, elect);
      mbar_wait(BAR(B_T1), 0);
      const uint32_t tad = sb + T1_OFF + q4 * 16;
      float4 tb[32];
#pragma unroll
      for (int c = 0; c < 4; c++) tb[c] = lds128(tad + c * 64);
      const float rs0 = lds32(sb + RS_OFF + (cw * 64 + wq * 16 + gq) * 4), rs1 = lds32(sb + RS_OFF + (cw * 64 + wq * 16 + gq + 8) * 4);
      const uint32_t dst = sb + cw * 8192 + mrow * 128, pb = BAR(B_PRDY + (lag ? 4 : 0));
      gemm_finish(acc, sb, elect);
      if (elect) { TRACE(lag ? 5 : 4); if (lag) TRACE_CLK(51); }
#pragma unroll
      for (int i = 0; i < 16; i++) {
        uint32_t r[4];
#pragma unroll
        for (int h = 0; h < 2; h++) {
          float4 tv = tb[2 * i + h];
          asm volatile("" : "+f"(tv.z), "+f"(tv.w));
          const int o = 8 * i + 4 * h;
          r[2 * h] = pack_bf16(fmaf(acc[o], tv.x, rs0 * tv.z), fmaf(acc[o + 1], tv.y, rs0 * tv.w));
          r[2 * h + 1] = pack_bf16(fmaf(acc[o + 2], tv.x, rs1 * tv.z), fmaf(acc[o + 3], tv.y, rs1 * tv.w));
        }
        asm volatile("" : "+r"(r[0]), "+r"(r[1]), "+r"(r[2]), "+r"(r[3]));
#pragma unroll
        for (int c = (i < 2 ? 4 * i + 4 : 2 * i + 8); c < (i < 2 ? 4 * i + 8 : 2 * i + 10); c++) if (c < 32) tb[c] = lds128(tad + c * 64);
        stsm_x4(dst + (i >> 2) * STAGE + (uint32_t)(((((2 * i) & 7) + (lane >> 4)) ^ (lane & 7)) << 4), r[0], r[1], r[2], r[3]);
        if ((i & 3) == 3) {
          fence_async_smem();
          __syncwarp();
          if (lane == 0) mbar_arrive(pb + (i >> 2) * 8);
        }
      }
      mbar_wait(pb + 24, 0);
    }
    if (elect) TRACE(lag ? 7 : 6);
    float acc[128];
    gemm_phase<0, 32, 48>(acc, sb, cw, lag, elect);

    if (!lag) {
      uint32_t rdst, rbar;
      asm volatile("mapa.shared::cluster.u32 %0, %1, %2;" : "=r"(rdst) : "r"(sb + RECV_OFF + wtid * 16), "r"(j ^ 1));
      asm volatile("mapa.shared::cluster.u32 %0, %1, %2;" : "=r"(rbar) : "r"(BAR(B_RECV)), "r"(j ^ 1));
      mbar_wait(BAR(B_T2), 0);
      mbar_wait(BAR(B_X), 0);
      mbar_wait_cluster(BAR(B_PEER), 0);
      uint32_t xf[16][4]; float4 ga[16];
      auto fetch = [&](int i) {
        ldsm_x4(sb + SPARE + (i >> 2) * 8192 + mrow * 128 + (uint32_t)(((((2 * i) & 7) + (lane >> 4)) ^ (lane & 7)) << 4), xf[i][0], xf[i][1], xf[i][2], xf[i][3]);
        ga[i] = lds128(sb + GA_OFF + (i * 4 + q4) * 16);
      };
      fetch(0); fetch(1);
      gemm_finish(acc, sb, elect);
      if (elect) TRACE(12);
      uint32_t cbp, sbp, gbp;
#pragma unroll
      for (int i = 0; i < 16; i++) {
        const int o = 8 * i;
        uint32_t w0 = pack_bf16(fmaf(ga[i].x, acc[o], bf_lo(xf[i][0])), fmaf(ga[i].y, acc[o + 1], bf_hi(xf[i][0])));
        uint32_t w1 = pack_bf16(fmaf(ga[i].x, acc[o + 2], bf_lo(xf[i][1])), fmaf(ga[i].y, acc[o + 3], bf_hi(xf[i][1])));
        uint32_t w2 = pack_bf16(fmaf(ga[i].z, acc[o + 4], bf_lo(xf[i][2])), fmaf(ga[i].w, acc[o + 5], bf_hi(xf[i][2])));
        uint32_t w3 = pack_bf16(fmaf(ga[i].z, acc[o + 6], bf_lo(xf[i][3])), fmaf(ga[i].w, acc[o + 7], bf_hi(xf[i][3])));
        asm volatile("" : "+r"(w0), "+r"(w1), "+r"(w2), "+r"(w3));
        if (i < 2) { fetch(2 * i + 2); fetch(2 * i + 3); } else if (i < 12) fetch(i + 4);
        if (i == 8) { cbp = ld_rlx(pp.mod + 2048 + m4 * 128 + wtid); sbp = ld_rlx(pp.mod + 1536 + m4 * 128 + wtid); gbp = ld_rlx(pp.mod + 2560 + m4 * 128 + wtid); }
        asm volatile("st.async.weak.shared::cluster.mbarrier::complete_tx::bytes.v4.b32 [%0], {%1, %2, %3, %4}, [%5];"
                     ::"r"(rdst + i * 2048), "r"(w0), "r"(w1), "r"(w2), "r"(w3), "r"(rbar) : "memory");
      }
      named_bar<1, 128>();
      if (elect) { mbar_arrive(BAR(B_XDONE)); TRACE(13); }
      {
        const float A0 = round_bf16(1.f + bf_lo(cbp)), A1 = round_bf16(1.f + bf_hi(cbp));
        sts128(sb + GH_OFF + wtid * 16, bf_lo(gbp) * A0, bf_hi(gbp) * A1, bf_lo(gbp) * bf_lo(sbp), bf_hi(gbp) * bf_hi(sbp));
        const uint32_t fo = ((wtid >> 4) * 4 + (wtid & 3)) * 16 + ((wtid >> 2) & 3) * 4;
        sts32u(sb + TA_OFF + fo, pack_bf16(A0, A1)); sts32u(sb + TS_OFF + fo, sbp);
      }
      named_bar<1, 128>();
      if (elect) mbar_arrive(BAR(B_T3));
      if (b < NMOE) {
        uint32_t wf[128];
        mbar_wait(BAR(B_GU), 0);
        const uint32_t box = sb + (wq ? STAGE + (wq - 1) * SLOT : 0);
        take_box<0>(wf, box, lane);
        take_box<1>(wf, box + 8192, lane);
        if (elect) TRACE(26);
        mbar_wait(BAR(B_SEL), 0);
        gate_up(pp, wf, sb, 4 + wq, lane);
      }
    } else {
      mbar_wait(BAR(B_T2), 0);
      mbar_wait_cluster(BAR(B_RECV), 0);
      if (elect) TRACE(56);
      uint32_t xa[64];
      float dl[4] = {0.f, 0.f, 0.f, 0.f}, d2[4] = {0.f, 0.f, 0.f, 0.f}, d3[4] = {0.f, 0.f, 0.f, 0.f};
      {
        const uint32_t wad = sb + W_OFF + ((gq & 2) ? 128 : (gq & 1) * 64 + q4 * 16);
        uint4 rv[16], wb[8]; float4 ga[16];
        auto fetch = [&](int i) { rv[i] = lds128u(sb + RECV_OFF + i * 2048 + wtid * 16); ga[i] = lds128(sb + GA_OFF + (i * 4 + q4) * 16); };
        fetch(0); fetch(1);
        gemm_finish(acc, sb, elect);
        if (elect) { TRACE(14); TRACE_CLK(53); }
#pragma unroll
        for (int i = 0; i < 16; i++) {
          const int o = 8 * i;
          uint32_t a0 = pack_bf16(fmaf(ga[i].x, acc[o], bf_lo(rv[i].x)), fmaf(ga[i].y, acc[o + 1], bf_hi(rv[i].x)));
          uint32_t a1 = pack_bf16(fmaf(ga[i].x, acc[o + 2], bf_lo(rv[i].y)), fmaf(ga[i].y, acc[o + 3], bf_hi(rv[i].y)));
          uint32_t a2 = pack_bf16(fmaf(ga[i].z, acc[o + 4], bf_lo(rv[i].z)), fmaf(ga[i].w, acc[o + 5], bf_hi(rv[i].z)));
          uint32_t a3 = pack_bf16(fmaf(ga[i].z, acc[o + 6], bf_lo(rv[i].w)), fmaf(ga[i].w, acc[o + 7], bf_hi(rv[i].w)));
          asm volatile("" : "+r"(a0), "+r"(a1), "+r"(a2), "+r"(a3));
          if (i < 14) fetch(i + 2);
          if (!(i & 1)) wb[i >> 1] = lds128u(wad + (i >> 1) * 144);
          xa[4 * i] = a0; xa[4 * i + 1] = a1; xa[4 * i + 2] = a2; xa[4 * i + 3] = a3;
          mma_1688(d2, a0, a1, a0); mma_1688(d3, a0, a1, a1);
          mma_1688(d2, a2, a3, a2); mma_1688(d3, a2, a3, a3);
          if (i & 1) {
            mma_16816(dl, xa[4 * i - 4], xa[4 * i - 3], xa[4 * i - 2], xa[4 * i - 1], wb[i >> 1].x, wb[i >> 1].y);
            mma_16816(dl, a0, a1, a2, a3, wb[i >> 1].z, wb[i >> 1].w);
          }
        }
      }
      {
        const bool odd = q4 & 1;
        const float mine = odd ? dl[2] : dl[0] + dl[1];
        const float other = __shfl_xor_sync(~0u, odd ? dl[0] : dl[2] + dl[3], 1);
        const int dsrc = (lane & ~3) | (gq >> 1);
        const float qa = __shfl_sync(~0u, (gq & 1) ? d2[1] : d2[0], dsrc), qb = __shfl_sync(~0u, (gq & 1) ? d3[3] : d3[2], dsrc);
        if (q4 < 2) st_msg(&pp.mail->stats[(blk * 4 + m4) * 64 + wq * 16 + gq + 8 * q4], __float_as_uint(odd ? mine : other), __float_as_uint(odd ? qb : qa),
                           __float_as_uint(odd ? other : mine), tag);
      }
      if (elect) TRACE(15);
      float rstd, nm, rme;
      {
        const uint4* src = &pp.mail->stats[(blk * 4 + (lane >> 4) * 2) * 64 + wq * 16 + (lane & 15)];
        const float2 cst = lds64(sb + CST_OFF);
        uint4 m0, m1; int it = 0;
        while (true) {
          m0 = ld_msg(src); m1 = ld_msg(src + 64);
          if (__all_sync(~0u, m0.w == tag && m1.w == tag)) break;
          if (++it > SPIN_LIMIT) SPIN_FAIL(0x209);
        }
        float sa = __uint_as_float(m0.x) + __uint_as_float(m1.x), qa = __uint_as_float(m0.y) + __uint_as_float(m1.y), da = __uint_as_float(m0.z) + __uint_as_float(m1.z);
        sa += __shfl_xor_sync(~0u, sa, 16); qa += __shfl_xor_sync(~0u, qa, 16); da += __shfl_xor_sync(~0u, da, 16);
        const float mean = sa * (1.f / D_);
        rstd = rsqrtf(fmaxf(fmaf(-mean, mean, qa * (1.f / D_)), 0.f) + 1e-5f);
        nm = -mean * rstd;
        rme = fmaf(rstd, fmaf(-mean, cst.x, da), cst.y);
      }
      if (elect) TRACE(16);
      int bi1, bi2;
      {
        uint32_t k1, k2; int i1, i2;
        warp_top2(lane < 16 ? fkey(rme) : 0u, blk * 64 + wq * 16 + (lane & 15), 0u, 0, k1, i1, k2, i2);
        if (lane == 0) sts128u(sb + TOP_OFF + wq * 16, k1, k2, i1, i2);
        named_bar<2, 128>();
        uint4 c = make_uint4(0, 0, 0, 0);
        if (lane < 4) c = lds128u(sb + TOP_OFF + lane * 16);
        warp_top2(c.x, (int)c.z, c.y, (int)c.w, k1, bi1, k2, bi2);
        if (wq == 0) st_msg(&pp.mail->cand[(m4 * 32 + lane) * 32 + blk], k1, k2, (uint32_t)bi1 | ((uint32_t)bi2 << 16), tag);
      }
      if (elect) TRACE(17);
      mbar_wait(BAR(B_T3), 0);
#pragma unroll 1
      for (int ci = 0; ci < 2; ci++) {
        const int lr = (ci ? bi2 : bi1) - blk * 64;
        if ((lr >> 4) == wq) {
          const uint32_t scr = sb + SCR_OFF + wq * 512;
          const bool up = lr & 8;
          if (gq == (lr & 7)) {
#pragma unroll
            for (int G = 0; G < 8; G++)
              sts128u(scr + (G * 4 + q4) * 16, up ? xa[8 * G + 1] : xa[8 * G], up ? xa[8 * G + 3] : xa[8 * G + 2], up ? xa[8 * G + 5] : xa[8 * G + 4], up ? xa[8 * G + 7] : xa[8 * G + 6]);
          }
          __syncwarp();
          const float rs_ = __shfl_sync(~0u, rstd, lr & 15), nm_ = __shfl_sync(~0u, nm, lr & 15);
          const uint4 v = lds128u(scr + lane * 16), A = lds128u(sb + TA_OFF + lane * 16), S = lds128u(sb + TS_OFF + lane * 16);
          auto h2 = [&](uint32_t xv, uint32_t av, uint32_t sv) {
            return pack_bf16(fmaf(fmaf(bf_lo(xv), rs_, nm_), bf_lo(av), bf_lo(sv)), fmaf(fmaf(bf_hi(xv), rs_, nm_), bf_hi(av), bf_hi(sv)));
          };
          const int o = (blk * 2 + ci) * 128 + m4 * 32 + lane;
          st_msg(&pp.mail->rowh[o], h2(v.x, A.x, S.x), h2(v.y, A.y, S.y), h2(v.z, A.z, S.z), h2(v.w, A.w, S.w));
          st_msg(&pp.mail->rowx[o], v.x, v.y, v.z, v.w);
          __syncwarp();
        }
      }
      if (elect) TRACE(18);
      {
        const float r0 = __shfl_sync(~0u, rstd, gq), n0 = __shfl_sync(~0u, nm, gq), r1 = __shfl_sync(~0u, rstd, gq + 8), n1 = __shfl_sync(~0u, nm, gq + 8);
        mbar_wait(BAR(B_EMPTY + 3), 1);
        const uint32_t dst = sb + OUT_OFF + mrow * OUT_LD + (lane >> 4) * 16, tad = sb + GH_OFF + q4 * 16;
        float4 tb[32];
#pragma unroll
        for (int c = 0; c < 8; c++) tb[c] = lds128(tad + c * 64);
#pragma unroll
        for (int i = 0; i < 16; i++) {
          uint32_t r[4];
#pragma unroll
          for (int h = 0; h < 2; h++) {
            const float4 tv = tb[2 * i + h];
            const uint32_t u0 = xa[4 * i + 2 * h], u1 = xa[4 * i + 2 * h + 1];
            r[2 * h] = pack_bf16(fmaf(fmaf(bf_lo(u0), r0, n0), tv.x, bf_lo(u0) + tv.z), fmaf(fmaf(bf_hi(u0), r0, n0), tv.y, bf_hi(u0) + tv.w));
            r[2 * h + 1] = pack_bf16(fmaf(fmaf(bf_lo(u1), r1, n1), tv.x, bf_lo(u1) + tv.z), fmaf(fmaf(bf_hi(u1), r1, n1), tv.y, bf_hi(u1) + tv.w));
          }
          if (i < 12) { tb[2 * i + 8] = lds128(tad + (2 * i + 8) * 64); tb[2 * i + 9] = lds128(tad + (2 * i + 9) * 64); }
          stsm_x4(dst + i * 32, r[0], r[1], r[2], r[3]);
        }
        fence_async_smem();
        __syncwarp();
      }
      const int orow = blk * 64 + wq * 16 + lane;
      const bool candrow = orow == bi1 || orow == bi2;
      char* odst = pp.out + (size_t)orow * (2 * D_) + m4 * 512;
      const uint32_t osrc = sb + OUT_OFF + (wq * 16 + lane) * OUT_LD;
      if (lane < 16 && !candrow) { bulk_store(odst, osrc, 512); bulk_commit(); }
      if (elect) TRACE(25);
      if (b < NMOE) {
        uint32_t wd[128];
        mbar_wait(BAR(B_DN), 0);
        {
          const int fr = (lane & 7) + (lane >> 4) * 8;
          const uint32_t base = sb + (wq < 3 ? 2 * STAGE + wq * SLOT : SPARE) + fr * 128;
#pragma unroll
          for (int c = 0; c < 4; c++) {
            const uint32_t ad = base + (((uint32_t)(c * 2 + ((lane >> 3) & 1)) ^ (uint32_t)(lane & 7)) << 4);
#pragma unroll
            for (int gI = 0; gI < 4; gI++)
#pragma unroll
              for (int ks = 0; ks < 2; ks++) {
                const int o = ((gI * 4 + c) * 2 + ks) * 4;
                ldsm_x4_t(ad + gI * 4096 + ks * 2048, wd[o], wd[o + 1], wd[o + 2], wd[o + 3]);
              }
          }
        }
        if (elect) TRACE(27);
        named_bar<4, 384>();
        if (elect) TRACE(21);
        float g0 = 0.f, g1 = 0.f, u0 = 0.f, u1 = 0.f;
#pragma unroll
        for (int w = 0; w < 8; w++) {
          const float2 gv = lds64(sb + PART_OFF + w * 512 + lane * 8), uv = lds64(sb + PART_OFF + w * 512 + 256 + lane * 8);
          g0 += gv.x; g1 += gv.y; u0 += uv.x; u1 += uv.y;
        }
        const uint32_t act = pack_bf16(round_bf16(silu_f(round_bf16(g0))) * round_bf16(u0), round_bf16(silu_f(round_bf16(g1))) * round_bf16(u1));
        uint32_t ab[4];
#pragma unroll
        for (int u = 0; u < 4; u++) {
          const uint32_t v0 = __shfl_sync(~0u, act, 8 * u + 2 * q4), v1 = __shfl_sync(~0u, act, 8 * u + 2 * q4 + 1);
          ab[u] = __byte_perm(v0, v1, (gq & 1) ? 0x7632 : 0x5410);
        }
        uint4* dst = &pp.mail->part[((size_t)(wq * 32 + (gq >> 2)) * NMOE + b) * 4 + (gq & 3)];
#pragma unroll
        for (int mt = 0; mt < 16; mt++) {
          float c[4] = {0.f, 0.f, 0.f, 0.f};
          mma_16816(c, wd[mt * 8], wd[mt * 8 + 1], wd[mt * 8 + 2], wd[mt * 8 + 3], ab[0], ab[1]);
          mma_16816(c, wd[mt * 8 + 4], wd[mt * 8 + 5], wd[mt * 8 + 6], wd[mt * 8 + 7], ab[2], ab[3]);
          if (q4 == 0) st_msg(dst + mt * (2 * NMOE * 4), __float_as_uint(c[0]), __float_as_uint(c[1]), __float_as_uint(c[2]), __float_as_uint(c[3]));
        }
        if (elect) TRACE(22);
      }
      mbar_wait(BAR(B_SEL), 0);
      if (lane < 16) {
        const uint4 sel = lds128u(sb + SEL_OFF);
        if (candrow && orow != (int)sel.x && orow != (int)sel.y) { bulk_store(odst, osrc, 512); bulk_commit(); }
        bulk_wait_read<0>();
      }
    }
  }
}

typedef CUresult (*PFN_encodeTiled)(CUtensorMap*, CUtensorMapDataType, cuuint32_t, void*, const cuuint64_t*, const cuuint64_t*,
                                    const cuuint32_t*, const cuuint32_t*, CUtensorMapInterleave, CUtensorMapSwizzle,
                                    CUtensorMapL2promotion, CUtensorMapFloatOOBfill);

static void map2d(PFN_encodeTiled enc, CUtensorMap* m, const void* p, uint64_t rows, uint64_t cols, uint32_t brows, uint32_t bcols, CUtensorMapSwizzle sw) {
  cuuint64_t dims[2] = {cols, rows}; cuuint64_t str[1] = {cols * 2}; cuuint32_t box[2] = {bcols, brows}; cuuint32_t es[2] = {1, 1};
  enc(m, CU_TENSOR_MAP_DATA_TYPE_BFLOAT16, 2, (void*)p, dims, str, box, es, CU_TENSOR_MAP_INTERLEAVE_NONE, sw,
      CU_TENSOR_MAP_L2_PROMOTION_L2_128B, CU_TENSOR_MAP_FLOAT_OOB_FILL_NONE);
}
static void map3d(PFN_encodeTiled enc, CUtensorMap* m, const void* p, uint64_t rows, uint64_t cols, uint32_t brows, uint32_t bgroups) {
  cuuint64_t dims[3] = {64, rows, cols / 64}; cuuint64_t str[2] = {cols * 2, 128}; cuuint32_t box[3] = {64, brows, bgroups}; cuuint32_t es[3] = {1, 1, 1};
  enc(m, CU_TENSOR_MAP_DATA_TYPE_BFLOAT16, 3, (void*)p, dims, str, box, es, CU_TENSOR_MAP_INTERLEAVE_NONE, CU_TENSOR_MAP_SWIZZLE_128B,
      CU_TENSOR_MAP_L2_PROMOTION_L2_128B, CU_TENSOR_MAP_FLOAT_OOB_FILL_NONE);
}

}

extern "C" void kernel_launch(void* const* d_in, const int* in_sizes, int n_in, void* d_out, int out_size) {
  using namespace fk;
  (void)in_sizes; (void)n_in; (void)out_size;
  static PFN_encodeTiled enc = nullptr;
  static void *pn = nullptr, *pP = nullptr, *pc = nullptr, *pm = nullptr, *pmod = nullptr;
  if (!enc) {
    void* fn = nullptr; cudaDriverEntryPointQueryResult qr;
    cudaGetDriverEntryPoint("cuTensorMapEncodeTiled", &fn, cudaEnableDefault, &qr);
    enc = (PFN_encodeTiled)fn;
    cudaGetSymbolAddress(&pn, g_n);
    cudaGetSymbolAddress(&pP, g_P);
    cudaGetSymbolAddress(&pc, g_cnt);
    cudaGetSymbolAddress(&pm, g_mail);
    cudaGetSymbolAddress(&pmod, g_mod);
    cudaFuncSetAttribute(fused_kernel, cudaFuncAttributeMaxDynamicSharedMemorySize, SMEM_BYTES);
  }
  Maps maps;
  map2d(enc, &maps.ws[0], d_in[1], S_, S_, 128, 64, CU_TENSOR_MAP_SWIZZLE_128B);
  map2d(enc, &maps.ws[1], d_in[2], S_, S_, 128, 64, CU_TENSOR_MAP_SWIZZLE_128B);
  map3d(enc, &maps.n, pn, S_, D_, 64, 4);
  map2d(enc, &maps.p, pP, 2 * S_, D_, 128, 64, CU_TENSOR_MAP_SWIZZLE_128B);
  map2d(enc, &maps.ps, pP, 2 * S_, D_, 64, 64, CU_TENSOR_MAP_SWIZZLE_128B);
  map2d(enc, &maps.wd[0], d_in[3], D_, D_, 256, 64, CU_TENSOR_MAP_SWIZZLE_128B);
  map2d(enc, &maps.wd[1], d_in[4], D_, D_, 256, 64, CU_TENSOR_MAP_SWIZZLE_128B);
  map3d(enc, &maps.x, d_in[0], S_, D_, 64, 4);
  map2d(enc, &maps.wg, d_in[7], D_, F_, 128, 32, CU_TENSOR_MAP_SWIZZLE_64B);
  map2d(enc, &maps.wu, d_in[8], D_, F_, 128, 32, CU_TENSOR_MAP_SWIZZLE_64B);
  map3d(enc, &maps.wdn, d_in[9], F_, D_, 32, 4);
  map2d(enc, &maps.wm, d_in[11], D_, 6 * D_, 32, 48, CU_TENSOR_MAP_SWIZZLE_NONE);

  cudaLaunchConfig_t cfg = {};
  cfg.gridDim = dim3(NCTA); cfg.blockDim = dim3(384); cfg.dynamicSmemBytes = SMEM_BYTES; cfg.stream = cudaStreamPerThread;
  cudaLaunchAttribute at[1];
  at[0].id = cudaLaunchAttributeClusterDimension; at[0].val.clusterDim.x = 2; at[0].val.clusterDim.y = 1; at[0].val.clusterDim.z = 1;
  cfg.attrs = at; cfg.numAttrs = 1;
  Ptrs pp{(const char*)d_in[0], (char*)pn, (unsigned*)pc, (Mail*)pm, (uint32_t*)pmod, (const char*)d_in[10], (const char*)d_in[1], (const char*)d_in[2],
          (const char*)d_in[3], (const char*)d_in[4], (const char*)d_in[6], (const char*)d_in[7], (const char*)d_in[8], (const char*)d_in[9], (char*)d_out};
  cudaLaunchKernelEx(&cfg, fused_kernel, pp, maps);
}
```

```cpp
#include <cuda_runtime.h>
#include <cuda_bf16.h>
#include <cuda.h>
#include <stdint.h>

#define DEVINL __device__ __forceinline__

namespace fk {

constexpr int S_ = 2048, D_ = 1024, F_ = 3584;
constexpr int NCTA = 128;
constexpr int NEXTRA = 4;
constexpr int NMOE = 112;
constexpr int SLOT = 16384;
constexpr int STAGE = 3 * SLOT;
constexpr int SPARE = 4 * STAGE;
constexpr int MISC = SPARE + 32768;
constexpr int SMEM_BYTES = MISC + 3072;
constexpr int BAR_OFF = MISC;
constexpr int CST_OFF = MISC + 480;
constexpr int SEL_OFF = MISC + 496;
constexpr int T1_OFF = MISC + 512;
constexpr int RS_OFF = T1_OFF + 2048;
constexpr int GA_OFF = T1_OFF;
constexpr int W_OFF = GA_OFF + 512;
constexpr int TOP_OFF = GA_OFF + 1792;
constexpr int RECV_OFF = SLOT;
constexpr int GH_OFF = SPARE + 16384;
constexpr int TA_OFF = GH_OFF + 2048;
constexpr int TS_OFF = TA_OFF + 512;
constexpr int PART_OFF = GH_OFF + 4096;
constexpr int SCR_OFF = GH_OFF + 8192;
constexpr int OUT_OFF = 3 * STAGE;
constexpr int OUT_LD = 528;
enum { B_FULL = 0, B_EMPTY = 4, B_EMPTYH = 8, B_PRDY = 12  , B_WM = 20  , B_RDY = 24  , B_WB = 36  ,
       B_WT = 40  , B_RECV = 44  , B_STAG = 48, B_T1 = 49, B_MODOK = 50, B_GDONE = 51, B_X = 52, B_T2 = 53, B_GU = 54, B_XDONE = 55,
       B_DN = 56, B_T3 = 57, B_SEL = 58, B_NUM = 59 };

__host__ __device__ constexpr int bar_count(int i) {
  return (i >= B_EMPTY && i < B_EMPTYH) || (i >= B_PRDY && i < B_WM) || i == B_X ? 4
         : (i == B_T1 || i == B_GU || i == B_DN || i == B_MODOK || (i >= B_RDY && i < B_RDY + 4)) ? 2 : 1;
}

#define FK_XDEPTH 2
#define FK_G0 8
#define FK_ROW0DLY 500
#define FK_ROWDLY 200
#define FK_WS0DLY 400
#define FK_WS1DLY 1400
#define FK_ADLY 1800
#define FK_L1 2
#define FK_L2 3
#define FK_PF0 19
#define FK_E1DLY 300
#define FK_E2DLY 300
#define FK_E4DLY 2200
#define FK_RSTEP 6
#define FK_MAILQ 14
#define FK_MAP 3
#define FK_PPACE 280
#define FK_PACE0 1000
#define FK_WMPF 0
#define FK_TG 28
#define FK_TU 31
#define FK_BSLEEP 250
#define FK_PFSKIP 0
#define FK_PACE 2000
constexpr int SPIN_LIMIT = 1 << 22;
constexpr uint32_t SENT = 0xFFFFFFFFu;

struct Maps {
  CUtensorMap ws[2];
  CUtensorMap n;
  CUtensorMap p;
  CUtensorMap ps;
  CUtensorMap wd[2];
  CUtensorMap x;
  CUtensorMap wg, wu;
  CUtensorMap wdn;
  CUtensorMap wm;
};
template <int V> struct IntC { static constexpr int value = V; };
struct Mail;
struct Ptrs { const char* x; char* n; unsigned* cnt; int b0; Mail* mail; uint32_t* mod; const char *c, *ws_re, *ws_im, *wd_re, *wd_im, *wr, *wg, *wu, *wdn, *wm; char* out; unsigned long long* trace; };

__device__ __align__(1024) __nv_bfloat16 g_n[S_ * D_];
__device__ __align__(1024) __nv_bfloat16 g_P[2 * S_ * D_];
__device__ __align__(128) uint32_t g_mod[3 * D_];
__device__ __align__(128) unsigned g_cnt[17 * 32];
struct Mail {
  uint4 stats[32 * 4 * 64];
  uint4 cand[128 * 32];
  uint4 rowh[64 * 128];
  uint4 rowx[64 * 128];
  uint4 part[128 * NMOE * 2];
  uint2 rs[2 * 16 * 128];
  unsigned flagP[512 * 8];
};
static_assert(sizeof(Mail) % (16 * NCTA) == 0, "mail size");
constexpr int MAIL_PER_CTA = sizeof(Mail) / 16 / NCTA;
__device__ __align__(1024) Mail g_mail;

#define SPIN_FAIL(what) __trap()
DEVINL uint32_t smem_u32(const void* p) { return (uint32_t)__cvta_generic_to_shared(p); }
DEVINL void mbar_init(uint32_t bar, uint32_t cnt) { asm volatile("mbarrier.init.shared::cta.b64 [%0], %1;" ::"r"(bar), "r"(cnt) : "memory"); }
DEVINL void mbar_expect_tx(uint32_t bar, uint32_t bytes) { asm volatile("mbarrier.arrive.expect_tx.shared::cta.b64 _, [%0], %1;" ::"r"(bar), "r"(bytes) : "memory"); }
DEVINL void mbar_arrive(uint32_t bar) { asm volatile("mbarrier.arrive.shared::cta.b64 _, [%0];" ::"r"(bar) : "memory"); }
DEVINL void mbar_arrive_cluster(uint32_t bar) { asm volatile("mbarrier.arrive.shared::cluster.b64 _, [%0];" ::"r"(bar) : "memory"); }
DEVINL uint32_t mapa(uint32_t a, uint32_t cta) { uint32_t r; asm("mapa.shared::cluster.u32 %0, %1, %2;" : "=r"(r) : "r"(a), "r"(cta)); return r; }
DEVINL void mbar_wait(uint32_t bar, uint32_t parity) {
  asm volatile("{\n.reg .pred p;\n.reg .u32 c;\nmov.u32 c, 0;\n"
               "LW:\nmbarrier.try_wait.parity.shared::cta.b64 p, [%0], %1;\n@p bra LD;\n"
               "add.u32 c, c, 1;\nsetp.lt.u32 p, c, 4194304;\n@p bra LW;\ntrap;\nLD:\n}" ::"r"(bar), "r"(parity) : "memory");
}
DEVINL void mbar_wait_cluster(uint32_t bar, uint32_t parity) {
  asm volatile("{\n.reg .pred p;\n.reg .u32 c;\nmov.u32 c, 0;\n"
               "LW:\nmbarrier.try_wait.parity.acquire.cluster.shared::cta.b64 p, [%0], %1;\n@p bra LD;\n"
               "add.u32 c, c, 1;\nsetp.lt.u32 p, c, 4194304;\n@p bra LW;\ntrap;\nLD:\n}" ::"r"(bar), "r"(parity) : "memory");
}
DEVINL void fence_async_smem() { asm volatile("fence.proxy.async.shared::cta;" ::: "memory"); }
DEVINL void fence_async_global() { asm volatile("fence.proxy.async.global;" ::: "memory"); }
DEVINL void fence_gpu() { asm volatile("fence.acq_rel.gpu;" ::: "memory"); }
template <int ID, int N> DEVINL void named_bar() { asm volatile("bar.sync %0, %1;" ::"n"(ID), "n"(N) : "memory"); }
template <int ID, int N> DEVINL void named_arrive() { asm volatile("bar.arrive %0, %1;" ::"n"(ID), "n"(N) : "memory"); }

DEVINL void tma_2d(uint32_t dst, const CUtensorMap* m, int x, int y, uint32_t bar) {
  asm volatile("cp.async.bulk.tensor.2d.shared::cluster.global.mbarrier::complete_tx::bytes [%0], [%1, {%3, %4}], [%2];"
               ::"r"(dst), "l"(m), "r"(bar), "r"(x), "r"(y) : "memory");
}
DEVINL void tma_2d_hint(uint32_t dst, const CUtensorMap* m, int x, int y, uint32_t bar, uint64_t pol) {
  asm volatile("cp.async.bulk.tensor.2d.shared::cluster.global.mbarrier::complete_tx::bytes.L2::cache_hint [%0], [%1, {%3, %4}], [%2], %5;"
               ::"r"(dst), "l"(m), "r"(bar), "r"(x), "r"(y), "l"(pol) : "memory");
}
DEVINL void tma_3d(uint32_t dst, const CUtensorMap* m, int x, int y, int z, uint32_t bar) {
  asm volatile("cp.async.bulk.tensor.3d.shared::cluster.global.mbarrier::complete_tx::bytes [%0], [%1, {%3, %4, %5}], [%2];"
               ::"r"(dst), "l"(m), "r"(bar), "r"(x), "r"(y), "r"(z) : "memory");
}
DEVINL void tma_store_2d(const CUtensorMap* m, uint32_t src, int x, int y) {
  asm volatile("cp.async.bulk.tensor.2d.global.shared::cta.bulk_group [%0, {%2, %3}], [%1];" ::"l"(m), "r"(src), "r"(x), "r"(y) : "memory");
}
DEVINL void bulk_load(uint32_t dst, const void* src, uint32_t bytes, uint32_t bar) {
  asm volatile("cp.async.bulk.shared::cluster.global.mbarrier::complete_tx::bytes [%0], [%1], %2, [%3];" ::"r"(dst), "l"(src), "r"(bytes), "r"(bar) : "memory");
}
DEVINL void bulk_store(void* dst, uint32_t src, uint32_t bytes) {
  asm volatile("cp.async.bulk.global.shared::cta.bulk_group [%0], [%1], %2;" ::"l"(dst), "r"(src), "r"(bytes) : "memory");
}
DEVINL void pf_bulk(const void* p, uint32_t bytes) { asm volatile("cp.async.bulk.prefetch.L2.global [%0], %1;" ::"l"(p), "r"(bytes) : "memory"); }
DEVINL void pf_bulk_hint(const void* p, uint32_t bytes, uint64_t pol) {
  asm volatile("cp.async.bulk.prefetch.L2.global.L2::cache_hint [%0], %1, %2;" ::"l"(p), "r"(bytes), "l"(pol) : "memory");
}
DEVINL void pf_2d(const CUtensorMap* m, int x, int y) {
  asm volatile("cp.async.bulk.prefetch.tensor.2d.L2.global [%0, {%1, %2}];" ::"l"(m), "r"(x), "r"(y) : "memory");
}
DEVINL void bulk_commit() { asm volatile("cp.async.bulk.commit_group;" ::: "memory"); }
template <int N> DEVINL void bulk_wait() { asm volatile("cp.async.bulk.wait_group %0;" ::"n"(N) : "memory"); }
template <int N> DEVINL void bulk_wait_read() { asm volatile("cp.async.bulk.wait_group.read %0;" ::"n"(N) : "memory"); }
DEVINL void prefetch_tmap(const CUtensorMap* m) { asm volatile("prefetch.tensormap [%0];" ::"l"(m) : "memory"); }

DEVINL void wg_fence() { asm volatile("wgmma.fence.sync.aligned;" ::: "memory"); }
DEVINL void wg_commit() { asm volatile("wgmma.commit_group.sync.aligned;" ::: "memory"); }
template <int N> DEVINL void wg_wait() { asm volatile("wgmma.wait_group.sync.aligned %0;" ::"n"(N) : "memory"); }

DEVINL uint64_t make_desc(uint32_t addr, uint32_t lbo, uint32_t sbo) {
  return (uint64_t)((addr & 0x3FFFF) >> 4) | ((uint64_t)(lbo >> 4) << 16) | ((uint64_t)(sbo >> 4) << 32) | ((uint64_t)1 << 62);
}

#define R8(a, o) "+f"(a[o]), "+f"(a[o + 1]), "+f"(a[o + 2]), "+f"(a[o + 3]), "+f"(a[o + 4]), "+f"(a[o + 5]), "+f"(a[o + 6]), "+f"(a[o + 7])
#define R128(a) R8(a, 0), R8(a, 8), R8(a, 16), R8(a, 24), R8(a, 32), R8(a, 40), R8(a, 48), R8(a, 56), \
                R8(a, 64), R8(a, 72), R8(a, 80), R8(a, 88), R8(a, 96), R8(a, 104), R8(a, 112), R8(a, 120)
template <int TB>
DEVINL void wgmma_n256(float (&d)[128], uint64_t da, uint64_t db, int scale_d) {
  asm volatile(
      "{\n.reg .pred p;\nsetp.ne.b32 p, %130, 0;\n"
      "wgmma.mma_async.sync.aligned.m64n256k16.f32.bf16.bf16 "
      "{%0, %1, %2, %3, %4, %5, %6, %7, %8, %9, %10, %11, %12, %13, %14, %15, "
      "%16, %17, %18, %19, %20, %21, %22, %23, %24, %25, %26, %27, %28, %29, %30, %31, "
      "%32, %33, %34, %35, %36, %37, %38, %39, %40, %41, %42, %43, %44, %45, %46, %47, "
      "%48, %49, %50, %51, %52, %53, %54, %55, %56, %57, %58, %59, %60, %61, %62, %63, "
      "%64, %65, %66, %67, %68, %69, %70, %71, %72, %73, %74, %75, %76, %77, %78, %79, "
      "%80, %81, %82, %83, %84, %85, %86, %87, %88, %89, %90, %91, %92, %93, %94, %95, "
      "%96, %97, %98, %99, %100, %101, %102, %103, %104, %105, %106, %107, %108, %109, %110, %111, "
      "%112, %113, %114, %115, %116, %117, %118, %119, %120, %121, %122, %123, %124, %125, %126, %127}, "
      "%128, %129, p, 1, 1, 0, %131;\n}\n"
      : R128(d)
      : "l"(da), "l"(db), "r"(scale_d), "n"(TB));
}
DEVINL void reg_fence128(float (&a)[128]) {
#pragma unroll
  for (int i = 0; i < 128; i++) asm volatile("" : "+f"(a[i])::"memory");
}

DEVINL uint32_t pack_bf16(float lo, float hi) {
  uint32_t r;
  asm("cvt.rn.bf16x2.f32 %0, %1, %2;" : "=r"(r) : "f"(hi), "f"(lo));
  return r;
}
DEVINL uint32_t fma_bf2(uint32_t a, uint32_t b, uint32_t c) { uint32_t r; asm("fma.rn.bf16x2 %0, %1, %2, %3;" : "=r"(r) : "r"(a), "r"(b), "r"(c)); return r; }
DEVINL uint32_t mul_bf2(uint32_t a, uint32_t b) { uint32_t r; asm("mul.rn.bf16x2 %0, %1, %2;" : "=r"(r) : "r"(a), "r"(b)); return r; }
DEVINL uint32_t add1_bf2(uint32_t a) { return fma_bf2(a, 0x3F803F80u, 0x3F803F80u); }
DEVINL float bf_lo(uint32_t w) { return __uint_as_float(w << 16); }
DEVINL float bf_hi(uint32_t w) { return __uint_as_float(w & 0xFFFF0000u); }
DEVINL float round_bf16(float v) { return __bfloat162float(__float2bfloat16_rn(v)); }
DEVINL float sigmoid_f(float v) { float r; asm("rcp.approx.ftz.f32 %0, %1;" : "=f"(r) : "f"(1.f + __expf(-v))); return r; }
DEVINL float silu_f(float v) { return v * sigmoid_f(v); }
DEVINL void stsm_x4(uint32_t addr, uint32_t r0, uint32_t r1, uint32_t r2, uint32_t r3) {
  asm volatile("stmatrix.sync.aligned.m8n8.x4.shared.b16 [%0], {%1, %2, %3, %4};" ::"r"(addr), "r"(r0), "r"(r1), "r"(r2), "r"(r3) : "memory");
}
DEVINL void ldsm_x4(uint32_t addr, uint32_t& r0, uint32_t& r1, uint32_t& r2, uint32_t& r3) {
  asm volatile("ldmatrix.sync.aligned.m8n8.x4.shared.b16 {%0, %1, %2, %3}, [%4];" : "=r"(r0), "=r"(r1), "=r"(r2), "=r"(r3) : "r"(addr) : "memory");
}
DEVINL void ldsm_x4_t(uint32_t addr, uint32_t& r0, uint32_t& r1, uint32_t& r2, uint32_t& r3) {
  asm volatile("ldmatrix.sync.aligned.m8n8.x4.trans.shared.b16 {%0, %1, %2, %3}, [%4];" : "=r"(r0), "=r"(r1), "=r"(r2), "=r"(r3) : "r"(addr) : "memory");
}
DEVINL void mma_16816(float (&c)[4], uint32_t a0, uint32_t a1, uint32_t a2, uint32_t a3, uint32_t b0, uint32_t b1) {
  asm("mma.sync.aligned.m16n8k16.row.col.f32.bf16.bf16.f32 {%0, %1, %2, %3}, {%4, %5, %6, %7}, {%8, %9}, {%0, %1, %2, %3};"
      : "+f"(c[0]), "+f"(c[1]), "+f"(c[2]), "+f"(c[3]) : "r"(a0), "r"(a1), "r"(a2), "r"(a3), "r"(b0), "r"(b1));
}
DEVINL void mma_1688(float (&c)[4], uint32_t a0, uint32_t a1, uint32_t b0) {
  asm("mma.sync.aligned.m16n8k8.row.col.f32.bf16.bf16.f32 {%0, %1, %2, %3}, {%4, %5}, {%6}, {%0, %1, %2, %3};"
      : "+f"(c[0]), "+f"(c[1]), "+f"(c[2]), "+f"(c[3]) : "r"(a0), "r"(a1), "r"(b0));
}
DEVINL float4 lds128(uint32_t a) { float4 v; asm volatile("ld.shared.v4.f32 {%0, %1, %2, %3}, [%4];" : "=f"(v.x), "=f"(v.y), "=f"(v.z), "=f"(v.w) : "r"(a)); return v; }
DEVINL uint4 lds128u(uint32_t a) { uint4 v; asm volatile("ld.shared.v4.u32 {%0, %1, %2, %3}, [%4];" : "=r"(v.x), "=r"(v.y), "=r"(v.z), "=r"(v.w) : "r"(a)); return v; }
DEVINL float2 lds64(uint32_t a) { float2 v; asm volatile("ld.shared.v2.f32 {%0, %1}, [%2];" : "=f"(v.x), "=f"(v.y) : "r"(a)); return v; }
DEVINL float lds32(uint32_t a) { float v; asm volatile("ld.shared.f32 %0, [%1];" : "=f"(v) : "r"(a)); return v; }
DEVINL float lds16f(uint32_t a) { uint32_t v; asm volatile("ld.shared.u16 %0, [%1];" : "=r"(v) : "r"(a)); return __uint_as_float(v << 16); }
DEVINL uint32_t lds32u(uint32_t a) { uint32_t v; asm volatile("ld.shared.u32 %0, [%1];" : "=r"(v) : "r"(a)); return v; }
DEVINL void sts128(uint32_t a, float x, float y, float z, float w) { asm volatile("st.shared.v4.f32 [%0], {%1, %2, %3, %4};" ::"r"(a), "f"(x), "f"(y), "f"(z), "f"(w) : "memory"); }
DEVINL void sts128u(uint32_t a, uint32_t x, uint32_t y, uint32_t z, uint32_t w) { asm volatile("st.shared.v4.u32 [%0], {%1, %2, %3, %4};" ::"r"(a), "r"(x), "r"(y), "r"(z), "r"(w) : "memory"); }
DEVINL void sts64(uint32_t a, float x, float y) { asm volatile("st.shared.v2.f32 [%0], {%1, %2};" ::"r"(a), "f"(x), "f"(y) : "memory"); }
DEVINL void sts32(uint32_t a, float v) { asm volatile("st.shared.f32 [%0], %1;" ::"r"(a), "f"(v) : "memory"); }
DEVINL void sts32u(uint32_t a, uint32_t v) { asm volatile("st.shared.u32 [%0], %1;" ::"r"(a), "r"(v) : "memory"); }

DEVINL uint4 ld_msg(const uint4* p) {
  unsigned long long a, b;
  asm volatile("{\n.reg .b128 r;\nld.relaxed.gpu.global.b128 r, [%2];\nmov.b128 {%0, %1}, r;\n}" : "=l"(a), "=l"(b) : "l"(p) : "memory");
  return make_uint4((uint32_t)a, (uint32_t)(a >> 32), (uint32_t)b, (uint32_t)(b >> 32));
}
DEVINL void st_msg(uint4* p, uint32_t x, uint32_t y, uint32_t z, uint32_t w) {
  unsigned long long a = (unsigned long long)x | ((unsigned long long)y << 32), b = (unsigned long long)z | ((unsigned long long)w << 32);
  asm volatile("{\n.reg .b128 r;\nmov.b128 r, {%1, %2};\nst.relaxed.gpu.global.b128 [%0], r;\n}" ::"l"(p), "l"(a), "l"(b) : "memory");
}
DEVINL uint2 ld_msg8(const void* p) {
  unsigned long long a;
  asm volatile("ld.relaxed.gpu.global.b64 %0, [%1];" : "=l"(a) : "l"(p) : "memory");
  return make_uint2((uint32_t)a, (uint32_t)(a >> 32));
}
DEVINL void st_msg8(uint2* p, uint32_t x, uint32_t y) {
  asm volatile("st.relaxed.gpu.global.b64 [%0], %1;" ::"l"(p), "l"((unsigned long long)x | ((unsigned long long)y << 32)) : "memory");
}
DEVINL unsigned ld_rlx(const void* p) { unsigned v; asm volatile("ld.relaxed.gpu.global.u32 %0, [%1];" : "=r"(v) : "l"(p) : "memory"); return v; }
DEVINL void st_rlx(unsigned* p, unsigned v) { asm volatile("st.relaxed.gpu.global.u32 [%0], %1;" ::"l"(p), "r"(v) : "memory"); }
DEVINL void red_add(unsigned* p, unsigned v) { asm volatile("red.relaxed.gpu.global.add.u32 [%0], %1;" ::"l"(p), "r"(v) : "memory"); }
DEVINL void red_add_release(unsigned* p, unsigned v) { asm volatile("red.release.gpu.global.add.u32 [%0], %1;" ::"l"(p), "r"(v) : "memory"); }
DEVINL uint4 ldg_nc(const void* p) {
  uint4 v;
  asm volatile("ld.global.nc.L1::no_allocate.v4.u32 {%0, %1, %2, %3}, [%4];" : "=r"(v.x), "=r"(v.y), "=r"(v.z), "=r"(v.w) : "l"(p));
  return v;
}
DEVINL void stg128(void* p, uint4 v) { asm volatile("st.global.v4.u32 [%0], {%1, %2, %3, %4};" ::"l"(p), "r"(v.x), "r"(v.y), "r"(v.z), "r"(v.w) : "memory"); }
DEVINL void delay_until(uint32_t c0, uint32_t cycles) { while ((uint32_t)clock() - c0 < cycles) {} }

#define TRACE(id)
#define TRACE_CLK(id)

DEVINL const char* piece_addr(const Ptrs& pp, int b, int i) {
  if (i >= 20) return pp.wdn + (size_t)b * 57344 + (i - 20) * 8192;
  if ((i >> 2) == 2) return (b < 64 ? pp.wd_re : pp.wd_im) + (size_t)(b & 63) * 32768 + (i & 3) * 8192;
  return (i < 4 || (i >> 2) == 3 ? pp.wg : pp.wu) + (size_t)((i < 8 ? ((i & 3) ^ 2) * 128 : 512 + (i & 3) * 128) + b) * (2 * F_);
}

DEVINL int sibling(int m4, int r) {
  return r < 2 ? m4 ^ r : ((m4 & 2) ^ 2) + r - 2;
}

DEVINL uint32_t fkey(float v) { const uint32_t u = __float_as_uint(v); return (u & 0x80000000u) ? ~u : (u | 0x80000000u); }
DEVINL float fkey_inv(uint32_t k) { return __uint_as_float((k & 0x80000000u) ? (k & 0x7FFFFFFFu) : ~k); }
DEVINL uint32_t redux_max(uint32_t v) { uint32_t r; asm volatile("redux.sync.max.u32 %0, %1, 0xffffffff;" : "=r"(r) : "r"(v)); return r; }
DEVINL void warp_top2(uint32_t ka, int ia, uint32_t kb, int ib, uint32_t& k1, int& i1, uint32_t& k2, int& i2) {
  const int lane = threadIdx.x & 31;
  k1 = redux_max(ka);
  const int l1 = __ffs(__ballot_sync(~0u, ka == k1)) - 1;
  const uint32_t kc = lane == l1 ? kb : ka;
  const int ic = lane == l1 ? ib : ia;
  k2 = redux_max(kc);
  const int l2 = __ffs(__ballot_sync(~0u, kc == k2)) - 1;
  i1 = __shfl_sync(~0u, ia, l1);
  i2 = __shfl_sync(~0u, ic, l2);
}

DEVINL void ln_row(uint4 (&w)[4]) {
  float v[32];
#pragma unroll
  for (int i = 0; i < 4; i++) {
    v[8 * i + 0] = bf_lo(w[i].x); v[8 * i + 1] = bf_hi(w[i].x); v[8 * i + 2] = bf_lo(w[i].y); v[8 * i + 3] = bf_hi(w[i].y);
    v[8 * i + 4] = bf_lo(w[i].z); v[8 * i + 5] = bf_hi(w[i].z); v[8 * i + 6] = bf_lo(w[i].w); v[8 * i + 7] = bf_hi(w[i].w);
  }
  float s[4] = {0.f, 0.f, 0.f, 0.f}, q[4] = {0.f, 0.f, 0.f, 0.f};
#pragma unroll
  for (int i = 0; i < 32; i++) { s[i & 3] += v[i]; q[i & 3] = fmaf(v[i], v[i], q[i & 3]); }
  float sum = (s[0] + s[1]) + (s[2] + s[3]), sq = (q[0] + q[1]) + (q[2] + q[3]);
#pragma unroll
  for (int o = 16; o; o >>= 1) { sum += __shfl_xor_sync(~0u, sum, o); sq += __shfl_xor_sync(~0u, sq, o); }
  const float mean = sum * (1.f / D_);
  const float rstd = rsqrtf(fmaxf(fmaf(-mean, mean, sq * (1.f / D_)), 0.f) + 1e-5f), nmr = -mean * rstd;
#pragma unroll
  for (int i = 0; i < 4; i++) {
    w[i].x = pack_bf16(fmaf(v[8 * i], rstd, nmr), fmaf(v[8 * i + 1], rstd, nmr)); w[i].y = pack_bf16(fmaf(v[8 * i + 2], rstd, nmr), fmaf(v[8 * i + 3], rstd, nmr));
    w[i].z = pack_bf16(fmaf(v[8 * i + 4], rstd, nmr), fmaf(v[8 * i + 5], rstd, nmr)); w[i].w = pack_bf16(fmaf(v[8 * i + 6], rstd, nmr), fmaf(v[8 * i + 7], rstd, nmr));
  }
}
DEVINL float sum8(uint4 u) { return ((bf_lo(u.x) + bf_hi(u.x)) + (bf_lo(u.y) + bf_hi(u.y))) + ((bf_lo(u.z) + bf_hi(u.z)) + (bf_lo(u.w) + bf_hi(u.w))); }

template <int R> DEVINL void take_box(uint32_t (&wf)[128], uint32_t box, int lane) {
  const int kr = (lane & 7) + (lane >> 4) * 8;
  const uint32_t base = box + kr * 64, sw = (uint32_t)((kr >> 1) & 3), hb = (uint32_t)((lane >> 3) & 1);
#pragma unroll
  for (int mt = 0; mt < 2; mt++) {
    const uint32_t ad = base + (((mt * 2 + hb) ^ sw) << 4);
#pragma unroll
    for (int ks = 0; ks < 8; ks++) {
      const int o = (ks * 4 + R * 2 + mt) * 4;
      ldsm_x4_t(ad + ks * 1024, wf[o], wf[o + 1], wf[o + 2], wf[o + 3]);
    }
  }
}
DEVINL void gate_up(const Ptrs& pp, uint32_t (&wf)[128], uint32_t sb, int ksl, int lane) {
  const uint4 sel = lds128u(sb + SEL_OFF);
  const int gq = lane >> 2, q4 = lane & 3;
  const int bA = (int)sel.x >> 6, bB = (int)sel.y >> 6;
  const uint4* src = &pp.mail->rowh[((gq & 1) ? bB * 2 + (bA == bB ? 1 : 0) : bA * 2) * 128 + ksl * 16 + q4];
  uint4 bf[4];
  int it = 0;
  while (true) {
#pragma unroll
    for (int u = 0; u < 4; u++) bf[u] = ld_msg(src + u * 4);
    if (__all_sync(~0u, bf[0].x != SENT && bf[1].x != SENT && bf[2].x != SENT && bf[3].x != SENT)) break;
    if (++it > SPIN_LIMIT) SPIN_FAIL(0x207);
  }
  if (lane == 0 && ksl == 4) TRACE(20);
  float acc[8][4];
#pragma unroll
  for (int i = 0; i < 8; i++) { acc[i][0] = acc[i][1] = acc[i][2] = acc[i][3] = 0.f; }
#pragma unroll
  for (int u = 0; u < 4; u++)
#pragma unroll
    for (int mt = 0; mt < 4; mt++) {
      const int o = (2 * u * 4 + mt) * 4;
      mma_16816(acc[mt], wf[o], wf[o + 1], wf[o + 2], wf[o + 3], bf[u].x, bf[u].y);
      mma_16816(acc[4 + mt], wf[o + 16], wf[o + 17], wf[o + 18], wf[o + 19], bf[u].z, bf[u].w);
    }
  if (q4 == 0) {
    const uint32_t pb = sb + PART_OFF + ksl * 512 + gq * 8;
#pragma unroll
    for (int mt = 0; mt < 4; mt++) {
      sts64(pb + mt * 128, acc[mt][0] + acc[4 + mt][0], acc[mt][1] + acc[4 + mt][1]);
      sts64(pb + mt * 128 + 64, acc[mt][2] + acc[4 + mt][2], acc[mt][3] + acc[4 + mt][3]);
    }
  }
  named_arrive<4, 384>();
}

template <int TB, int G0, int G1>
DEVINL void gemm_phase(const Ptrs& pp, float (&acc)[128], uint32_t sb, int cw, bool lag, bool elect, uint32_t rel) {
  const uint32_t bars = sb + BAR_OFF;
#pragma unroll 1
  for (int g = G0; g < G1; g++) {
    const int s = g & 3;
    mbar_wait(bars + (B_FULL + s) * 8, (g >> 2) & 1);
    const bool hold = lag && g == G1 - (TB ? FK_L1 : FK_L2);
    if (hold) {
      wg_wait<0>();
      if (rel) mbar_arrive_cluster(rel + ((g - 1) & 3) * 8);
      mbar_wait(bars + B_STAG * 8, TB ? 0 : 1);
    }
    const uint32_t sa = sb + s * STAGE;
    const uint64_t da = make_desc(sa + cw * 8192, 16, 1024), db = make_desc(sa + SLOT, TB ? 8192 : 16, 1024);
    constexpr int KB = TB ? 128 : 2;
    wg_fence();
    wgmma_n256<TB>(acc, da, db, g > G0);
    wgmma_n256<TB>(acc, da + 2, db + KB, 1);
    wg_commit();
    wg_wait<1>();
    if (rel && g > G0 && !hold) mbar_arrive_cluster(rel + ((g - 1) & 3) * 8);
    wg_fence();
    wgmma_n256<TB>(acc, da + 4, db + 2 * KB, 1);
    wgmma_n256<TB>(acc, da + 6, db + 3 * KB, 1);
    wg_commit();
  }
  if (!lag) { wg_wait<1>(); if (elect) mbar_arrive(bars + B_STAG * 8); }
}
DEVINL void gemm_finish(float (&acc)[128], uint32_t rel) {
  wg_wait<0>();
  reg_fence128(acc);
  if (rel) mbar_arrive_cluster(rel + 24);
}

__global__ void __launch_bounds__(384, 1)
fused_kernel(const Ptrs pp, const __grid_constant__ Maps maps) {
  extern __shared__ __align__(1024) uint8_t smem_raw[];
  const uint32_t c0 = (uint32_t)clock();
  if (threadIdx.x == 0) TRACE(0);
  const uint32_t sb = smem_u32(smem_raw);
  const int tid = threadIdx.x, lane = tid & 31;
  const int warp = __shfl_sync(~0u, tid >> 5, 0);
  const int rb = (int)blockIdx.x + pp.b0;
  const uint32_t bars = sb + BAR_OFF;
  auto BAR = [&](int i) { return bars + i * 8; };

  if (rb < 0) {
    const uint32_t ring = sb + warp * 16384, rbar = sb + MISC + warp * 64;
    const int row0 = FK_G0 * 128 + ((rb + NEXTRA) * 12 + warp) * 2;
    if (lane == 0) {
#pragma unroll 1
      for (int i = 0; i < 4; i++) mbar_init(rbar + i * 8, 1);
      asm volatile("fence.mbarrier_init.release.cluster;" ::: "memory");
#pragma unroll 1
      for (int i = 0; i < FK_XDEPTH; i++) { mbar_expect_tx(rbar + i * 8, 4096); bulk_load(ring + i * 4096, pp.x + (size_t)(row0 + 96 * i) * (2 * D_), 4096, rbar + i * 8); }
    }
    __syncwarp();
#pragma unroll 1
    for (int it = 0, row = row0; row < S_; it++, row += 96) {
      const uint32_t st = ring + (it & 3) * 4096;
      mbar_wait(rbar + (it & 3) * 8, (it >> 2) & 1);
      uint4 w[4], w2[4];
#pragma unroll
      for (int i = 0; i < 4; i++) { w[i] = lds128u(st + lane * 16 + i * 512); w2[i] = lds128u(st + 2048 + lane * 16 + i * 512); }
      ln_row(w); ln_row(w2);
#pragma unroll
      for (int i = 0; i < 4; i++) { sts128u(st + lane * 16 + i * 512, w[i].x, w[i].y, w[i].z, w[i].w); sts128u(st + 2048 + lane * 16 + i * 512, w2[i].x, w2[i].y, w2[i].z, w2[i].w); }
      fence_async_smem();
      __syncwarp();
      if (lane == 0) {
        if (it) { bulk_wait<0>(); red_add(&pp.cnt[((row - 96) >> 7) * 32], 2); }
        bulk_store(pp.n + (size_t)row * (2 * D_), st, 4096); bulk_commit();
        if (row + 96 * FK_XDEPTH < S_) {
          const int sn = (it + FK_XDEPTH) & 3;
          mbar_expect_tx(rbar + sn * 8, 4096); bulk_load(ring + sn * 4096, pp.x + (size_t)(row + 96 * FK_XDEPTH) * (2 * D_), 4096, rbar + sn * 8);
        }
        if (row + 96 >= S_) { bulk_wait<0>(); red_add(&pp.cnt[(row >> 7) * 32], 2); }
      }
      __syncwarp();
    }
    return;
  }
  if (warp > 4) asm volatile("barrier.cluster.arrive.relaxed.aligned;" ::: "memory");
  if ((unsigned)(warp - 4) < FK_G0) {
    const int row = (warp - 4) * 128 + rb;
    uint4 w[4];
    if (warp > 4) delay_until(c0, FK_ROW0DLY + (warp - 5) * FK_ROWDLY);
#pragma unroll
    for (int i = 0; i < 4; i++) w[i] = ldg_nc(pp.x + (size_t)row * (2 * D_) + lane * 16 + i * 512);
    if (tid == 128) TRACE(58);
    if (warp == 4) asm volatile("barrier.cluster.arrive.relaxed.aligned;" ::: "memory");
    ln_row(w);
    const uint32_t st = sb + SPARE + ((warp - 4) >> 2) * 16384 + (warp & 3) * 2048;
#pragma unroll
    for (int i = 0; i < 4; i++) sts128u(st + lane * 16 + i * 512, w[i].x, w[i].y, w[i].z, w[i].w);
    if (tid == 128) TRACE(31);
    fence_async_smem();
    __syncwarp();
    if (lane == 0) {
      bulk_store(pp.n + (size_t)row * (2 * D_), st, 2048); bulk_commit(); bulk_wait<0>();
      red_add(&pp.cnt[(warp - 4) * 32], 1);
      if (warp == 4) TRACE(1);
      if (warp == 3 + FK_G0) TRACE(55);
    }
    __syncwarp();
  }
  int m4, t;
  {
    const int c = (rb >> 1) - 2;
    int g = 8, i = c + 2;
    if (c >= 32) { i = ((c - 32) * 37) >> 8; g = c - 32 - 7 * i; g += g >= 2; i += 4; }
    else if (c >= 0) { g = c & 7; i = c >> 3; }
    if (g == 8) { g = 2; i += 6; } else if (i == 8) { i = 4 + g; g = 2; }
    m4 = (g >> 2) * 2 + (i & 1); t = (g & 3) * 4 + (i >> 1);
  }
  const int j = rb & 1, b = t * 8 + m4 * 2 + j;
  const int blk = t * 2 + j;
  if (warp >= 10) {
    delay_until(c0, warp == 10 ? FK_WS0DLY : FK_WS1DLY);
    uint32_t dummy;
    asm volatile("ld.global.nc.L1::no_allocate.L2::256B.u32 %0, [%1];" : "=r"(dummy)
                 : "l"((j ? pp.ws_im : pp.ws_re) + (size_t)(t * 128 + m4 * 32 + lane) * (2 * S_) + (warp - 10) * 256));
    sts32u(sb + SEL_OFF, dummy);
  }

  if (warp < 4) {
    uint32_t tag = ld_rlx(&pp.cnt[1]);
    if (lane == 0) {
      if (warp < 2) {
        if (warp == 0) {
          prefetch_tmap(&maps.ws[j]); prefetch_tmap(&maps.n);
          if (sb & 1023) __trap();
#pragma unroll
          for (int i = 0; i < 8; i++) mbar_init(BAR(i), bar_count(i));
        } else {
#pragma unroll
          for (int i = 8; i < 26; i++) mbar_init(BAR(i), bar_count(i));
        }
      } else if (warp == 2) {
#pragma unroll
        for (int i = 26; i < 44; i++) mbar_init(BAR(i), bar_count(i));
      } else {
#pragma unroll
        for (int i = 44; i < B_NUM; i++) mbar_init(BAR(i), bar_count(i));
#pragma unroll
        for (int i = 0; i < 4; i++) mbar_expect_tx(BAR(B_RECV + i), 8192);
      }
      asm volatile("fence.mbarrier_init.release.cluster;" ::: "memory");
    }
    named_bar<6, 128>();
    named_arrive<0, 384>();
    asm volatile("barrier.cluster.arrive.relaxed.aligned;" ::: "memory");
    uint64_t pol_first;
    asm volatile("createpolicy.fractional.L2::evict_first.b64 %0, 1.0;" : "=l"(pol_first));
    const bool moe = b < NMOE;
    uint32_t wf[128];
    auto take = [&](auto R) {
      constexpr int r = decltype(R)::value;
      const uint32_t box = sb + SPARE + warp * 8192;
      if (moe || r == 0) mbar_wait(BAR(B_WB + warp), r);
      if (moe) take_box<r>(wf, box, lane);
      asm volatile("" ::"r"(wf[124 - 8 * (1 - r)]) : "memory");
      __syncwarp();
      if (lane == 0) {
        if (r) { mbar_expect_tx(BAR(B_X), 8192); tma_2d(box, &maps.x, m4 * 256 + warp * 64, t * 128 + (1 - j) * 64, BAR(B_X)); }
        else if (moe) { mbar_expect_tx(BAR(B_WB + warp), 8192); tma_2d_hint(box, &maps.wu, b * 32, warp * 128, BAR(B_WB + warp), pol_first); }
      }
      __syncwarp();
    };

    if (warp == 0) {
      auto loadA = [&](int g) {
        mbar_expect_tx(BAR(B_FULL + (g & 3)), STAGE);
        tma_2d_hint(sb + (g & 3) * STAGE, &maps.ws[j], g * 64, t * 128, BAR(B_FULL + (g & 3)), pol_first);
      };
            auto loadB = [&](int g) { tma_3d(sb + (g & 3) * STAGE + SLOT, &maps.n, 0, g * 64, m4 * 4, BAR(B_FULL + (g & 3))); };
      unsigned ready = 0;
      delay_until(c0, FK_ADLY);
#pragma unroll 1
      for (int gi = 0; gi < 2; gi++) {
        if (lane == 0) { loadA(2 * gi); loadA(2 * gi + 1); }
        if (gi == 0) {
          if (lane == 0) TRACE(63);
          asm volatile("add.u32 %0, %0, 1;" : "+r"(tag)::"memory");
        }
        int it = 0;
        while (!((ready >> gi) & 1)) {
          ready = __ballot_sync(~0u, (int)(ld_rlx(&pp.cnt[(lane & 1) * 32]) - tag * 128u) >= 0) & 3;
          if (++it > SPIN_LIMIT) SPIN_FAIL(0x201);
        }
        fence_async_global();
        if (lane == 0) { if (gi == 0) TRACE(2); loadB(2 * gi); loadB(2 * gi + 1); }
        __syncwarp();
      }
      if (lane == 0) { prefetch_tmap(&maps.p); prefetch_tmap(&maps.wd[j]); }
      const unsigned tgt = tag * 128u;
      unsigned pend = ld_rlx(&pp.cnt[2 * 32]);
      const char* pfa = piece_addr(pp, b, lane);
      const uint32_t pfn = (lane >> 2) == 2 || lane >= 20 ? 8192 : 7168;
      auto produce1 = [&](int g0, int g1) {
#pragma unroll 1
        for (int g = g0; g < g1; g++) {
          mbar_wait(BAR(B_EMPTYH + (g & 3)), ((g >> 2) - 1) & 1);
          mbar_wait(BAR(B_EMPTY + (g & 3)), ((g >> 2) - 1) & 1);
          if (!(g & 1)) {
            if ((int)(pend - tgt) < 0) {
              int it = 0;
              while ((int)(ld_rlx(&pp.cnt[(g >> 1) * 32]) - tgt) < 0) { if (++it > SPIN_LIMIT) SPIN_FAIL(0x20c); }
            }
            fence_async_global();
            pend = ld_rlx(&pp.cnt[((g >> 1) + 1) * 32]);
          }
          if (lane == 0) {
            loadA(g); loadB(g);
          }
          if (lane == g - FK_PF0 && lane >= FK_PFSKIP) pf_bulk(pfa, pfn);
          __syncwarp();
        }
      };
      produce1(4, FK_TG);
      take(IntC<0>{});
      produce1(FK_TG, FK_TU);
      take(IntC<1>{});
      produce1(FK_TU, 32);
      int sib = 0, pc = 0;
      auto produce2 = [&](int q0, int q1) {
#pragma unroll 1
        for (int q = q0; q < q1; q++) {
          const int s = q & 3, k0 = sibling(m4, sib) * 256 + pc * 64;
          const uint32_t sa = sb + s * STAGE;
          mbar_wait(BAR(B_EMPTY + s), ((q >> 2) + 1) & 1);
          if (lane == 0) {
            mbar_expect_tx(BAR(B_FULL + s), q < 4 ? 2 * SLOT : STAGE);
            tma_2d(sa + SLOT, &maps.wd[j], k0, m4 * 256, BAR(B_FULL + s));
          }
          __syncwarp();
          if (q >= 4) {
            mbar_wait(BAR(B_RDY - 4 + q), 0);
            if (lane == 0) tma_2d(sa, &maps.p, k0, j * S_ + t * 128, BAR(B_FULL + s));
            if (++sib == 4) { sib = 1; pc++; }
          } else if (++pc == 4) { pc = 0; sib = 1; }
          if (lane == 32 + q - FK_PF0 && lane < 27) pf_bulk(pfa, pfn);
          if (q == FK_MAILQ && lane == 0) pf_bulk(reinterpret_cast<const char*>(pp.mail) + (size_t)b * (MAIL_PER_CTA * 16), MAIL_PER_CTA * 16);
          __syncwarp();
        }
      };
      produce2(0, 16);
      mbar_wait(BAR(B_EMPTY + 0), 1);
      if (moe) {
        if (lane == 0) {
          mbar_expect_tx(BAR(B_GU), 16384);
          tma_2d(sb, &maps.wg, b * 32, 512, BAR(B_GU));
          tma_2d(sb + 8192, &maps.wu, b * 32, 512, BAR(B_GU));
        }
        mbar_wait(BAR(B_EMPTY + 1), 1);
        if (lane == 0) {
          mbar_expect_tx(BAR(B_GU), 49152);
#pragma unroll 1
          for (int i = 0; i < 3; i++) {
            tma_2d(sb + STAGE + i * SLOT, &maps.wg, b * 32, 640 + i * 128, BAR(B_GU));
            tma_2d(sb + STAGE + i * SLOT + 8192, &maps.wu, b * 32, 640 + i * 128, BAR(B_GU));
          }
        }
        mbar_wait(BAR(B_EMPTY + 2), 1);
        if (lane == 0) {
          mbar_expect_tx(BAR(B_DN), 49152);
#pragma unroll 1
          for (int i = 0; i < 3; i++) tma_3d(sb + 2 * STAGE + i * SLOT, &maps.wdn, 0, b * 32, i * 4, BAR(B_DN));
        }
        mbar_wait(BAR(B_XDONE), 0);
        if (lane == 0) {
          mbar_expect_tx(BAR(B_DN), 16384);
          tma_3d(sb + SPARE, &maps.wdn, 0, b * 32, 12, BAR(B_DN));
        }
      }
      __syncwarp();
    } else if (warp == 1) {
      asm volatile("add.u32 %0, %0, 1;" : "+r"(tag)::"memory");
      if (lane == 0) prefetch_tmap(&maps.ps);
      float a0 = 0.f, a1 = 0.f;
      auto rowsum = [&](int g0, int g1) {
        const uint32_t rb = sb + (m4 * 32 + lane) * 128 + ((lane & 7) << 4);
#pragma unroll 1
        for (int g = g0; g < g1; g++) {
          const int s = g & 3;
          mbar_wait(BAR(B_FULL + s), (g >> 2) & 1);
          uint4 u[8];
#pragma unroll
          for (int c = 0; c < 8; c++) u[c] = lds128u((rb ^ (uint32_t)(c << 4)) + s * STAGE);
#pragma unroll
          for (int c = 0; c < 8; c += 2) { a0 += sum8(u[c]); a1 += sum8(u[c + 1]); }
          asm volatile("" : "+f"(a0), "+f"(a1)::"memory");
          __syncwarp();
          if (lane == 0) mbar_arrive(BAR(B_EMPTYH + s));
        }
      };
      rowsum(0, FK_TG - 2);
      take(IntC<0>{});
      rowsum(FK_TG - 2, 28);
      mbar_wait(BAR(B_MODOK), 0);
      a0 += lds32(sb + RS_OFF + 256 + lane * 4);
      __syncwarp();
      uint2* rsp = &pp.mail->rs[(j * 16 + t) * 128 + lane];
      st_msg8(rsp + m4 * 32, __float_as_uint(a0 + a1), tag);
      {
        uint2 m[4]; int it = 0;
        while (true) {
#pragma unroll
          for (int i = 0; i < 4; i++) m[i] = ld_msg8(rsp + 32 * i);
          if (__all_sync(~0u, m[0].y == tag && m[1].y == tag && m[2].y == tag && m[3].y == tag)) break;
          if (++it > SPIN_LIMIT) SPIN_FAIL(0x208);
        }
#pragma unroll
        for (int i = 0; i < 4; i++) sts32u(sb + RS_OFF + (lane + 32 * i) * 4, pack_bf16(__uint_as_float(m[i].x), __uint_as_float(m[i].x)));
      }
      __syncwarp();
      if (lane == 0) { mbar_arrive(BAR(B_T1)); TRACE(11); }
      take(IntC<1>{});
      {
        unsigned* fl = &pp.mail->flagP[(((j * 16 + t) * 4 + m4) * 4) * 8];
        uint32_t cn = 0;
#pragma unroll 1
        for (int i = 0; i < 16; i++) {
          const int pr = (0x73625410u >> (4 * ((i >> 1) & 7))) & 7, q = pr & 3, half = pr < 4 ? 1 - j : j;
          if (i < 8) mbar_wait(BAR(B_PRDY + (q ? pr | 3 : pr)), 0);
          if (i) delay_until(cn, FK_PPACE);
          cn = (uint32_t)clock();
          if (lane == 0) {
            tma_store_2d(&maps.ps, sb + q * STAGE + half * 8192 + (i & 1) * 4096, m4 * 256 + q * 64, j * S_ + t * 128 + half * 64 + (i & 1) * 32);
            bulk_commit();
            if (i == 5 || i == 7 || i == 11 || i == 15) {
              const int dq = (i - 3) >> 2;
              bulk_wait<0>(); st_rlx(fl + dq * 8, tag); mbar_arrive(BAR(B_RDY + dq));
              if (i == 5) TRACE(29);
            }
          }
          __syncwarp();
        }
        if (lane == 0) TRACE(8);
      }
      named_bar<7, 64>();
      delay_until((uint32_t)clock(), FK_E2DLY);
      uint4 m; int it = 0;
      while (true) {
        m = ld_msg(&pp.mail->cand[b * 32 + lane]);
        if (__all_sync(~0u, m.w == tag)) break;
        if (++it > SPIN_LIMIT) SPIN_FAIL(0x206);
      }
      uint32_t k1, k2; int i1, i2;
      warp_top2(m.x, (int)(m.z & 0xFFFF), m.y, (int)(m.z >> 16), k1, i1, k2, i2);
      if (lane == 0) {
        sts128u(sb + SEL_OFF, i1, i2, k1, k2);
        mbar_arrive(BAR(B_SEL));
        TRACE(19);
      }
    } else {
      const int kh = warp - 2;
      const uint32_t reg = sb + SPARE + kh * 16384;
#pragma unroll 1
      for (int i = 0; i < 2; i++) {
        const uint4 cw4 = ldg_nc(pp.c + (kh * 64 + lane + 32 * i) * 16);
        const uint32_t ad = reg + 12288 + (lane + 32 * i) * 32;
        sts128(ad, round_bf16(silu_f(bf_lo(cw4.x))), round_bf16(silu_f(bf_hi(cw4.x))), round_bf16(silu_f(bf_lo(cw4.y))), round_bf16(silu_f(bf_hi(cw4.y))));
        sts128(ad + 16, round_bf16(silu_f(bf_lo(cw4.z))), round_bf16(silu_f(bf_hi(cw4.z))), round_bf16(silu_f(bf_lo(cw4.w))), round_bf16(silu_f(bf_hi(cw4.w))));
        if (kh) { sts128u(sb + T1_OFF + (lane + 32 * i) * 32, SENT, SENT, SENT, SENT); sts128u(sb + T1_OFF + (lane + 32 * i) * 32 + 16, SENT, SENT, SENT, SENT); }
      }
      asm volatile("add.u32 %0, %0, 1;" : "+r"(tag)::"memory");
      fence_async_smem();
      if (lane == 0) prefetch_tmap(&maps.wm);
      {
        float acc[3][8];
        uint32_t sad[3];
#pragma unroll
        for (int a = 0; a < 3; a++) {
          sad[a] = reg + 12288 + ((32 * a + lane) / 6) * 4;
#pragma unroll
          for (int i = 0; i < 8; i++) acc[a][i] = 0.f;
        }
        const char* wpf = pp.wm + (size_t)kh * (512 * 12 * D_) + b * 6144;
        const char* wsrc = (j ? pp.ws_im : pp.ws_re) + (size_t)(t * 128 + m4 * 32 + kh * 16 - 16) * (2 * S_) + 28 * 128 + lane * 16;
        mbar_wait(BAR(B_FULL), 0);
        if (FK_WMPF && lane == 0) pf_bulk(wpf, 6144);
        uint32_t cn = (uint32_t)clock() + FK_PACE0 + (1 - kh) * (FK_PACE / 2);
        auto request = [&](int c) {
          mbar_expect_tx(BAR(B_WM + kh * 2 + (c & 1)), 6144);
          tma_2d_hint(reg + (c & 1) * 6144, &maps.wm, b * 48, kh * 512 + c * 64, BAR(B_WM + kh * 2 + (c & 1)), pol_first);
        };
        uint4 e[4];
#pragma unroll 1
        for (int c = -2; c < 8; c++) {
          while ((int)((uint32_t)clock() - cn) < 0) __nanosleep(40);
          cn += c < 0 ? FK_PACE0 : FK_PACE;
          if (lane == 0) {
            if (FK_WMPF && c < 5) pf_bulk(wpf + (size_t)(c + 3) * (64 * 12 * D_), 6144);
            if (c == FK_RSTEP && kh) {
              char* mb = reinterpret_cast<char*>(pp.mail) + (size_t)b * (MAIL_PER_CTA * 16);
#pragma unroll 1
              for (int o = 0; o < MAIL_PER_CTA * 16; o += 2048) bulk_store(mb + o, sb + T1_OFF, min(2048, MAIL_PER_CTA * 16 - o));
              bulk_commit();
            }
          }
          __syncwarp();
          if (c < 0) {
            if (c == -2) mbar_wait(BAR(B_EMPTY), 0);
            if (lane == 0) request(c + 2);
            __syncwarp();
            continue;
          }
          if (c >= 4) {
            const float v0 = sum8(e[0]), v1 = sum8(e[1]), v2 = sum8(e[2]), v3 = sum8(e[3]);
            const bool u4 = lane & 16, u3 = lane & 8;
            const float w0 = (u4 ? v2 : v0) + __shfl_xor_sync(~0u, u4 ? v0 : v2, 16), w1 = (u4 ? v3 : v1) + __shfl_xor_sync(~0u, u4 ? v1 : v3, 16);
            float v = (u3 ? w1 : w0) + __shfl_xor_sync(~0u, u3 ? w0 : w1, 8);
            v += __shfl_xor_sync(~0u, v, 4); v += __shfl_xor_sync(~0u, v, 2); v += __shfl_xor_sync(~0u, v, 1);
            if (!(lane & 7)) sts32(sb + RS_OFF + 256 + (kh * 16 + c * 4 - 16 + (lane >> 3)) * 4, v);
          }
          if (c >= 3 && c < 7) {
#pragma unroll
            for (int i = 0; i < 4; i++) e[i] = ldg_nc(wsrc + (size_t)(c * 4 + 4 + i) * (2 * S_));
          }
          mbar_wait(BAR(B_WM + kh * 2 + (c & 1)), (c >> 1) & 1);
#pragma unroll
          for (int u = 0; u < 12; u++) {
            const uint4 v = lds128u(reg + (c & 1) * 6144 + lane * 16 + u * 512);
            const float sc = lds32(sad[u % 3] + (u / 3) * 64);
            float (&ac)[8] = acc[u % 3];
            ac[0] = fmaf(sc, bf_lo(v.x), ac[0]); ac[1] = fmaf(sc, bf_hi(v.x), ac[1]);
            ac[2] = fmaf(sc, bf_lo(v.y), ac[2]); ac[3] = fmaf(sc, bf_hi(v.y), ac[3]);
            ac[4] = fmaf(sc, bf_lo(v.z), ac[4]); ac[5] = fmaf(sc, bf_hi(v.z), ac[5]);
            ac[6] = fmaf(sc, bf_lo(v.w), ac[6]); ac[7] = fmaf(sc, bf_hi(v.w), ac[7]);
          }
#pragma unroll
          for (int a = 0; a < 3; a++) sad[a] += 256;
          asm volatile("" ::"f"(acc[0][0]), "f"(acc[1][0]), "f"(acc[2][0]) : "memory");
          __syncwarp();
          if (lane == 0 && c < 6) request(c + 2);
        }
        __syncwarp();
#pragma unroll
        for (int a = 0; a < 3; a++) {
          sts128(reg + (32 * a + lane) * 32, acc[a][0], acc[a][1], acc[a][2], acc[a][3]);
          sts128(reg + (32 * a + lane) * 32 + 16, acc[a][4], acc[a][5], acc[a][6], acc[a][7]);
        }
        __syncwarp();
        float s0 = 0.f, s1 = 0.f;
#pragma unroll 8
        for (int m = 0; m < 16; m++) { const float2 v = lds64(reg + (lane < 24 ? lane * 8 : 0) + m * 192); s0 += v.x; s1 += v.y; }
        if (kh == 0) sts64(sb + RS_OFF + lane * 8, s0, s1);
        if (lane == 0) TRACE(80 + kh);
        named_bar<5, 64>();
        if (kh == 1) {
          const float2 p = lds64(sb + RS_OFF + lane * 8);
          __syncwarp();
          sts32u(sb + RS_OFF + lane * 4, pack_bf16(s0 + p.x, s1 + p.y));
          fence_async_smem();
          __syncwarp();
          if (lane == 0) {
            bulk_store(pp.mod + b * 24, sb + RS_OFF, 96); bulk_commit(); bulk_wait<0>();
            red_add(&pp.cnt[16 * 32], 1);
            TRACE(9);
          }
          __syncwarp();
        }
      }
      if (kh == 0) {
        if (lane == 0) { mbar_arrive(BAR(B_MODOK)); TRACE(57); }
#pragma unroll 1
        for (int i = 0; i < 4; i++) {
          const int w = i ^ 2;
          if (lane == 0) {
            if (moe) { mbar_expect_tx(BAR(B_WB + w), 8192); tma_2d_hint(sb + SPARE + w * 8192, &maps.wg, b * 32, w * 128, BAR(B_WB + w), pol_first); }
            else mbar_arrive(BAR(B_WB + w));
          }
          __nanosleep(FK_BSLEEP);
        }
        take(IntC<0>{});
        take(IntC<1>{});
        if (lane == 0) TRACE(98);
        const unsigned* flagAddr = &pp.mail->flagP[(((j * 16 + t) * 4 + sibling(m4, 1 + lane % 3)) * 4 + ((lane / 3) & 3)) * 8];
        mbar_wait(BAR(B_PRDY + 7), 0);
        bool done = lane >= 12; int it = 0;
        while (true) {
          if (!done && ld_rlx(flagAddr) == tag) {
            fence_async_global(); mbar_arrive(BAR(B_RDY + lane)); done = true;
          }
          if (__all_sync(~0u, done)) break;
          if (++it > SPIN_LIMIT) SPIN_FAIL(0x202);
        }
        if (lane == 0) TRACE(99);
      } else {
        take(IntC<0>{});
        {
          const unsigned tgt = tag * 128u; int it = 0;
          while ((int)(ld_rlx(&pp.cnt[16 * 32]) - tgt) < 0) { __nanosleep(100); if (++it > SPIN_LIMIT) SPIN_FAIL(0x204); }
        }
        if (lane == 0) { mbar_arrive(BAR(B_MODOK)); TRACE(10); }
        {
          const uint32_t sgn = j ? 0x80008000u : 0u;
          uint32_t sa[4], ca[4]; uint4 sv[4], cv[4], wr[4];
#pragma unroll
          for (int i = 0; i < 4; i++) {
            const int p = lane + 32 * i;
            sa[i] = ld_rlx(pp.mod + m4 * 128 + p); ca[i] = ld_rlx(pp.mod + 512 + m4 * 128 + p);
            sv[i] = ld_msg(reinterpret_cast<const uint4*>(pp.mod + 1536) + p); cv[i] = ld_msg(reinterpret_cast<const uint4*>(pp.mod + 2048) + p);
            wr[i] = ldg_nc(pp.wr + p * 16);
          }
          float c1 = 0.f, c2 = 0.f;
#pragma unroll
          for (int i = 0; i < 4; i++) {
            const int p = lane + 32 * i;
            sts64(sb + T1_OFF + ((p >> 3) * 4 + (p & 3)) * 16 + ((p >> 2) & 1) * 8, __uint_as_float(add1_bf2(ca[i]) ^ sgn), __uint_as_float(sa[i] ^ sgn));
            const uint32_t s4[4] = {sv[i].x, sv[i].y, sv[i].z, sv[i].w}, c4[4] = {cv[i].x, cv[i].y, cv[i].z, cv[i].w}, w4[4] = {wr[i].x, wr[i].y, wr[i].z, wr[i].w};
#pragma unroll
            for (int u = 0; u < 4; u++) {
              const uint32_t A = add1_bf2(c4[u]);
              c1 = fmaf(bf_lo(A), bf_lo(w4[u]), c1); c1 = fmaf(bf_hi(A), bf_hi(w4[u]), c1);
              c2 = fmaf(bf_lo(s4[u]), bf_lo(w4[u]), c2); c2 = fmaf(bf_hi(s4[u]), bf_hi(w4[u]), c2);
            }
          }
#pragma unroll
          for (int o = 16; o; o >>= 1) { c1 += __shfl_xor_sync(~0u, c1, o); c2 += __shfl_xor_sync(~0u, c2, o); }
          __syncwarp();
          if (lane == 0) { sts128(sb + CST_OFF, c1, c2, __uint_as_float(tag), 0.f); mbar_arrive(BAR(B_T1)); TRACE(30); }
        }
        take(IntC<1>{});
        const int G = lane >> 2, q = lane & 3, p0 = m4 * 128 + G * 16 + q;
        mbar_wait(BAR(B_PRDY + 3), 0);
        mbar_wait(BAR(B_PRDY + 7), 0);
        uint32_t ga[4], hi[4], lo[4];
#pragma unroll
        for (int u = 0; u < 4; u++) {
          ga[u] = ld_rlx(pp.mod + 1024 + p0 + 4 * u);
          const uint32_t cb = ld_rlx(pp.mod + 2048 + p0 + 4 * u), wr = __ldg(reinterpret_cast<const uint32_t*>(pp.wr) + p0 + 4 * u);
          const float w0 = bf_lo(add1_bf2(cb)) * bf_lo(wr), w1 = bf_hi(add1_bf2(cb)) * bf_hi(wr);
          hi[u] = pack_bf16(w0, w1);
          lo[u] = pack_bf16(w0 - bf_lo(hi[u]), w1 - bf_hi(hi[u]));
        }
        sts128u(sb + GA_OFF + lane * 16, ga[0], ga[1], ga[2], ga[3]);
        sts128u(sb + W_OFF + G * 144 + q * 16, hi[0], hi[1], hi[2], hi[3]);
        sts128u(sb + W_OFF + G * 144 + 64 + q * 16, lo[0], lo[1], lo[2], lo[3]);
        sts32u(sb + W_OFF + G * 144 + 128 + q * 4, 0x3F803F80u);
        __syncwarp();
        if (lane == 0) mbar_arrive(BAR(B_T2));
      }
    }
    mbar_wait(BAR(B_SEL), 0);
    const uint32_t csel = (uint32_t)clock();
    if (moe) gate_up(pp, wf, sb, warp, lane);
    if (warp == 1) {
      const uint4 sel = lds128u(sb + SEL_OFF);
      const int bA = (int)sel.x >> 6, bB = (int)sel.y >> 6;
      const int n = (lane >> 3) & 1;
      const int col = (b >> 4) * 128 + (lane & 1) * 64 + ((b >> 2) & 3) * 16 + (b & 3) * 2 + ((lane >> 1) & 1) + (lane >> 4) * 8;
      const int wofs = ((n ? bB * 2 + (bA == bB ? 1 : 0) : bA * 2) * 128 + (col >> 5) * 4 + ((col >> 1) & 3)) * 4 + ((col >> 3) & 3);
      const uint32_t gbp = ld_rlx(pp.mod + 2560 + (col >> 1));
      uint32_t hp, xp; int it = 0;
      while (true) {
        hp = ld_rlx(reinterpret_cast<const uint32_t*>(pp.mail->rowh) + wofs); xp = ld_rlx(reinterpret_cast<const uint32_t*>(pp.mail->rowx) + wofs);
        if (__all_sync(~0u, hp != SENT && xp != SENT)) break;
        if (++it > SPIN_LIMIT) SPIN_FAIL(0x2ff);
      }
      const float sg = round_bf16(sigmoid_f(round_bf16(fkey_inv(n ? sel.w : sel.z))));
      const int gq = lane >> 2;
      const uint32_t one = (lane & 1) == (gq >> 2) ? ((gq & 1) ? 0x3F800000u : 0x00003F80u) : 0u;
      const uint32_t s0 = (gq & 2) ? 0u : one, s1 = (gq & 2) ? one : 0u;
      const uint4* src = &pp.mail->part[(size_t)b * (NMOE * 2) + lane];
      uint4 m[7];
      delay_until(csel, FK_E4DLY);
      it = 0;
      while (true) {
        bool ok = true;
#pragma unroll
        for (int i = 0; i < 7; i++) m[i] = ld_msg(src + 32 * i);
#pragma unroll
        for (int i = 0; i < 7; i++) ok &= m[i].x != SENT;
        if (__all_sync(~0u, ok)) break;
        if (++it > SPIN_LIMIT) SPIN_FAIL(0x20b);
      }
      if (lane == 0) TRACE(23);
      float c[3][4];
#pragma unroll
      for (int i = 0; i < 3; i++) { c[i][0] = c[i][1] = c[i][2] = c[i][3] = 0.f; }
#pragma unroll
      for (int i = 0; i < 7; i++) mma_16816(c[i % 3], m[i].x, m[i].y, m[i].z, m[i].w, s0, s1);
#pragma unroll
      for (int i = 0; i < 4; i++) c[0][i] += c[1][i] + c[2][i];
      const bool u4 = lane & 16, u3 = lane & 8;
      const float a0 = (u4 ? c[0][2] : c[0][0]) + __shfl_xor_sync(~0u, u4 ? c[0][0] : c[0][2], 16), a1 = (u4 ? c[0][3] : c[0][1]) + __shfl_xor_sync(~0u, u4 ? c[0][1] : c[0][3], 16);
      float y = (u3 ? a1 : a0) + __shfl_xor_sync(~0u, u3 ? a0 : a1, 8);
      y += __shfl_xor_sync(~0u, y, 4);
      const bool odd = col & 1;
      const float upd = round_bf16(round_bf16(y) * sg);
      const float o = fmaf(odd ? bf_hi(gbp) : bf_lo(gbp), (odd ? bf_hi(hp) : bf_lo(hp)) + upd, odd ? bf_hi(xp) : bf_lo(xp));
      if (!(lane & 4)) reinterpret_cast<__nv_bfloat16*>(pp.out)[(size_t)(n ? sel.y : sel.x) * D_ + col] = __float2bfloat16_rn(o);
      if (lane == 0) { TRACE(24); TRACE_CLK(54); if (b == 0) pp.cnt[1] = tag; }
    }
  } else {
    const int cw = (warp - 4) >> 2;
    const int wq = warp & 3;
    const int wtid = tid & 127;
    const int gq = lane >> 2, q4 = lane & 3;
    const bool lag = cw == j;
    const bool elect = wtid == 0;
    const uint32_t rel = wtid < 2 ? mapa(BAR(B_EMPTY), wtid) : 0;

    named_bar<0, 384>();
    asm volatile("barrier.cluster.wait.acquire.aligned;" ::: "memory");

    const int mrow = wq * 16 + (lane & 7) + ((lane >> 3) & 1) * 8;
    {
      float acc[128];
      gemm_phase<1, 0, 32>(pp, acc, sb, cw, lag, elect, rel);
      mbar_wait(BAR(B_T1), 0);
      const uint32_t tad = sb + T1_OFF + q4 * 16;
      uint4 tb[16];
#pragma unroll
      for (int c = 0; c < 4; c++) tb[c] = lds128u(tad + c * 64);
      const uint32_t rs0 = lds32u(sb + RS_OFF + (cw * 64 + wq * 16 + gq) * 4), rs1 = lds32u(sb + RS_OFF + (cw * 64 + wq * 16 + gq + 8) * 4);
      const uint32_t dst = sb + cw * 8192 + mrow * 128, pb = BAR(B_PRDY + (lag ? 4 : 0));
      gemm_finish(acc, rel);
      if (elect) { TRACE(lag ? 5 : 4); if (lag) TRACE_CLK(51); }
#pragma unroll
      for (int i = 0; i < 16; i++) {
        uint32_t r[4];
        const int o = 8 * i;
        r[0] = fma_bf2(pack_bf16(acc[o], acc[o + 1]), tb[i].x, mul_bf2(rs0, tb[i].y));
        r[1] = fma_bf2(pack_bf16(acc[o + 2], acc[o + 3]), tb[i].x, mul_bf2(rs1, tb[i].y));
        r[2] = fma_bf2(pack_bf16(acc[o + 4], acc[o + 5]), tb[i].z, mul_bf2(rs0, tb[i].w));
        r[3] = fma_bf2(pack_bf16(acc[o + 6], acc[o + 7]), tb[i].z, mul_bf2(rs1, tb[i].w));
        if (i < 12) tb[i + 4] = lds128u(tad + (i + 4) * 64);
        stsm_x4(dst + (i >> 2) * STAGE + (uint32_t)(((((2 * i) & 7) + (lane >> 4)) ^ (lane & 7)) << 4), r[0], r[1], r[2], r[3]);
        if (i == 3 || i == 15) {
          fence_async_smem();
          __syncwarp();
          if (lane == 0) mbar_arrive(pb + (i >> 2) * 8);
        }
      }
      mbar_wait(pb + 24, 0);
    }
    if (elect) TRACE(lag ? 7 : 6);
    float acc[128];
    gemm_phase<0, 32, 48>(pp, acc, sb, cw, lag, elect, rel);

    if (!lag) {
      const uint32_t rdst = mapa(sb + RECV_OFF + wtid * 16, j ^ 1), rbar = mapa(BAR(B_RECV), j ^ 1);
      mbar_wait(BAR(B_T2), 0);
      mbar_wait(BAR(B_X), 0);
      mbar_wait_cluster(BAR(B_EMPTY), 1);
      uint32_t xf[16][4]; uint4 ga[8];
      auto fetch = [&](int i) {
        ldsm_x4(sb + SPARE + (i >> 2) * 8192 + mrow * 128 + (uint32_t)(((((2 * i) & 7) + (lane >> 4)) ^ (lane & 7)) << 4), xf[i][0], xf[i][1], xf[i][2], xf[i][3]);
        if (!(i & 1)) ga[i >> 1] = lds128u(sb + GA_OFF + ((i >> 1) * 4 + q4) * 16);
      };
      fetch(0); fetch(1); fetch(2);
      gemm_finish(acc, rel);
      if (elect) TRACE(12);
      uint32_t cbp, sbp, gbp;
#pragma unroll
      for (int i = 0; i < 16; i++) {
        const int o = 8 * i;
        const uint32_t g0 = (i & 1) ? ga[i >> 1].z : ga[i >> 1].x, g1 = (i & 1) ? ga[i >> 1].w : ga[i >> 1].y;
        const uint32_t w0 = fma_bf2(g0, pack_bf16(acc[o], acc[o + 1]), xf[i][0]), w1 = fma_bf2(g0, pack_bf16(acc[o + 2], acc[o + 3]), xf[i][1]);
        const uint32_t w2 = fma_bf2(g1, pack_bf16(acc[o + 4], acc[o + 5]), xf[i][2]), w3 = fma_bf2(g1, pack_bf16(acc[o + 6], acc[o + 7]), xf[i][3]);
        if (i == 0) { fetch(3); fetch(4); } else if (i < 12) fetch(i + 4);
        if (i == 8) { cbp = ld_rlx(pp.mod + 2048 + m4 * 128 + wtid); sbp = ld_rlx(pp.mod + 1536 + m4 * 128 + wtid); gbp = ld_rlx(pp.mod + 2560 + m4 * 128 + wtid); }
        asm volatile("st.async.weak.shared::cluster.mbarrier::complete_tx::bytes.v4.b32 [%0], {%1, %2, %3, %4}, [%5];"
                     ::"r"(rdst + i * 2048), "r"(w0), "r"(w1), "r"(w2), "r"(w3), "r"(rbar + (i >> 2) * 8) : "memory");
      }
      named_bar<1, 128>();
      if (elect) { mbar_arrive(BAR(B_XDONE)); TRACE(13); }
      {
        const float A0 = round_bf16(1.f + bf_lo(cbp)), A1 = round_bf16(1.f + bf_hi(cbp));
        sts128(sb + GH_OFF + wtid * 16, bf_lo(gbp) * A0, bf_hi(gbp) * A1, bf_lo(gbp) * bf_lo(sbp), bf_hi(gbp) * bf_hi(sbp));
        const uint32_t fo = ((wtid >> 4) * 4 + (wtid & 3)) * 16 + ((wtid >> 2) & 3) * 4;
        sts32u(sb + TA_OFF + fo, pack_bf16(A0, A1)); sts32u(sb + TS_OFF + fo, sbp);
      }
      named_bar<1, 128>();
      if (elect) mbar_arrive(BAR(B_T3));
      if (b < NMOE) {
        uint32_t wf[128];
        mbar_wait(BAR(B_GU), 0);
        const uint32_t box = sb + (wq ? STAGE + (wq - 1) * SLOT : 0);
        take_box<0>(wf, box, lane);
        take_box<1>(wf, box + 8192, lane);
        if (elect) TRACE(26);
        mbar_wait(BAR(B_SEL), 0);
        gate_up(pp, wf, sb, 4 + wq, lane);
      }
    } else {
      mbar_wait(BAR(B_T2), 0);
      uint32_t xa[64];
      float dl[4] = {0.f, 0.f, 0.f, 0.f}, d2[4] = {0.f, 0.f, 0.f, 0.f}, d3[4] = {0.f, 0.f, 0.f, 0.f};
      {
        const uint32_t wad = sb + W_OFF + ((gq & 2) ? 128 : (gq & 1) * 64 + q4 * 16);
        uint4 rv[16], wb[8], ga[8];
        auto fetch = [&](int i) {
          if (!(i & 3)) mbar_wait_cluster(BAR(B_RECV + (i >> 2)), 0);
          rv[i] = lds128u(sb + RECV_OFF + i * 2048 + wtid * 16);
          if (!(i & 1)) ga[i >> 1] = lds128u(sb + GA_OFF + ((i >> 1) * 4 + q4) * 16); else wb[i >> 1] = lds128u(wad + (i >> 1) * 144);
        };
        fetch(0); fetch(1);
        gemm_finish(acc, rel);
        if (elect) { TRACE(14); TRACE_CLK(53); }
#pragma unroll
        for (int i = 0; i < 16; i++) {
          const int o = 8 * i;
          const uint32_t g0 = (i & 1) ? ga[i >> 1].z : ga[i >> 1].x, g1 = (i & 1) ? ga[i >> 1].w : ga[i >> 1].y;
          const uint32_t a0 = fma_bf2(g0, pack_bf16(acc[o], acc[o + 1]), rv[i].x), a1 = fma_bf2(g0, pack_bf16(acc[o + 2], acc[o + 3]), rv[i].y);
          const uint32_t a2 = fma_bf2(g1, pack_bf16(acc[o + 4], acc[o + 5]), rv[i].z), a3 = fma_bf2(g1, pack_bf16(acc[o + 6], acc[o + 7]), rv[i].w);
          if (i < 14) fetch(i + 2);
          xa[4 * i] = a0; xa[4 * i + 1] = a1; xa[4 * i + 2] = a2; xa[4 * i + 3] = a3;
          mma_1688(d2, a0, a1, a0); mma_1688(d3, a0, a1, a1);
          mma_1688(d2, a2, a3, a2); mma_1688(d3, a2, a3, a3);
          if (i & 1) {
            mma_16816(dl, xa[4 * i - 4], xa[4 * i - 3], xa[4 * i - 2], xa[4 * i - 1], wb[i >> 1].x, wb[i >> 1].y);
            mma_16816(dl, a0, a1, a2, a3, wb[i >> 1].z, wb[i >> 1].w);
          }
        }
      }
      const uint32_t tag = lds32u(sb + CST_OFF + 8);
      {
        const bool odd = q4 & 1;
        const float mine = odd ? dl[2] : dl[0] + dl[1];
        const float other = __shfl_xor_sync(~0u, odd ? dl[0] : dl[2] + dl[3], 1);
        const int dsrc = (lane & ~3) | (gq >> 1);
        const float qa = __shfl_sync(~0u, (gq & 1) ? d2[1] : d2[0], dsrc), qb = __shfl_sync(~0u, (gq & 1) ? d3[3] : d3[2], dsrc);
        if (q4 < 2) st_msg(&pp.mail->stats[(blk * 4 + m4) * 64 + wq * 16 + gq + 8 * q4], __float_as_uint(odd ? mine : other), __float_as_uint(odd ? qb : qa),
                           __float_as_uint(odd ? other : mine), tag);
      }
      if (elect) TRACE(15);
      float rstd, nm, rme;
      {
        const uint4* src = &pp.mail->stats[(blk * 4 + (lane >> 4) * 2) * 64 + wq * 16 + (lane & 15)];
        const float2 cst = lds64(sb + CST_OFF);
        uint4 m0, m1; int it = 0;
        delay_until((uint32_t)clock(), FK_E1DLY);
        while (true) {
          m0 = ld_msg(src); m1 = ld_msg(src + 64);
          if (__all_sync(~0u, m0.w == tag && m1.w == tag)) break;
          if (++it > SPIN_LIMIT) SPIN_FAIL(0x209);
        }
        float sa = __uint_as_float(m0.x) + __uint_as_float(m1.x), qa = __uint_as_float(m0.y) + __uint_as_float(m1.y), da = __uint_as_float(m0.z) + __uint_as_float(m1.z);
        sa += __shfl_xor_sync(~0u, sa, 16); qa += __shfl_xor_sync(~0u, qa, 16); da += __shfl_xor_sync(~0u, da, 16);
        const float mean = sa * (1.f / D_);
        rstd = rsqrtf(fmaxf(fmaf(-mean, mean, qa * (1.f / D_)), 0.f) + 1e-5f);
        nm = -mean * rstd;
        rme = fmaf(rstd, fmaf(-mean, cst.x, da), cst.y);
      }
      if (elect) TRACE(16);
      int bi1, bi2;
      {
        uint32_t k1, k2; int i1, i2;
        warp_top2(lane < 16 ? fkey(rme) : 0u, blk * 64 + wq * 16 + (lane & 15), 0u, 0, k1, i1, k2, i2);
        if (lane == 0) sts128u(sb + TOP_OFF + wq * 16, k1, k2, i1, i2);
        named_bar<2, 128>();
        uint4 c = make_uint4(0, 0, 0, 0);
        if (lane < 4) c = lds128u(sb + TOP_OFF + lane * 16);
        warp_top2(c.x, (int)c.z, c.y, (int)c.w, k1, bi1, k2, bi2);
        if (wq == 0) { st_msg(&pp.mail->cand[(m4 * 32 + lane) * 32 + blk], k1, k2, (uint32_t)bi1 | ((uint32_t)bi2 << 16), tag); named_arrive<7, 64>(); }
      }
      if (elect) TRACE(17);
      mbar_wait(BAR(B_T3), 0);
#pragma unroll 1
      for (int ci = 0; ci < 2; ci++) {
        const int lr = (ci ? bi2 : bi1) - blk * 64;
        if ((lr >> 4) == wq) {
          const uint32_t scr = sb + SCR_OFF + wq * 512;
          const bool up = lr & 8;
          if (gq == (lr & 7)) {
#pragma unroll
            for (int G = 0; G < 8; G++)
              sts128u(scr + (G * 4 + q4) * 16, up ? xa[8 * G + 1] : xa[8 * G], up ? xa[8 * G + 3] : xa[8 * G + 2], up ? xa[8 * G + 5] : xa[8 * G + 4], up ? xa[8 * G + 7] : xa[8 * G + 6]);
          }
          __syncwarp();
          const float rs_ = __shfl_sync(~0u, rstd, lr & 15), nm_ = __shfl_sync(~0u, nm, lr & 15);
          const uint4 v = lds128u(scr + lane * 16), A = lds128u(sb + TA_OFF + lane * 16), S = lds128u(sb + TS_OFF + lane * 16);
          auto h2 = [&](uint32_t xv, uint32_t av, uint32_t sv) {
            return pack_bf16(fmaf(fmaf(bf_lo(xv), rs_, nm_), bf_lo(av), bf_lo(sv)), fmaf(fmaf(bf_hi(xv), rs_, nm_), bf_hi(av), bf_hi(sv)));
          };
          const int o = (blk * 2 + ci) * 128 + m4 * 32 + lane;
          st_msg(&pp.mail->rowh[o], h2(v.x, A.x, S.x), h2(v.y, A.y, S.y), h2(v.z, A.z, S.z), h2(v.w, A.w, S.w));
          st_msg(&pp.mail->rowx[o], v.x, v.y, v.z, v.w);
          __syncwarp();
        }
      }
      if (elect) TRACE(18);
      {
        const float r0 = __shfl_sync(~0u, rstd, gq), n0 = __shfl_sync(~0u, nm, gq), r1 = __shfl_sync(~0u, rstd, gq + 8), n1 = __shfl_sync(~0u, nm, gq + 8);
        mbar_wait(BAR(B_EMPTY + 3), 1);
        const uint32_t dst = sb + OUT_OFF + mrow * OUT_LD + (lane >> 4) * 16, tad = sb + GH_OFF + q4 * 16;
        float4 tb[32];
#pragma unroll
        for (int c = 0; c < 8; c++) tb[c] = lds128(tad + c * 64);
#pragma unroll
        for (int i = 0; i < 16; i++) {
          uint32_t r[4];
#pragma unroll
          for (int h = 0; h < 2; h++) {
            const float4 tv = tb[2 * i + h];
            const uint32_t u0 = xa[4 * i + 2 * h], u1 = xa[4 * i + 2 * h + 1];
            r[2 * h] = pack_bf16(fmaf(fmaf(bf_lo(u0), r0, n0), tv.x, bf_lo(u0) + tv.z), fmaf(fmaf(bf_hi(u0), r0, n0), tv.y, bf_hi(u0) + tv.w));
            r[2 * h + 1] = pack_bf16(fmaf(fmaf(bf_lo(u1), r1, n1), tv.x, bf_lo(u1) + tv.z), fmaf(fmaf(bf_hi(u1), r1, n1), tv.y, bf_hi(u1) + tv.w));
          }
          if (i < 12) { tb[2 * i + 8] = lds128(tad + (2 * i + 8) * 64); tb[2 * i + 9] = lds128(tad + (2 * i + 9) * 64); }
          stsm_x4(dst + i * 32, r[0], r[1], r[2], r[3]);
        }
        fence_async_smem();
        __syncwarp();
      }
      const int orow = blk * 64 + wq * 16 + lane;
      const bool candrow = orow == bi1 || orow == bi2;
      char* odst = pp.out + (size_t)orow * (2 * D_) + m4 * 512;
      const uint32_t osrc = sb + OUT_OFF + (wq * 16 + lane) * OUT_LD;
      if (lane < 16 && !candrow) { bulk_store(odst, osrc, 512); bulk_commit(); }
      if (elect) TRACE(25);
      if (b < NMOE) {
        uint32_t wd[128];
        mbar_wait(BAR(B_DN), 0);
        {
          const int fr = (lane & 7) + (lane >> 4) * 8;
          const uint32_t base = sb + (wq < 3 ? 2 * STAGE + wq * SLOT : SPARE) + fr * 128;
#pragma unroll
          for (int c = 0; c < 4; c++) {
            const uint32_t ad = base + (((uint32_t)(c * 2 + ((lane >> 3) & 1)) ^ (uint32_t)(lane & 7)) << 4);
#pragma unroll
            for (int gI = 0; gI < 4; gI++)
#pragma unroll
              for (int ks = 0; ks < 2; ks++) {
                const int o = ((gI * 4 + c) * 2 + ks) * 4;
                ldsm_x4_t(ad + gI * 4096 + ks * 2048, wd[o], wd[o + 1], wd[o + 2], wd[o + 3]);
              }
          }
        }
        if (elect) TRACE(27);
        named_bar<4, 384>();
        if (elect) TRACE(21);
        float g0 = 0.f, g1 = 0.f, u0 = 0.f, u1 = 0.f;
#pragma unroll
        for (int w = 0; w < 8; w++) {
          const float2 gv = lds64(sb + PART_OFF + w * 512 + lane * 8), uv = lds64(sb + PART_OFF + w * 512 + 256 + lane * 8);
          g0 += gv.x; g1 += gv.y; u0 += uv.x; u1 += uv.y;
        }
        const uint32_t act = pack_bf16(round_bf16(silu_f(round_bf16(g0))) * round_bf16(u0), round_bf16(silu_f(round_bf16(g1))) * round_bf16(u1));
        uint32_t ab[4];
#pragma unroll
        for (int u = 0; u < 4; u++) {
          const uint32_t v0 = __shfl_sync(~0u, act, 8 * u + 2 * q4), v1 = __shfl_sync(~0u, act, 8 * u + 2 * q4 + 1);
          ab[u] = __byte_perm(v0, v1, (gq & 1) ? 0x7632 : 0x5410);
        }
        float c[4][4];
#pragma unroll
        for (int v = 0; v < 4; v++) { c[v][0] = c[v][1] = c[v][2] = c[v][3] = 0.f; }
#pragma unroll
        for (int q = 0; q < 4; q++) {
          const uint32_t mk = (gq >> 1) == q ? ~0u : 0u;
          const uint32_t b0 = ab[0] & mk, b1 = ab[1] & mk, b2 = ab[2] & mk, b3 = ab[3] & mk;
#pragma unroll
          for (int v = 0; v < 4; v++) { const int o = (4 * v + q) * 8; mma_16816(c[v], wd[o], wd[o + 1], wd[o + 2], wd[o + 3], b0, b1); }
#pragma unroll
          for (int v = 0; v < 4; v++) { const int o = (4 * v + q) * 8 + 4; mma_16816(c[v], wd[o], wd[o + 1], wd[o + 2], wd[o + 3], b2, b3); }
        }
        uint4* dst = &pp.mail->part[((size_t)(wq * 32 + q4 * 4 + (gq >> 1)) * NMOE + b) * 2 + (gq & 1)];
#pragma unroll
        for (int u = 0; u < 2; u++)
          st_msg(dst + u * (16 * NMOE * 2), pack_bf16(c[2 * u][0], c[2 * u][1]), pack_bf16(c[2 * u][2], c[2 * u][3]),
                 pack_bf16(c[2 * u + 1][0], c[2 * u + 1][1]), pack_bf16(c[2 * u + 1][2], c[2 * u + 1][3]));
        if (elect) TRACE(22);
      }
      mbar_wait(BAR(B_SEL), 0);
      if (lane < 16) {
        const uint4 sel = lds128u(sb + SEL_OFF);
        if (candrow && orow != (int)sel.x && orow != (int)sel.y) { bulk_store(odst, osrc, 512); bulk_commit(); }
        bulk_wait_read<0>();
      }
    }
  }
}

typedef CUresult (*PFN_encodeTiled)(CUtensorMap*, CUtensorMapDataType, cuuint32_t, void*, const cuuint64_t*, const cuuint64_t*,
                                    const cuuint32_t*, const cuuint32_t*, CUtensorMapInterleave, CUtensorMapSwizzle,
                                    CUtensorMapL2promotion, CUtensorMapFloatOOBfill);

static void map2d(PFN_encodeTiled enc, CUtensorMap* m, const void* p, uint64_t rows, uint64_t cols, uint32_t brows, uint32_t bcols, CUtensorMapSwizzle sw,
                  CUtensorMapL2promotion pr = CU_TENSOR_MAP_L2_PROMOTION_L2_128B) {
  cuuint64_t dims[2] = {cols, rows}; cuuint64_t str[1] = {cols * 2}; cuuint32_t box[2] = {bcols, brows}; cuuint32_t es[2] = {1, 1};
  enc(m, CU_TENSOR_MAP_DATA_TYPE_BFLOAT16, 2, (void*)p, dims, str, box, es, CU_TENSOR_MAP_INTERLEAVE_NONE, sw, pr,
      CU_TENSOR_MAP_FLOAT_OOB_FILL_NONE);
}
static void map3d(PFN_encodeTiled enc, CUtensorMap* m, const void* p, uint64_t rows, uint64_t cols, uint32_t brows, uint32_t bgroups) {
  cuuint64_t dims[3] = {64, rows, cols / 64}; cuuint64_t str[2] = {cols * 2, 128}; cuuint32_t box[3] = {64, brows, bgroups}; cuuint32_t es[3] = {1, 1, 1};
  enc(m, CU_TENSOR_MAP_DATA_TYPE_BFLOAT16, 3, (void*)p, dims, str, box, es, CU_TENSOR_MAP_INTERLEAVE_NONE, CU_TENSOR_MAP_SWIZZLE_128B,
      CU_TENSOR_MAP_L2_PROMOTION_L2_128B, CU_TENSOR_MAP_FLOAT_OOB_FILL_NONE);
}

}

extern "C" void kernel_launch(void* const* d_in, const int* in_sizes, int n_in, void* d_out, int out_size) {
  using namespace fk;
  (void)in_sizes; (void)n_in; (void)out_size;
  static PFN_encodeTiled enc = nullptr;
  static int maxClusters = -1;
  static void *pn = nullptr, *pP = nullptr, *pc = nullptr, *pm = nullptr, *pmod = nullptr;
  if (!enc) {
    void* fn = nullptr; cudaDriverEntryPointQueryResult qr;
    cudaGetDriverEntryPoint("cuTensorMapEncodeTiled", &fn, cudaEnableDefault, &qr);
    enc = (PFN_encodeTiled)fn;
    cudaGetSymbolAddress(&pn, g_n);
    cudaGetSymbolAddress(&pP, g_P);
    cudaGetSymbolAddress(&pc, g_cnt);
    cudaGetSymbolAddress(&pm, g_mail);
    cudaGetSymbolAddress(&pmod, g_mod);
    cudaFuncSetAttribute(fused_kernel, cudaFuncAttributeMaxDynamicSharedMemorySize, SMEM_BYTES);
  }
  Maps maps;
  map2d(enc, &maps.ws[0], d_in[1], S_, S_, 128, 64, CU_TENSOR_MAP_SWIZZLE_128B);
  map2d(enc, &maps.ws[1], d_in[2], S_, S_, 128, 64, CU_TENSOR_MAP_SWIZZLE_128B);
  map3d(enc, &maps.n, pn, S_, D_, 64, 4);
  map2d(enc, &maps.p, pP, 2 * S_, D_, 128, 64, CU_TENSOR_MAP_SWIZZLE_128B);
  map2d(enc, &maps.ps, pP, 2 * S_, D_, 32, 64, CU_TENSOR_MAP_SWIZZLE_128B);
  map2d(enc, &maps.wd[0], d_in[3], D_, D_, 256, 64, CU_TENSOR_MAP_SWIZZLE_128B);
  map2d(enc, &maps.wd[1], d_in[4], D_, D_, 256, 64, CU_TENSOR_MAP_SWIZZLE_128B);
  map2d(enc, &maps.x, d_in[0], S_, D_, 64, 64, CU_TENSOR_MAP_SWIZZLE_128B);
  map2d(enc, &maps.wg, d_in[7], D_, F_, 128, 32, CU_TENSOR_MAP_SWIZZLE_64B);
  map2d(enc, &maps.wu, d_in[8], D_, F_, 128, 32, CU_TENSOR_MAP_SWIZZLE_64B);
  map3d(enc, &maps.wdn, d_in[9], F_, D_, 32, 4);
  map2d(enc, &maps.wm, d_in[11], D_, 6 * D_, 64, 48, CU_TENSOR_MAP_SWIZZLE_NONE);

  cudaLaunchConfig_t cfg = {};
  cfg.gridDim = dim3(NCTA); cfg.blockDim = dim3(384); cfg.dynamicSmemBytes = SMEM_BYTES; cfg.stream = cudaStreamPerThread;
  cudaLaunchAttribute at[1];
  at[0].id = cudaLaunchAttributeClusterDimension; at[0].val.clusterDim.x = 2; at[0].val.clusterDim.y = 1; at[0].val.clusterDim.z = 1;
  cfg.attrs = at; cfg.numAttrs = 1;
  Ptrs pp{(const char*)d_in[0], (char*)pn, (unsigned*)pc, 0, (Mail*)pm, (uint32_t*)pmod, (const char*)d_in[10], (const char*)d_in[1], (const char*)d_in[2],
          (const char*)d_in[3], (const char*)d_in[4], (const char*)d_in[6], (const char*)d_in[7], (const char*)d_in[8], (const char*)d_in[9], (const char*)d_in[11], (char*)d_out, nullptr};
  if (maxClusters < 0) {
    cfg.gridDim = dim3(NCTA + NEXTRA);
    if (cudaOccupancyMaxActiveClusters(&maxClusters, fused_kernel, &cfg) != cudaSuccess) maxClusters = 0;
  }
  pp.b0 = -NEXTRA;
  if (maxClusters >= (NCTA + NEXTRA) / 2) {
    cfg.gridDim = dim3(NCTA + NEXTRA);
  } else {
    cfg.gridDim = dim3(NEXTRA);
    cudaLaunchKernelEx(&cfg, fused_kernel, pp, maps);
    cfg.gridDim = dim3(NCTA); pp.b0 = 0;
  }
  cudaLaunchKernelEx(&cfg, fused_kernel, pp, maps);
}
```

```cpp
#include <cuda_runtime.h>
#include <cuda_bf16.h>
#include <cuda.h>
#include <stdint.h>

#define DEVINL __device__ __forceinline__

namespace fk {

constexpr int S_ = 2048, D_ = 1024, F_ = 3584;
constexpr int NCTA = 128;
constexpr int NEXTRA = 4;
constexpr int NMOE = 112;
constexpr int SLOT = 16384;
constexpr int STAGE = 3 * SLOT;
constexpr int SPARE = 4 * STAGE;
constexpr int MISC = SPARE + 32768;
constexpr int SMEM_BYTES = MISC + 3072;
constexpr int BAR_OFF = MISC;
constexpr int CST_OFF = MISC + 480;
constexpr int SEL_OFF = MISC + 496;
constexpr int T1_OFF = MISC + 512;
constexpr int RS_OFF = T1_OFF + 2048;
constexpr int GA_OFF = T1_OFF;
constexpr int W_OFF = GA_OFF + 512;
constexpr int TOP_OFF = GA_OFF + 1792;
constexpr int XST_OFF = 3 * STAGE + SLOT;
constexpr int PART_REL = 0;
constexpr int SCR_REL = 4096;
constexpr int RST_REL = 6144;
enum { B_FULL = 0, B_EMPTY = 4, B_EMPTYH = 8, B_PRDY = 12  , B_WM = 20  , B_RDY = 24  , B_WB = 36  ,
       B_DN = 40  , B_RECV = 44  , B_STAG = 48, B_T1 = 49, B_MODOK = 50, B_PEER = 51  , B_X = 53, B_T2 = 54, B_GU = 55,
       B_XDONE = 56, B_SEL = 57, B_NUM = 58 };

__host__ __device__ constexpr int bar_count(int i) {
  return (i >= B_EMPTY && i < B_EMPTYH) || (i >= B_PRDY && i < B_WM) || i == B_X || i == B_XDONE ? 4
         : (i == B_T1 || i == B_GU || i == B_MODOK || (i >= B_RDY && i < B_RDY + 4)) ? 2 : 1;
}

#define FK_XDEPTH 2
#define FK_G0 8
#define FK_ROW0DLY 500
#define FK_ROWDLY 200
#define FK_WS0DLY 400
#define FK_WS1DLY 1400
#define FK_ADLY 1800
#define FK_L1 2
#define FK_L2 3
#define FK_PF0 19
#define FK_E1DLY 300
#define FK_E2DLY 300
#define FK_E4DLY 3000
#define FK_RSTEP 6
#define FK_MAILQ 14
#define FK_MAP 3
#define FK_PPACE 280
#define FK_PACE0 1000
#define FK_WMPF 0
#define FK_TG 28
#define FK_TU 31
#define FK_BSLEEP 250
#define FK_PFSKIP 0
#define FK_DNWIN 1
#define FK_OPACE 220
#define FK_OSPLIT 7
#define FK_PACE 2000
constexpr int SPIN_LIMIT = 1 << 22;
constexpr uint32_t SENT = 0xFFFFFFFFu;

struct Maps {
  CUtensorMap ws[2];
  CUtensorMap n;
  CUtensorMap p;
  CUtensorMap ps;
  CUtensorMap wd[2];
  CUtensorMap x;
  CUtensorMap wg, wu;
  CUtensorMap wdn;
  CUtensorMap wm;
};
template <int V> struct IntC { static constexpr int value = V; };
struct Mail;
struct Ptrs { const char* x; char* n; unsigned* cnt; int b0; uint32_t zero; Mail* mail; uint32_t* mod; const char *c, *ws_re, *ws_im, *wd_re, *wd_im, *wr, *wg, *wu, *wdn, *wm; char* out; unsigned long long* trace; };

__device__ __align__(1024) __nv_bfloat16 g_n[S_ * D_];
__device__ __align__(1024) __nv_bfloat16 g_P[2 * S_ * D_];
__device__ __align__(128) uint32_t g_mod[3 * D_];
__device__ __align__(128) unsigned g_cnt[17 * 32];
struct Mail {
  uint4 stats[32 * 4 * 64];
  uint2 cand[128 * 32];
  uint4 rowh[64 * 128];
  uint4 rowx[64 * 128];
  uint4 part[128 * NMOE * 2];
  uint2 rs[2 * 16 * 128];
  unsigned flagP[512 * 8];
};
static_assert(sizeof(Mail) % (16 * NCTA) == 0, "mail size");
static_assert(FK_L2 == 3, "the receive layout assumes a stagger of three k-blocks");
constexpr int MAIL_PER_CTA = sizeof(Mail) / 16 / NCTA;
__device__ __align__(1024) Mail g_mail;

#define SPIN_FAIL(what) __trap()
DEVINL uint32_t smem_u32(const void* p) { return (uint32_t)__cvta_generic_to_shared(p); }
DEVINL void mbar_init(uint32_t bar, uint32_t cnt) { asm volatile("mbarrier.init.shared::cta.b64 [%0], %1;" ::"r"(bar), "r"(cnt) : "memory"); }
DEVINL void mbar_expect_tx(uint32_t bar, uint32_t bytes) { asm volatile("mbarrier.arrive.expect_tx.shared::cta.b64 _, [%0], %1;" ::"r"(bar), "r"(bytes) : "memory"); }
DEVINL void mbar_arrive(uint32_t bar) { asm volatile("mbarrier.arrive.shared::cta.b64 _, [%0];" ::"r"(bar) : "memory"); }
DEVINL void mbar_arrive_cluster(uint32_t bar) { asm volatile("mbarrier.arrive.shared::cluster.b64 _, [%0];" ::"r"(bar) : "memory"); }
DEVINL uint32_t mapa(uint32_t a, uint32_t cta) { uint32_t r; asm("mapa.shared::cluster.u32 %0, %1, %2;" : "=r"(r) : "r"(a), "r"(cta)); return r; }
DEVINL void mbar_wait(uint32_t bar, uint32_t parity) {
  asm volatile("{\n.reg .pred p;\n.reg .u32 c;\nmov.u32 c, 0;\n"
               "LW:\nmbarrier.try_wait.parity.shared::cta.b64 p, [%0], %1;\n@p bra LD;\n"
               "add.u32 c, c, 1;\nsetp.lt.u32 p, c, 4194304;\n@p bra LW;\ntrap;\nLD:\n}" ::"r"(bar), "r"(parity) : "memory");
}
DEVINL void mbar_wait_cluster(uint32_t bar, uint32_t parity) {
  asm volatile("{\n.reg .pred p;\n.reg .u32 c;\nmov.u32 c, 0;\n"
               "LW:\nmbarrier.try_wait.parity.acquire.cluster.shared::cta.b64 p, [%0], %1;\n@p bra LD;\n"
               "add.u32 c, c, 1;\nsetp.lt.u32 p, c, 4194304;\n@p bra LW;\ntrap;\nLD:\n}" ::"r"(bar), "r"(parity) : "memory");
}
DEVINL void fence_async_smem() { asm volatile("fence.proxy.async.shared::cta;" ::: "memory"); }
DEVINL void fence_async_global() { asm volatile("fence.proxy.async.global;" ::: "memory"); }
DEVINL void fence_gpu() { asm volatile("fence.acq_rel.gpu;" ::: "memory"); }
template <int ID, int N> DEVINL void named_bar() { asm volatile("bar.sync %0, %1;" ::"n"(ID), "n"(N) : "memory"); }
template <int ID, int N> DEVINL void named_arrive() { asm volatile("bar.arrive %0, %1;" ::"n"(ID), "n"(N) : "memory"); }

DEVINL void tma_2d(uint32_t dst, const CUtensorMap* m, int x, int y, uint32_t bar) {
  asm volatile("cp.async.bulk.tensor.2d.shared::cluster.global.mbarrier::complete_tx::bytes [%0], [%1, {%3, %4}], [%2];"
               ::"r"(dst), "l"(m), "r"(bar), "r"(x), "r"(y) : "memory");
}
DEVINL void tma_2d_hint(uint32_t dst, const CUtensorMap* m, int x, int y, uint32_t bar, uint64_t pol) {
  asm volatile("cp.async.bulk.tensor.2d.shared::cluster.global.mbarrier::complete_tx::bytes.L2::cache_hint [%0], [%1, {%3, %4}], [%2], %5;"
               ::"r"(dst), "l"(m), "r"(bar), "r"(x), "r"(y), "l"(pol) : "memory");
}
DEVINL void tma_3d(uint32_t dst, const CUtensorMap* m, int x, int y, int z, uint32_t bar) {
  asm volatile("cp.async.bulk.tensor.3d.shared::cluster.global.mbarrier::complete_tx::bytes [%0], [%1, {%3, %4, %5}], [%2];"
               ::"r"(dst), "l"(m), "r"(bar), "r"(x), "r"(y), "r"(z) : "memory");
}
DEVINL void tma_store_2d(const CUtensorMap* m, uint32_t src, int x, int y) {
  asm volatile("cp.async.bulk.tensor.2d.global.shared::cta.bulk_group [%0, {%2, %3}], [%1];" ::"l"(m), "r"(src), "r"(x), "r"(y) : "memory");
}
DEVINL void bulk_load(uint32_t dst, const void* src, uint32_t bytes, uint32_t bar) {
  asm volatile("cp.async.bulk.shared::cluster.global.mbarrier::complete_tx::bytes [%0], [%1], %2, [%3];" ::"r"(dst), "l"(src), "r"(bytes), "r"(bar) : "memory");
}
DEVINL void bulk_store(void* dst, uint32_t src, uint32_t bytes) {
  asm volatile("cp.async.bulk.global.shared::cta.bulk_group [%0], [%1], %2;" ::"l"(dst), "r"(src), "r"(bytes) : "memory");
}
DEVINL void pf_bulk(const void* p, uint32_t bytes) { asm volatile("cp.async.bulk.prefetch.L2.global [%0], %1;" ::"l"(p), "r"(bytes) : "memory"); }
DEVINL void pf_bulk_hint(const void* p, uint32_t bytes, uint64_t pol) {
  asm volatile("cp.async.bulk.prefetch.L2.global.L2::cache_hint [%0], %1, %2;" ::"l"(p), "r"(bytes), "l"(pol) : "memory");
}
DEVINL void pf_2d(const CUtensorMap* m, int x, int y) {
  asm volatile("cp.async.bulk.prefetch.tensor.2d.L2.global [%0, {%1, %2}];" ::"l"(m), "r"(x), "r"(y) : "memory");
}
DEVINL void bulk_commit() { asm volatile("cp.async.bulk.commit_group;" ::: "memory"); }
template <int N> DEVINL void bulk_wait() { asm volatile("cp.async.bulk.wait_group %0;" ::"n"(N) : "memory"); }
template <int N> DEVINL void bulk_wait_read() { asm volatile("cp.async.bulk.wait_group.read %0;" ::"n"(N) : "memory"); }
DEVINL void prefetch_tmap(const CUtensorMap* m) { asm volatile("prefetch.tensormap [%0];" ::"l"(m) : "memory"); }

DEVINL void wg_fence() { asm volatile("wgmma.fence.sync.aligned;" ::: "memory"); }
DEVINL void wg_commit() { asm volatile("wgmma.commit_group.sync.aligned;" ::: "memory"); }
template <int N> DEVINL void wg_wait() { asm volatile("wgmma.wait_group.sync.aligned %0;" ::"n"(N) : "memory"); }

DEVINL uint64_t make_desc(uint32_t addr, uint32_t lbo, uint32_t sbo) {
  return (uint64_t)((addr & 0x3FFFF) >> 4) | ((uint64_t)(lbo >> 4) << 16) | ((uint64_t)(sbo >> 4) << 32) | ((uint64_t)1 << 62);
}

#define R8(a, o) "+f"(a[o]), "+f"(a[o + 1]), "+f"(a[o + 2]), "+f"(a[o + 3]), "+f"(a[o + 4]), "+f"(a[o + 5]), "+f"(a[o + 6]), "+f"(a[o + 7])
#define R128(a) R8(a, 0), R8(a, 8), R8(a, 16), R8(a, 24), R8(a, 32), R8(a, 40), R8(a, 48), R8(a, 56), \
                R8(a, 64), R8(a, 72), R8(a, 80), R8(a, 88), R8(a, 96), R8(a, 104), R8(a, 112), R8(a, 120)
template <int TB>
DEVINL void wgmma_n256(float (&d)[128], uint64_t da, uint64_t db, int scale_d) {
  asm volatile(
      "{\n.reg .pred p;\nsetp.ne.b32 p, %130, 0;\n"
      "wgmma.mma_async.sync.aligned.m64n256k16.f32.bf16.bf16 "
      "{%0, %1, %2, %3, %4, %5, %6, %7, %8, %9, %10, %11, %12, %13, %14, %15, "
      "%16, %17, %18, %19, %20, %21, %22, %23, %24, %25, %26, %27, %28, %29, %30, %31, "
      "%32, %33, %34, %35, %36, %37, %38, %39, %40, %41, %42, %43, %44, %45, %46, %47, "
      "%48, %49, %50, %51, %52, %53, %54, %55, %56, %57, %58, %59, %60, %61, %62, %63, "
      "%64, %65, %66, %67, %68, %69, %70, %71, %72, %73, %74, %75, %76, %77, %78, %79, "
      "%80, %81, %82, %83, %84, %85, %86, %87, %88, %89, %90, %91, %92, %93, %94, %95, "
      "%96, %97, %98, %99, %100, %101, %102, %103, %104, %105, %106, %107, %108, %109, %110, %111, "
      "%112, %113, %114, %115, %116, %117, %118, %119, %120, %121, %122, %123, %124, %125, %126, %127}, "
      "%128, %129, p, 1, 1, 0, %131;\n}\n"
      : R128(d)
      : "l"(da), "l"(db), "r"(scale_d), "n"(TB));
}
DEVINL void reg_fence128(float (&a)[128]) {
#pragma unroll
  for (int i = 0; i < 128; i++) asm volatile("" : "+f"(a[i])::"memory");
}

DEVINL uint32_t pack_bf16(float lo, float hi) {
  uint32_t r;
  asm("cvt.rn.bf16x2.f32 %0, %1, %2;" : "=r"(r) : "f"(hi), "f"(lo));
  return r;
}
DEVINL uint32_t fma_bf2(uint32_t a, uint32_t b, uint32_t c) { uint32_t r; asm("fma.rn.bf16x2 %0, %1, %2, %3;" : "=r"(r) : "r"(a), "r"(b), "r"(c)); return r; }
DEVINL uint32_t mul_bf2(uint32_t a, uint32_t b) { uint32_t r; asm("mul.rn.bf16x2 %0, %1, %2;" : "=r"(r) : "r"(a), "r"(b)); return r; }
DEVINL uint32_t add1_bf2(uint32_t a) { return fma_bf2(a, 0x3F803F80u, 0x3F803F80u); }
DEVINL float bf_lo(uint32_t w) { return __uint_as_float(w << 16); }
DEVINL float bf_hi(uint32_t w) { return __uint_as_float(w & 0xFFFF0000u); }
DEVINL float round_bf16(float v) { return __bfloat162float(__float2bfloat16_rn(v)); }
DEVINL float sigmoid_f(float v) { float r; asm("rcp.approx.ftz.f32 %0, %1;" : "=f"(r) : "f"(1.f + __expf(-v))); return r; }
DEVINL float silu_f(float v) { return v * sigmoid_f(v); }
DEVINL void stsm_x4(uint32_t addr, uint32_t r0, uint32_t r1, uint32_t r2, uint32_t r3) {
  asm volatile("stmatrix.sync.aligned.m8n8.x4.shared.b16 [%0], {%1, %2, %3, %4};" ::"r"(addr), "r"(r0), "r"(r1), "r"(r2), "r"(r3) : "memory");
}
DEVINL void ldsm_x4(uint32_t addr, uint32_t& r0, uint32_t& r1, uint32_t& r2, uint32_t& r3) {
  asm volatile("ldmatrix.sync.aligned.m8n8.x4.shared.b16 {%0, %1, %2, %3}, [%4];" : "=r"(r0), "=r"(r1), "=r"(r2), "=r"(r3) : "r"(addr) : "memory");
}
DEVINL void ldsm_x4_t(uint32_t addr, uint32_t& r0, uint32_t& r1, uint32_t& r2, uint32_t& r3) {
  asm volatile("ldmatrix.sync.aligned.m8n8.x4.trans.shared.b16 {%0, %1, %2, %3}, [%4];" : "=r"(r0), "=r"(r1), "=r"(r2), "=r"(r3) : "r"(addr) : "memory");
}
DEVINL void mma_16816(float (&c)[4], uint32_t a0, uint32_t a1, uint32_t a2, uint32_t a3, uint32_t b0, uint32_t b1) {
  asm("mma.sync.aligned.m16n8k16.row.col.f32.bf16.bf16.f32 {%0, %1, %2, %3}, {%4, %5, %6, %7}, {%8, %9}, {%0, %1, %2, %3};"
      : "+f"(c[0]), "+f"(c[1]), "+f"(c[2]), "+f"(c[3]) : "r"(a0), "r"(a1), "r"(a2), "r"(a3), "r"(b0), "r"(b1));
}
DEVINL void mma_1688(float (&c)[4], uint32_t a0, uint32_t a1, uint32_t b0) {
  asm("mma.sync.aligned.m16n8k8.row.col.f32.bf16.bf16.f32 {%0, %1, %2, %3}, {%4, %5}, {%6}, {%0, %1, %2, %3};"
      : "+f"(c[0]), "+f"(c[1]), "+f"(c[2]), "+f"(c[3]) : "r"(a0), "r"(a1), "r"(b0));
}
DEVINL float4 lds128(uint32_t a) { float4 v; asm volatile("ld.shared.v4.f32 {%0, %1, %2, %3}, [%4];" : "=f"(v.x), "=f"(v.y), "=f"(v.z), "=f"(v.w) : "r"(a)); return v; }
DEVINL uint4 lds128u(uint32_t a) { uint4 v; asm volatile("ld.shared.v4.u32 {%0, %1, %2, %3}, [%4];" : "=r"(v.x), "=r"(v.y), "=r"(v.z), "=r"(v.w) : "r"(a)); return v; }
DEVINL float2 lds64(uint32_t a) { float2 v; asm volatile("ld.shared.v2.f32 {%0, %1}, [%2];" : "=f"(v.x), "=f"(v.y) : "r"(a)); return v; }
DEVINL uint2 lds64u(uint32_t a) { uint2 v; asm volatile("ld.shared.v2.u32 {%0, %1}, [%2];" : "=r"(v.x), "=r"(v.y) : "r"(a)); return v; }
DEVINL float lds32(uint32_t a) { float v; asm volatile("ld.shared.f32 %0, [%1];" : "=f"(v) : "r"(a)); return v; }
DEVINL float lds16f(uint32_t a) { uint32_t v; asm volatile("ld.shared.u16 %0, [%1];" : "=r"(v) : "r"(a)); return __uint_as_float(v << 16); }
DEVINL uint32_t lds32u(uint32_t a) { uint32_t v; asm volatile("ld.shared.u32 %0, [%1];" : "=r"(v) : "r"(a)); return v; }
DEVINL void sts128(uint32_t a, float x, float y, float z, float w) { asm volatile("st.shared.v4.f32 [%0], {%1, %2, %3, %4};" ::"r"(a), "f"(x), "f"(y), "f"(z), "f"(w) : "memory"); }
DEVINL void sts128u(uint32_t a, uint32_t x, uint32_t y, uint32_t z, uint32_t w) { asm volatile("st.shared.v4.u32 [%0], {%1, %2, %3, %4};" ::"r"(a), "r"(x), "r"(y), "r"(z), "r"(w) : "memory"); }
DEVINL void sts64(uint32_t a, float x, float y) { asm volatile("st.shared.v2.f32 [%0], {%1, %2};" ::"r"(a), "f"(x), "f"(y) : "memory"); }
DEVINL void sts64u(uint32_t a, uint32_t x, uint32_t y) { asm volatile("st.shared.v2.u32 [%0], {%1, %2};" ::"r"(a), "r"(x), "r"(y) : "memory"); }
DEVINL void sts32(uint32_t a, float v) { asm volatile("st.shared.f32 [%0], %1;" ::"r"(a), "f"(v) : "memory"); }
DEVINL void sts32u(uint32_t a, uint32_t v) { asm volatile("st.shared.u32 [%0], %1;" ::"r"(a), "r"(v) : "memory"); }

DEVINL uint4 ld_msg(const uint4* p) {
  unsigned long long a, b;
  asm volatile("{\n.reg .b128 r;\nld.relaxed.gpu.global.b128 r, [%2];\nmov.b128 {%0, %1}, r;\n}" : "=l"(a), "=l"(b) : "l"(p) : "memory");
  return make_uint4((uint32_t)a, (uint32_t)(a >> 32), (uint32_t)b, (uint32_t)(b >> 32));
}
DEVINL void st_msg(uint4* p, uint32_t x, uint32_t y, uint32_t z, uint32_t w) {
  unsigned long long a = (unsigned long long)x | ((unsigned long long)y << 32), b = (unsigned long long)z | ((unsigned long long)w << 32);
  asm volatile("{\n.reg .b128 r;\nmov.b128 r, {%1, %2};\nst.relaxed.gpu.global.b128 [%0], r;\n}" ::"l"(p), "l"(a), "l"(b) : "memory");
}
DEVINL uint2 ld_msg8(const void* p) {
  unsigned long long a;
  asm volatile("ld.relaxed.gpu.global.b64 %0, [%1];" : "=l"(a) : "l"(p) : "memory");
  return make_uint2((uint32_t)a, (uint32_t)(a >> 32));
}
DEVINL void st_msg8(uint2* p, uint32_t x, uint32_t y) {
  asm volatile("st.relaxed.gpu.global.b64 [%0], %1;" ::"l"(p), "l"((unsigned long long)x | ((unsigned long long)y << 32)) : "memory");
}
DEVINL unsigned ld_rlx(const void* p) { unsigned v; asm volatile("ld.relaxed.gpu.global.u32 %0, [%1];" : "=r"(v) : "l"(p) : "memory"); return v; }
DEVINL void st_rlx(unsigned* p, unsigned v) { asm volatile("st.relaxed.gpu.global.u32 [%0], %1;" ::"l"(p), "r"(v) : "memory"); }
DEVINL void red_add(unsigned* p, unsigned v) { asm volatile("red.relaxed.gpu.global.add.u32 [%0], %1;" ::"l"(p), "r"(v) : "memory"); }
DEVINL void red_add_release(unsigned* p, unsigned v) { asm volatile("red.release.gpu.global.add.u32 [%0], %1;" ::"l"(p), "r"(v) : "memory"); }
DEVINL uint4 ldg_nc(const void* p) {
  uint4 v;
  asm volatile("ld.global.nc.L1::no_allocate.v4.u32 {%0, %1, %2, %3}, [%4];" : "=r"(v.x), "=r"(v.y), "=r"(v.z), "=r"(v.w) : "l"(p));
  return v;
}
DEVINL void stg128(void* p, uint4 v) { asm volatile("st.global.v4.u32 [%0], {%1, %2, %3, %4};" ::"l"(p), "r"(v.x), "r"(v.y), "r"(v.z), "r"(v.w) : "memory"); }
DEVINL void delay_until(uint32_t c0, uint32_t cycles) { while ((uint32_t)clock() - c0 < cycles) {} }

#define TRACE(id)
#define TRACE_CLK(id)

DEVINL const char* piece_addr(const Ptrs& pp, int b, int i) {
  if (i >= 20) return pp.wdn + (size_t)b * 57344 + (i - 20) * 8192;
  if ((i >> 2) == 2) return (b < 64 ? pp.wd_re : pp.wd_im) + (size_t)(b & 63) * 32768 + (i & 3) * 8192;
  return (i < 4 || (i >> 2) == 3 ? pp.wg : pp.wu) + (size_t)((i < 8 ? ((i & 3) ^ 2) * 128 : 512 + (i & 3) * 128) + b) * (2 * F_);
}

DEVINL uint32_t dn_box(int i) { return i == 0 ? STAGE + 2 * SLOT : i == 3 ? SPARE : 2 * STAGE + i * SLOT; }
DEVINL int sibling(int m4, int r) {
  return r < 2 ? m4 ^ r : ((m4 & 2) ^ 2) + r - 2;
}

DEVINL uint32_t fkey(float v, int row) {
  const uint32_t u = __float_as_uint(v);
  return (((u & 0x80000000u) ? ~u : (u | 0x80000000u)) & ~2047u) | (uint32_t)(2047 - row);
}
DEVINL int key_row(uint32_t k) { return 2047 - (int)(k & 2047u); }
DEVINL float key_val(uint32_t k) { k = (k & ~2047u) | 1024u; return __uint_as_float((k & 0x80000000u) ? (k & 0x7FFFFFFFu) : ~k); }
DEVINL uint32_t redux_max(uint32_t v) { uint32_t r; asm volatile("redux.sync.max.u32 %0, %1, 0xffffffff;" : "=r"(r) : "r"(v)); return r; }
DEVINL void warp_top2(uint32_t ka, uint32_t kb, uint32_t& k1, uint32_t& k2) {
  k1 = redux_max(ka);
  k2 = redux_max(ka == k1 ? kb : ka);
}
DEVINL int sel_slot(uint2 sel, int n) {
  const int bA = key_row(sel.x) >> 6, bB = key_row(sel.y) >> 6;
  return n ? bB * 2 + (bA == bB ? 1 : 0) : bA * 2;
}

DEVINL void ln_row(uint4 (&w)[4]) {
  float v[32];
#pragma unroll
  for (int i = 0; i < 4; i++) {
    v[8 * i + 0] = bf_lo(w[i].x); v[8 * i + 1] = bf_hi(w[i].x); v[8 * i + 2] = bf_lo(w[i].y); v[8 * i + 3] = bf_hi(w[i].y);
    v[8 * i + 4] = bf_lo(w[i].z); v[8 * i + 5] = bf_hi(w[i].z); v[8 * i + 6] = bf_lo(w[i].w); v[8 * i + 7] = bf_hi(w[i].w);
  }
  float s[4] = {0.f, 0.f, 0.f, 0.f}, q[4] = {0.f, 0.f, 0.f, 0.f};
#pragma unroll
  for (int i = 0; i < 32; i++) { s[i & 3] += v[i]; q[i & 3] = fmaf(v[i], v[i], q[i & 3]); }
  float sum = (s[0] + s[1]) + (s[2] + s[3]), sq = (q[0] + q[1]) + (q[2] + q[3]);
#pragma unroll
  for (int o = 16; o; o >>= 1) { sum += __shfl_xor_sync(~0u, sum, o); sq += __shfl_xor_sync(~0u, sq, o); }
  const float mean = sum * (1.f / D_);
  const float rstd = rsqrtf(fmaxf(fmaf(-mean, mean, sq * (1.f / D_)), 0.f) + 1e-5f), nmr = -mean * rstd;
#pragma unroll
  for (int i = 0; i < 4; i++) {
    w[i].x = pack_bf16(fmaf(v[8 * i], rstd, nmr), fmaf(v[8 * i + 1], rstd, nmr)); w[i].y = pack_bf16(fmaf(v[8 * i + 2], rstd, nmr), fmaf(v[8 * i + 3], rstd, nmr));
    w[i].z = pack_bf16(fmaf(v[8 * i + 4], rstd, nmr), fmaf(v[8 * i + 5], rstd, nmr)); w[i].w = pack_bf16(fmaf(v[8 * i + 6], rstd, nmr), fmaf(v[8 * i + 7], rstd, nmr));
  }
}
DEVINL float sum8(uint4 u) { return ((bf_lo(u.x) + bf_hi(u.x)) + (bf_lo(u.y) + bf_hi(u.y))) + ((bf_lo(u.z) + bf_hi(u.z)) + (bf_lo(u.w) + bf_hi(u.w))); }

template <int R> DEVINL void take_box(uint32_t (&wf)[128], uint32_t box, int lane) {
  const int kr = (lane & 7) + (lane >> 4) * 8;
  const uint32_t base = box + kr * 64, sw = (uint32_t)((kr >> 1) & 3), hb = (uint32_t)((lane >> 3) & 1);
#pragma unroll
  for (int mt = 0; mt < 2; mt++) {
    const uint32_t ad = base + (((mt * 2 + hb) ^ sw) << 4);
#pragma unroll
    for (int ks = 0; ks < 8; ks++) {
      const int o = (ks * 4 + R * 2 + mt) * 4;
      ldsm_x4_t(ad + ks * 1024, wf[o], wf[o + 1], wf[o + 2], wf[o + 3]);
    }
  }
}
DEVINL void gate_up(const Ptrs& pp, uint32_t (&wf)[128], uint32_t sb, uint32_t scr, int ksl, int lane) {
  const uint2 sel = lds64u(sb + SEL_OFF);
  const int gq = lane >> 2, q4 = lane & 3;
  const uint4* src = &pp.mail->rowh[sel_slot(sel, gq & 1) * 128 + ksl * 16 + q4];
  uint4 bf[4];
  int it = 0;
  while (true) {
#pragma unroll
    for (int u = 0; u < 4; u++) bf[u] = ld_msg(src + u * 4);
    if (__all_sync(~0u, bf[0].x != SENT && bf[1].x != SENT && bf[2].x != SENT && bf[3].x != SENT)) break;
    if (++it > SPIN_LIMIT) SPIN_FAIL(0x207);
  }
  if (lane == 0 && ksl == 4) TRACE(20);
  float acc[8][4];
#pragma unroll
  for (int i = 0; i < 8; i++) { acc[i][0] = acc[i][1] = acc[i][2] = acc[i][3] = 0.f; }
#pragma unroll
  for (int u = 0; u < 4; u++)
#pragma unroll
    for (int mt = 0; mt < 4; mt++) {
      const int o = (2 * u * 4 + mt) * 4;
      mma_16816(acc[mt], wf[o], wf[o + 1], wf[o + 2], wf[o + 3], bf[u].x, bf[u].y);
      mma_16816(acc[4 + mt], wf[o + 16], wf[o + 17], wf[o + 18], wf[o + 19], bf[u].z, bf[u].w);
    }
  if (q4 == 0) {
    const uint32_t pb = scr + PART_REL + ksl * 512 + gq * 8;
#pragma unroll
    for (int mt = 0; mt < 4; mt++) {
      sts64(pb + mt * 128, acc[mt][0] + acc[4 + mt][0], acc[mt][1] + acc[4 + mt][1]);
      sts64(pb + mt * 128 + 64, acc[mt][2] + acc[4 + mt][2], acc[mt][3] + acc[4 + mt][3]);
    }
  }
  named_arrive<4, 384>();
}

struct OutTab { float G[8], H[8]; };
DEVINL void out_tab(OutTab& tb, uint4 cb, uint4 sv, uint4 gb) {
  const uint32_t c4[4] = {cb.x, cb.y, cb.z, cb.w}, s4[4] = {sv.x, sv.y, sv.z, sv.w}, g4[4] = {gb.x, gb.y, gb.z, gb.w};
#pragma unroll
  for (int u = 0; u < 4; u++) {
    const uint32_t A = add1_bf2(c4[u]);
    tb.G[2 * u] = bf_lo(g4[u]) * bf_lo(A); tb.G[2 * u + 1] = bf_hi(g4[u]) * bf_hi(A);
    tb.H[2 * u] = bf_lo(g4[u]) * bf_lo(s4[u]); tb.H[2 * u + 1] = bf_hi(g4[u]) * bf_hi(s4[u]);
  }
}
DEVINL void out_row(const OutTab& tb, uint32_t sb, uint32_t scr, int r, int lane, char* dst) {
  const uint4 v = lds128u(sb + XST_OFF + r * 512 + ((lane ^ (r & 7)) << 4));
  const float2 st = lds64(scr + RST_REL + r * 8);
  const uint32_t x4[4] = {v.x, v.y, v.z, v.w};
  uint32_t o[4];
#pragma unroll
  for (int u = 0; u < 4; u++)
    o[u] = pack_bf16(fmaf(fmaf(bf_lo(x4[u]), st.x, st.y), tb.G[2 * u], bf_lo(x4[u]) + tb.H[2 * u]),
                     fmaf(fmaf(bf_hi(x4[u]), st.x, st.y), tb.G[2 * u + 1], bf_hi(x4[u]) + tb.H[2 * u + 1]));
  stg128(dst + (size_t)r * (2 * D_), make_uint4(o[0], o[1], o[2], o[3]));
}

template <int TB, int G0, int G1>
DEVINL void gemm_phase(const Ptrs& pp, float (&acc)[128], uint32_t sb, int cw, bool lag, bool elect, uint32_t rel) {
  const uint32_t bars = sb + BAR_OFF;
#pragma unroll 1
  for (int g = G0; g < G1; g++) {
    const int s = g & 3;
    mbar_wait(bars + (B_FULL + s) * 8, (g >> 2) & 1);
    const bool hold = lag && g == G1 - (TB ? FK_L1 : FK_L2);
    if (hold) {
      wg_wait<0>();
      if (rel) mbar_arrive_cluster(rel + ((g - 1) & 3) * 8);
      mbar_wait(bars + B_STAG * 8, TB ? 0 : 1);
    }
    const uint32_t sa = sb + s * STAGE;
    const uint64_t da = make_desc(sa + cw * 8192, 16, 1024), db = make_desc(sa + SLOT, TB ? 8192 : 16, 1024);
    constexpr int KB = TB ? 128 : 2;
    wg_fence();
    wgmma_n256<TB>(acc, da, db, g > G0);
    wgmma_n256<TB>(acc, da + 2, db + KB, 1);
    wg_commit();
    wg_wait<1>();
    if (rel && g > G0 && !hold) mbar_arrive_cluster(rel + ((g - 1) & 3) * 8);
    wg_fence();
    wgmma_n256<TB>(acc, da + 4, db + 2 * KB, 1);
    wgmma_n256<TB>(acc, da + 6, db + 3 * KB, 1);
    wg_commit();
  }
  if (!lag) {
    wg_wait<1>();
    if (elect) { mbar_arrive(bars + B_STAG * 8); if (!TB) mbar_arrive_cluster(mapa(bars + B_PEER * 8, cw)); }
  }
}
DEVINL void gemm_finish(float (&acc)[128], uint32_t rel) {
  wg_wait<0>();
  reg_fence128(acc);
  if (rel) mbar_arrive_cluster(rel + 24);
}

__global__ void __launch_bounds__(384, 1)
fused_kernel(const Ptrs pp, const __grid_constant__ Maps maps) {
  extern __shared__ __align__(1024) uint8_t smem_raw[];
  const uint32_t c0 = (uint32_t)clock();
  if (threadIdx.x == 0) TRACE(0);
  const uint32_t sb = smem_u32(smem_raw);
  const int tid = threadIdx.x, lane = tid & 31;
  const int warp = __shfl_sync(~0u, tid >> 5, 0);
  const int rb = (int)blockIdx.x + pp.b0;
  const uint32_t bars = sb + BAR_OFF;
  auto BAR = [&](int i) { return bars + i * 8; };

  if (rb < 0) {
    const uint32_t ring = sb + warp * 16384, rbar = sb + MISC + warp * 64;
    const int row0 = FK_G0 * 128 + ((rb + NEXTRA) * 12 + warp) * 2;
    if (lane == 0) {
#pragma unroll 1
      for (int i = 0; i < 4; i++) mbar_init(rbar + i * 8, 1);
      asm volatile("fence.mbarrier_init.release.cluster;" ::: "memory");
#pragma unroll 1
      for (int i = 0; i < FK_XDEPTH; i++) { mbar_expect_tx(rbar + i * 8, 4096); bulk_load(ring + i * 4096, pp.x + (size_t)(row0 + 96 * i) * (2 * D_), 4096, rbar + i * 8); }
    }
    __syncwarp();
#pragma unroll 1
    for (int it = 0, row = row0; row < S_; it++, row += 96) {
      const uint32_t st = ring + (it & 3) * 4096;
      mbar_wait(rbar + (it & 3) * 8, (it >> 2) & 1);
      uint4 w[4], w2[4];
#pragma unroll
      for (int i = 0; i < 4; i++) { w[i] = lds128u(st + lane * 16 + i * 512); w2[i] = lds128u(st + 2048 + lane * 16 + i * 512); }
      ln_row(w); ln_row(w2);
#pragma unroll
      for (int i = 0; i < 4; i++) { sts128u(st + lane * 16 + i * 512, w[i].x, w[i].y, w[i].z, w[i].w); sts128u(st + 2048 + lane * 16 + i * 512, w2[i].x, w2[i].y, w2[i].z, w2[i].w); }
      fence_async_smem();
      __syncwarp();
      if (lane == 0) {
        if (it) { bulk_wait<0>(); red_add(&pp.cnt[((row - 96) >> 7) * 32], 2); }
        bulk_store(pp.n + (size_t)row * (2 * D_), st, 4096); bulk_commit();
        if (row + 96 * FK_XDEPTH < S_) {
          const int sn = (it + FK_XDEPTH) & 3;
          mbar_expect_tx(rbar + sn * 8, 4096); bulk_load(ring + sn * 4096, pp.x + (size_t)(row + 96 * FK_XDEPTH) * (2 * D_), 4096, rbar + sn * 8);
        }
        if (row + 96 >= S_) { bulk_wait<0>(); red_add(&pp.cnt[(row >> 7) * 32], 2); }
      }
      __syncwarp();
    }
    return;
  }
  if (warp > 4) asm volatile("barrier.cluster.arrive.relaxed.aligned;" ::: "memory");
  if ((unsigned)(warp - 4) < FK_G0) {
    const int row = (warp - 4) * 128 + rb;
    uint4 w[4];
    if (warp > 4) delay_until(c0, FK_ROW0DLY + (warp - 5) * FK_ROWDLY);
#pragma unroll
    for (int i = 0; i < 4; i++) w[i] = ldg_nc(pp.x + (size_t)row * (2 * D_) + lane * 16 + i * 512);
    if (tid == 128) TRACE(58);
    if (warp == 4) asm volatile("barrier.cluster.arrive.relaxed.aligned;" ::: "memory");
    ln_row(w);
    const uint32_t st = sb + SPARE + ((warp - 4) >> 2) * 16384 + (warp & 3) * 2048;
#pragma unroll
    for (int i = 0; i < 4; i++) sts128u(st + lane * 16 + i * 512, w[i].x, w[i].y, w[i].z, w[i].w);
    if (tid == 128) TRACE(31);
    fence_async_smem();
    __syncwarp();
    if (lane == 0) {
      bulk_store(pp.n + (size_t)row * (2 * D_), st, 2048); bulk_commit(); bulk_wait<0>();
      red_add(&pp.cnt[(warp - 4) * 32], 1);
      if (warp == 4) TRACE(1);
      if (warp == 3 + FK_G0) TRACE(55);
    }
    __syncwarp();
  }
  int m4, t;
  {
    const int c = (rb >> 1) - 2;
    int g = 8, i = c + 2;
    if (c >= 32) { i = ((c - 32) * 37) >> 8; g = c - 32 - 7 * i; g += g >= 2; i += 4; }
    else if (c >= 0) { g = c & 7; i = c >> 3; }
    if (g == 8) { g = 2; i += 6; } else if (i == 8) { i = 4 + g; g = 2; }
    m4 = (g >> 2) * 2 + (i & 1); t = (g & 3) * 4 + (i >> 1);
  }
  const int j = rb & 1, b = t * 8 + m4 * 2 + j;
  const int blk = t * 2 + j;
  const uint32_t scr = sb + 2 * STAGE + j * 8192;
  if (warp >= 10) {
    delay_until(c0, warp == 10 ? FK_WS0DLY : FK_WS1DLY);
    uint32_t dummy;
    asm volatile("ld.global.nc.L1::no_allocate.L2::256B.u32 %0, [%1];" : "=r"(dummy)
                 : "l"((j ? pp.ws_im : pp.ws_re) + (size_t)(t * 128 + m4 * 32 + lane) * (2 * S_) + (warp - 10) * 256));
    sts32u(sb + SEL_OFF, dummy);
  }

  if (warp < 4) {
    uint32_t tag = ld_rlx(&pp.cnt[1]);
    if (lane == 0) {
      if (warp < 2) {
        if (warp == 0) {
          prefetch_tmap(&maps.ws[j]); prefetch_tmap(&maps.n);
          if (sb & 1023) __trap();
#pragma unroll
          for (int i = 0; i < 8; i++) mbar_init(BAR(i), bar_count(i));
        } else {
#pragma unroll
          for (int i = 8; i < 26; i++) mbar_init(BAR(i), bar_count(i));
        }
      } else if (warp == 2) {
#pragma unroll
        for (int i = 26; i < 44; i++) mbar_init(BAR(i), bar_count(i));
      } else {
#pragma unroll
        for (int i = 44; i < B_NUM; i++) mbar_init(BAR(i), bar_count(i));
#pragma unroll
        for (int i = 0; i < 4; i++) mbar_expect_tx(BAR(B_RECV + i), 8192);
      }
      asm volatile("fence.mbarrier_init.release.cluster;" ::: "memory");
    }
    named_bar<6, 128>();
    named_arrive<0, 384>();
    asm volatile("barrier.cluster.arrive.relaxed.aligned;" ::: "memory");
    uint64_t pol_first;
    asm volatile("createpolicy.fractional.L2::evict_first.b64 %0, 1.0;" : "=l"(pol_first));
    const bool moe = b < NMOE;
    uint32_t wf[128];
    auto take = [&](auto R) {
      constexpr int r = decltype(R)::value;
      const uint32_t box = sb + SPARE + warp * 8192;
      if (moe || r == 0) mbar_wait(BAR(B_WB + warp), r);
      if (moe) take_box<r>(wf, box, lane);
      fence_async_smem();
      __syncwarp();
      if (lane == 0) {
        if (r) { mbar_expect_tx(BAR(B_X), 8192); tma_2d(box, &maps.x, m4 * 256 + warp * 64, t * 128 + (1 - j) * 64, BAR(B_X)); }
        else if (moe) { mbar_expect_tx(BAR(B_WB + warp), 8192); tma_2d_hint(box, &maps.wu, b * 32, warp * 128, BAR(B_WB + warp), pol_first); }
      }
      __syncwarp();
    };

    if (warp == 0) {
      auto loadA = [&](int g) {
        mbar_expect_tx(BAR(B_FULL + (g & 3)), STAGE);
        tma_2d_hint(sb + (g & 3) * STAGE, &maps.ws[j], g * 64, t * 128, BAR(B_FULL + (g & 3)), pol_first);
      };
            auto loadB = [&](int g) { tma_3d(sb + (g & 3) * STAGE + SLOT, &maps.n, 0, g * 64, m4 * 4, BAR(B_FULL + (g & 3))); };
      unsigned ready = 0;
      delay_until(c0, FK_ADLY);
#pragma unroll 1
      for (int gi = 0; gi < 2; gi++) {
        if (lane == 0) { loadA(2 * gi); loadA(2 * gi + 1); }
        if (gi == 0) {
          if (lane == 0) TRACE(63);
          asm volatile("add.u32 %0, %0, 1;" : "+r"(tag)::"memory");
        }
        int it = 0;
        while (!((ready >> gi) & 1)) {
          ready = __ballot_sync(~0u, (int)(ld_rlx(&pp.cnt[(lane & 1) * 32]) - tag * 128u) >= 0) & 3;
          if (++it > SPIN_LIMIT) SPIN_FAIL(0x201);
        }
        fence_async_global();
        if (lane == 0) { if (gi == 0) TRACE(2); loadB(2 * gi); loadB(2 * gi + 1); }
        __syncwarp();
      }
      if (lane == 0) { prefetch_tmap(&maps.p); prefetch_tmap(&maps.wd[j]); }
      const unsigned tgt = tag * 128u;
      unsigned pend = ld_rlx(&pp.cnt[2 * 32]);
      const char* pfa = piece_addr(pp, b, lane);
      const uint32_t pfn = (lane >> 2) == 2 || lane >= 20 ? 8192 : 7168;
      auto produce1 = [&](int g0, int g1) {
#pragma unroll 1
        for (int g = g0; g < g1; g++) {
          mbar_wait(BAR(B_EMPTYH + (g & 3)), ((g >> 2) - 1) & 1);
          mbar_wait(BAR(B_EMPTY + (g & 3)), ((g >> 2) - 1) & 1);
          if (!(g & 1)) {
            if ((int)(pend - tgt) < 0) {
              int it = 0;
              while ((int)(ld_rlx(&pp.cnt[(g >> 1) * 32]) - tgt) < 0) { if (++it > SPIN_LIMIT) SPIN_FAIL(0x20c); }
            }
            fence_async_global();
            pend = ld_rlx(&pp.cnt[((g >> 1) + 1) * 32]);
          }
          if (lane == 0) {
            loadA(g); loadB(g);
          }
          if (lane == g - FK_PF0 && lane >= FK_PFSKIP) pf_bulk(pfa, pfn);
          __syncwarp();
        }
      };
      produce1(4, FK_TG);
      take(IntC<0>{});
      produce1(FK_TG, FK_TU);
      take(IntC<1>{});
      produce1(FK_TU, 32);
      int sib = 0, pc = 0;
      auto produce2 = [&](int q0, int q1) {
#pragma unroll 1
        for (int q = q0; q < q1; q++) {
          const int s = q & 3, k0 = sibling(m4, sib) * 256 + pc * 64;
          const uint32_t sa = sb + s * STAGE;
          mbar_wait(BAR(B_EMPTY + s), ((q >> 2) + 1) & 1);
          if (lane == 0) {
            mbar_expect_tx(BAR(B_FULL + s), q < 4 ? 2 * SLOT : STAGE);
            tma_2d(sa + SLOT, &maps.wd[j], k0, m4 * 256, BAR(B_FULL + s));
          }
          __syncwarp();
          if (q >= 4) {
            mbar_wait(BAR(B_RDY - 4 + q), 0);
            if (lane == 0) tma_2d(sa, &maps.p, k0, j * S_ + t * 128, BAR(B_FULL + s));
            if (++sib == 4) { sib = 1; pc++; }
          } else if (++pc == 4) { pc = 0; sib = 1; }
          if (lane == 32 + q - FK_PF0 && lane < 27) pf_bulk(pfa, pfn);
          if (q == FK_MAILQ && lane == 0) pf_bulk(reinterpret_cast<const char*>(pp.mail) + (size_t)b * (MAIL_PER_CTA * 16), MAIL_PER_CTA * 16);
          __syncwarp();
        }
      };
      produce2(0, 16);
      if (moe) {
        mbar_wait(BAR(B_EMPTY + 0), 1);
        if (lane == 0) {
          mbar_expect_tx(BAR(B_GU), 49152);
#pragma unroll 1
          for (int i = 0; i < 3; i++) {
            tma_2d(sb + i * SLOT, &maps.wg, b * 32, 512 + i * 128, BAR(B_GU));
            tma_2d(sb + i * SLOT + 8192, &maps.wu, b * 32, 512 + i * 128, BAR(B_GU));
          }
        }
        mbar_wait(BAR(B_EMPTY + 1), 1);
        if (lane == 0) {
          mbar_expect_tx(BAR(B_GU), 16384);
          tma_2d(sb + STAGE + SLOT, &maps.wg, b * 32, 896, BAR(B_GU));
          tma_2d(sb + STAGE + SLOT + 8192, &maps.wu, b * 32, 896, BAR(B_GU));
        }
#pragma unroll 1
        for (int i = 0; i < 4; i++) {
          if (i == 1) mbar_wait(BAR(B_EMPTY + 2), 1);
          if (i == 3) mbar_wait(BAR(B_XDONE), 0);
          if (i >= FK_DNWIN) mbar_wait(BAR(B_DN + i - FK_DNWIN), 0);
          if (lane == 0) {
            mbar_expect_tx(BAR(B_DN + i), 16384);
            tma_3d(sb + dn_box(i), &maps.wdn, 0, b * 32, i * 4, BAR(B_DN + i));
          }
        }
      }
      __syncwarp();
    } else if (warp == 1) {
      asm volatile("add.u32 %0, %0, 1;" : "+r"(tag)::"memory");
      if (lane == 0) prefetch_tmap(&maps.ps);
      float a0 = 0.f, a1 = 0.f;
      auto rowsum = [&](int g0, int g1) {
        const uint32_t rb = sb + (m4 * 32 + lane) * 128 + ((lane & 7) << 4);
#pragma unroll 1
        for (int g = g0; g < g1; g++) {
          const int s = g & 3;
          mbar_wait(BAR(B_FULL + s), (g >> 2) & 1);
          uint4 u[8];
#pragma unroll
          for (int c = 0; c < 8; c++) u[c] = lds128u((rb ^ (uint32_t)(c << 4)) + s * STAGE);
#pragma unroll
          for (int c = 0; c < 8; c += 2) { a0 += sum8(u[c]); a1 += sum8(u[c + 1]); }
          if (lane == 0) mbar_arrive(BAR(B_EMPTYH + s) + ((__float_as_uint(a0) | __float_as_uint(a1)) & pp.zero));
        }
      };
      rowsum(0, FK_TG - 2);
      take(IntC<0>{});
      rowsum(FK_TG - 2, 28);
      mbar_wait(BAR(B_MODOK), 0);
      a0 += lds32(sb + RS_OFF + 256 + lane * 4);
      __syncwarp();
      uint2* rsp = &pp.mail->rs[(j * 16 + t) * 128 + lane];
      st_msg8(rsp + m4 * 32, __float_as_uint(a0 + a1), tag);
      {
        uint2 m[4]; int it = 0;
        while (true) {
#pragma unroll
          for (int i = 0; i < 4; i++) m[i] = ld_msg8(rsp + 32 * i);
          if (__all_sync(~0u, m[0].y == tag && m[1].y == tag && m[2].y == tag && m[3].y == tag)) break;
          if (++it > SPIN_LIMIT) SPIN_FAIL(0x208);
        }
#pragma unroll
        for (int i = 0; i < 4; i++) sts32u(sb + RS_OFF + (lane + 32 * i) * 4, pack_bf16(__uint_as_float(m[i].x), __uint_as_float(m[i].x)));
      }
      __syncwarp();
      if (lane == 0) { mbar_arrive(BAR(B_T1)); TRACE(11); }
      take(IntC<1>{});
      {
        unsigned* fl = &pp.mail->flagP[(((j * 16 + t) * 4 + m4) * 4) * 8];
        uint32_t cn = 0;
#pragma unroll 1
        for (int i = 0; i < 16; i++) {
          const int pr = (0x73625410u >> (4 * ((i >> 1) & 7))) & 7, q = pr & 3, half = pr < 4 ? 1 - j : j;
          if (i < 8) mbar_wait(BAR(B_PRDY + (q ? pr | 3 : pr)), 0);
          if (i) delay_until(cn, FK_PPACE);
          cn = (uint32_t)clock();
          if (lane == 0) {
            tma_store_2d(&maps.ps, sb + q * STAGE + half * 8192 + (i & 1) * 4096, m4 * 256 + q * 64, j * S_ + t * 128 + half * 64 + (i & 1) * 32);
            bulk_commit();
            if (i == 5 || i == 7 || i == 11 || i == 15) {
              const int dq = (i - 3) >> 2;
              bulk_wait<0>(); st_rlx(fl + dq * 8, tag); mbar_arrive(BAR(B_RDY + dq));
              if (i == 5) TRACE(29);
            }
          }
          __syncwarp();
        }
        if (lane == 0) TRACE(8);
      }
      named_bar<7, 64>();
      delay_until((uint32_t)clock(), FK_E2DLY);
      uint2 m; int it = 0;
      while (true) {
        m = ld_msg8(&pp.mail->cand[b * 32 + lane]);
        if (__all_sync(~0u, m.y != SENT)) break;
        if (++it > SPIN_LIMIT) SPIN_FAIL(0x206);
      }
      uint32_t k1, k2;
      warp_top2(m.x, m.y, k1, k2);
      if (lane == 0) {
        sts64u(sb + SEL_OFF, k1, k2);
        mbar_arrive(BAR(B_SEL));
        TRACE(19);
      }
    } else {
      const int kh = warp - 2;
      const uint32_t reg = sb + SPARE + kh * 16384;
#pragma unroll 1
      for (int i = 0; i < 2; i++) {
        const uint4 cw4 = ldg_nc(pp.c + (kh * 64 + lane + 32 * i) * 16);
        const uint32_t ad = reg + 12288 + (lane + 32 * i) * 32;
        sts128(ad, round_bf16(silu_f(bf_lo(cw4.x))), round_bf16(silu_f(bf_hi(cw4.x))), round_bf16(silu_f(bf_lo(cw4.y))), round_bf16(silu_f(bf_hi(cw4.y))));
        sts128(ad + 16, round_bf16(silu_f(bf_lo(cw4.z))), round_bf16(silu_f(bf_hi(cw4.z))), round_bf16(silu_f(bf_lo(cw4.w))), round_bf16(silu_f(bf_hi(cw4.w))));
        if (kh) { sts128u(sb + T1_OFF + (lane + 32 * i) * 32, SENT, SENT, SENT, SENT); sts128u(sb + T1_OFF + (lane + 32 * i) * 32 + 16, SENT, SENT, SENT, SENT); }
      }
      asm volatile("add.u32 %0, %0, 1;" : "+r"(tag)::"memory");
      fence_async_smem();
      if (lane == 0) prefetch_tmap(&maps.wm);
      {
        float acc[3][8];
        uint32_t sad[3];
#pragma unroll
        for (int a = 0; a < 3; a++) {
          sad[a] = reg + 12288 + ((32 * a + lane) / 6) * 4;
#pragma unroll
          for (int i = 0; i < 8; i++) acc[a][i] = 0.f;
        }
        const char* wpf = pp.wm + (size_t)kh * (512 * 12 * D_) + b * 6144;
        const char* wsrc = (j ? pp.ws_im : pp.ws_re) + (size_t)(t * 128 + m4 * 32 + kh * 16 - 16) * (2 * S_) + 28 * 128 + lane * 16;
        mbar_wait(BAR(B_FULL), 0);
        if (FK_WMPF && lane == 0) pf_bulk(wpf, 6144);
        uint32_t cn = (uint32_t)clock() + FK_PACE0 + (1 - kh) * (FK_PACE / 2);
        auto request = [&](int c) {
          mbar_expect_tx(BAR(B_WM + kh * 2 + (c & 1)), 6144 + ((__float_as_uint(acc[0][0]) | __float_as_uint(acc[1][0]) | __float_as_uint(acc[2][0])) & pp.zero));
          tma_2d_hint(reg + (c & 1) * 6144, &maps.wm, b * 48, kh * 512 + c * 64, BAR(B_WM + kh * 2 + (c & 1)), pol_first);
        };
        uint4 e[4];
#pragma unroll 1
        for (int c = -2; c < 8; c++) {
          while ((int)((uint32_t)clock() - cn) < 0) __nanosleep(40);
          cn += c < 0 ? FK_PACE0 : FK_PACE;
          if (lane == 0) {
            if (FK_WMPF && c < 5) pf_bulk(wpf + (size_t)(c + 3) * (64 * 12 * D_), 6144);
            if (c == FK_RSTEP && kh) {
              char* mb = reinterpret_cast<char*>(pp.mail) + (size_t)b * (MAIL_PER_CTA * 16);
#pragma unroll 1
              for (int o = 0; o < MAIL_PER_CTA * 16; o += 2048) bulk_store(mb + o, sb + T1_OFF, min(2048, MAIL_PER_CTA * 16 - o));
              bulk_commit();
            }
          }
          __syncwarp();
          if (c < 0) {
            if (c == -2) mbar_wait(BAR(B_EMPTY), 0);
            if (lane == 0) request(c + 2);
            __syncwarp();
            continue;
          }
          if (c >= 4) {
            const float v0 = sum8(e[0]), v1 = sum8(e[1]), v2 = sum8(e[2]), v3 = sum8(e[3]);
            const bool u4 = lane & 16, u3 = lane & 8;
            const float w0 = (u4 ? v2 : v0) + __shfl_xor_sync(~0u, u4 ? v0 : v2, 16), w1 = (u4 ? v3 : v1) + __shfl_xor_sync(~0u, u4 ? v1 : v3, 16);
            float v = (u3 ? w1 : w0) + __shfl_xor_sync(~0u, u3 ? w0 : w1, 8);
            v += __shfl_xor_sync(~0u, v, 4); v += __shfl_xor_sync(~0u, v, 2); v += __shfl_xor_sync(~0u, v, 1);
            if (!(lane & 7)) sts32(sb + RS_OFF + 256 + (kh * 16 + c * 4 - 16 + (lane >> 3)) * 4, v);
          }
          if (c >= 3 && c < 7) {
#pragma unroll
            for (int i = 0; i < 4; i++) e[i] = ldg_nc(wsrc + (size_t)(c * 4 + 4 + i) * (2 * S_));
          }
          mbar_wait(BAR(B_WM + kh * 2 + (c & 1)), (c >> 1) & 1);
#pragma unroll
          for (int u = 0; u < 12; u++) {
            const uint4 v = lds128u(reg + (c & 1) * 6144 + lane * 16 + u * 512);
            const float sc = lds32(sad[u % 3] + (u / 3) * 64);
            float (&ac)[8] = acc[u % 3];
            ac[0] = fmaf(sc, bf_lo(v.x), ac[0]); ac[1] = fmaf(sc, bf_hi(v.x), ac[1]);
            ac[2] = fmaf(sc, bf_lo(v.y), ac[2]); ac[3] = fmaf(sc, bf_hi(v.y), ac[3]);
            ac[4] = fmaf(sc, bf_lo(v.z), ac[4]); ac[5] = fmaf(sc, bf_hi(v.z), ac[5]);
            ac[6] = fmaf(sc, bf_lo(v.w), ac[6]); ac[7] = fmaf(sc, bf_hi(v.w), ac[7]);
          }
#pragma unroll
          for (int a = 0; a < 3; a++) sad[a] += 256;
          __syncwarp();
          if (lane == 0 && c < 6) request(c + 2);
        }
        __syncwarp();
#pragma unroll
        for (int a = 0; a < 3; a++) {
          sts128(reg + (32 * a + lane) * 32, acc[a][0], acc[a][1], acc[a][2], acc[a][3]);
          sts128(reg + (32 * a + lane) * 32 + 16, acc[a][4], acc[a][5], acc[a][6], acc[a][7]);
        }
        __syncwarp();
        float s0 = 0.f, s1 = 0.f;
#pragma unroll 8
        for (int m = 0; m < 16; m++) { const float2 v = lds64(reg + (lane < 24 ? lane * 8 : 0) + m * 192); s0 += v.x; s1 += v.y; }
        if (kh == 0) sts64(sb + RS_OFF + lane * 8, s0, s1);
        if (lane == 0) TRACE(80 + kh);
        named_bar<5, 64>();
        if (kh == 1) {
          const float2 p = lds64(sb + RS_OFF + lane * 8);
          __syncwarp();
          sts32u(sb + RS_OFF + lane * 4, pack_bf16(s0 + p.x, s1 + p.y));
          fence_async_smem();
          __syncwarp();
          if (lane == 0) {
            bulk_store(pp.mod + b * 24, sb + RS_OFF, 96); bulk_commit(); bulk_wait<0>();
            red_add(&pp.cnt[16 * 32], 1);
            TRACE(9);
          }
          __syncwarp();
        }
      }
      if (kh == 0) {
        if (lane == 0) { mbar_arrive(BAR(B_MODOK)); TRACE(57); }
#pragma unroll 1
        for (int i = 0; i < 4; i++) {
          const int w = i ^ 2;
          if (lane == 0) {
            if (moe) { mbar_expect_tx(BAR(B_WB + w), 8192); tma_2d_hint(sb + SPARE + w * 8192, &maps.wg, b * 32, w * 128, BAR(B_WB + w), pol_first); }
            else mbar_arrive(BAR(B_WB + w));
          }
          __nanosleep(FK_BSLEEP);
        }
        take(IntC<0>{});
        take(IntC<1>{});
        if (lane == 0) TRACE(98);
        const unsigned* flagAddr = &pp.mail->flagP[(((j * 16 + t) * 4 + sibling(m4, 1 + lane % 3)) * 4 + ((lane / 3) & 3)) * 8];
        mbar_wait(BAR(B_PRDY + 7), 0);
        bool done = lane >= 12; int it = 0;
        while (true) {
          if (!done && ld_rlx(flagAddr) == tag) {
            fence_async_global(); mbar_arrive(BAR(B_RDY + lane)); done = true;
          }
          if (__all_sync(~0u, done)) break;
          if (++it > SPIN_LIMIT) SPIN_FAIL(0x202);
        }
        if (lane == 0) TRACE(99);
      } else {
        take(IntC<0>{});
        {
          const unsigned tgt = tag * 128u; int it = 0;
          while ((int)(ld_rlx(&pp.cnt[16 * 32]) - tgt) < 0) { __nanosleep(100); if (++it > SPIN_LIMIT) SPIN_FAIL(0x204); }
        }
        if (lane == 0) { mbar_arrive(BAR(B_MODOK)); TRACE(10); }
        {
          const uint32_t sgn = j ? 0x80008000u : 0u;
          uint32_t sa[4], ca[4]; uint4 sv[4], cv[4], wr[4];
#pragma unroll
          for (int i = 0; i < 4; i++) {
            const int p = lane + 32 * i;
            sa[i] = ld_rlx(pp.mod + m4 * 128 + p); ca[i] = ld_rlx(pp.mod + 512 + m4 * 128 + p);
            sv[i] = ld_msg(reinterpret_cast<const uint4*>(pp.mod + 1536) + p); cv[i] = ld_msg(reinterpret_cast<const uint4*>(pp.mod + 2048) + p);
            wr[i] = ldg_nc(pp.wr + p * 16);
          }
          float c1 = 0.f, c2 = 0.f;
#pragma unroll
          for (int i = 0; i < 4; i++) {
            const int p = lane + 32 * i;
            sts64(sb + T1_OFF + ((p >> 3) * 4 + (p & 3)) * 16 + ((p >> 2) & 1) * 8, __uint_as_float(add1_bf2(ca[i]) ^ sgn), __uint_as_float(sa[i] ^ sgn));
            const uint32_t s4[4] = {sv[i].x, sv[i].y, sv[i].z, sv[i].w}, c4[4] = {cv[i].x, cv[i].y, cv[i].z, cv[i].w}, w4[4] = {wr[i].x, wr[i].y, wr[i].z, wr[i].w};
#pragma unroll
            for (int u = 0; u < 4; u++) {
              const uint32_t A = add1_bf2(c4[u]);
              c1 = fmaf(bf_lo(A), bf_lo(w4[u]), c1); c1 = fmaf(bf_hi(A), bf_hi(w4[u]), c1);
              c2 = fmaf(bf_lo(s4[u]), bf_lo(w4[u]), c2); c2 = fmaf(bf_hi(s4[u]), bf_hi(w4[u]), c2);
            }
          }
#pragma unroll
          for (int o = 16; o; o >>= 1) { c1 += __shfl_xor_sync(~0u, c1, o); c2 += __shfl_xor_sync(~0u, c2, o); }
          __syncwarp();
          if (lane == 0) { sts128(sb + CST_OFF, c1, c2, __uint_as_float(tag), 0.f); mbar_arrive(BAR(B_T1)); TRACE(30); }
        }
        take(IntC<1>{});
        const int G = lane >> 2, q = lane & 3, p0 = m4 * 128 + G * 16 + q;
        mbar_wait(BAR(B_PRDY + 3), 0);
        mbar_wait(BAR(B_PRDY + 7), 0);
        uint32_t ga[4], hi[4], lo[4];
#pragma unroll
        for (int u = 0; u < 4; u++) {
          ga[u] = ld_rlx(pp.mod + 1024 + p0 + 4 * u);
          const uint32_t cb = ld_rlx(pp.mod + 2048 + p0 + 4 * u), wr = __ldg(reinterpret_cast<const uint32_t*>(pp.wr) + p0 + 4 * u);
          const float w0 = bf_lo(add1_bf2(cb)) * bf_lo(wr), w1 = bf_hi(add1_bf2(cb)) * bf_hi(wr);
          hi[u] = pack_bf16(w0, w1);
          lo[u] = pack_bf16(w0 - bf_lo(hi[u]), w1 - bf_hi(hi[u]));
        }
        sts128u(sb + GA_OFF + lane * 16, ga[0], ga[1], ga[2], ga[3]);
        sts128u(sb + W_OFF + G * 144 + q * 16, hi[0], hi[1], hi[2], hi[3]);
        sts128u(sb + W_OFF + G * 144 + 64 + q * 16, lo[0], lo[1], lo[2], lo[3]);
        sts32u(sb + W_OFF + G * 144 + 128 + q * 4, 0x3F803F80u);
        __syncwarp();
        if (lane == 0) mbar_arrive(BAR(B_T2));
      }
    }
    mbar_wait(BAR(B_SEL), 0);
    const uint32_t csel = (uint32_t)clock();
    if (moe) gate_up(pp, wf, sb, scr, warp, lane);
    if (warp == 1) {
      const uint2 sel = lds64u(sb + SEL_OFF);
      const int n = (lane >> 3) & 1;
      const int col = (b >> 4) * 128 + (lane & 1) * 64 + ((b >> 2) & 3) * 16 + (b & 3) * 2 + ((lane >> 1) & 1) + (lane >> 4) * 8;
      const int slot = sel_slot(sel, n) * 512, wofs = slot + ((col >> 5) * 4 + ((col >> 1) & 3)) * 4 + ((col >> 3) & 3);
      const uint32_t gbp = ld_rlx(pp.mod + 2560 + (col >> 1));
      uint32_t hp, xp; int it = 0;
      while (true) {
        hp = ld_rlx(reinterpret_cast<const uint32_t*>(pp.mail->rowh) + wofs); xp = ld_rlx(reinterpret_cast<const uint32_t*>(pp.mail->rowx) + slot + (col >> 1));
        if (__all_sync(~0u, hp != SENT && xp != SENT)) break;
        if (++it > SPIN_LIMIT) SPIN_FAIL(0x2ff);
      }
      const float sg = round_bf16(sigmoid_f(round_bf16(key_val(n ? sel.y : sel.x))));
      const int gq = lane >> 2;
      const uint32_t one = (lane & 1) == (gq >> 2) ? ((gq & 1) ? 0x3F800000u : 0x00003F80u) : 0u;
      const uint32_t s0 = (gq & 2) ? 0u : one, s1 = (gq & 2) ? one : 0u;
      const uint4* src = &pp.mail->part[(size_t)b * (NMOE * 2) + lane];
      uint4 m[7];
      delay_until(csel, FK_E4DLY);
      it = 0;
      while (true) {
        bool ok = true;
#pragma unroll
        for (int i = 0; i < 7; i++) m[i] = ld_msg(src + 32 * i);
#pragma unroll
        for (int i = 0; i < 7; i++) ok &= m[i].x != SENT;
        if (__all_sync(~0u, ok)) break;
        if (++it > SPIN_LIMIT) SPIN_FAIL(0x20b);
      }
      if (lane == 0) TRACE(23);
      float c[3][4];
#pragma unroll
      for (int i = 0; i < 3; i++) { c[i][0] = c[i][1] = c[i][2] = c[i][3] = 0.f; }
#pragma unroll
      for (int i = 0; i < 7; i++) mma_16816(c[i % 3], m[i].x, m[i].y, m[i].z, m[i].w, s0, s1);
#pragma unroll
      for (int i = 0; i < 4; i++) c[0][i] += c[1][i] + c[2][i];
      const bool u4 = lane & 16, u3 = lane & 8;
      const float a0 = (u4 ? c[0][2] : c[0][0]) + __shfl_xor_sync(~0u, u4 ? c[0][0] : c[0][2], 16), a1 = (u4 ? c[0][3] : c[0][1]) + __shfl_xor_sync(~0u, u4 ? c[0][1] : c[0][3], 16);
      float y = (u3 ? a1 : a0) + __shfl_xor_sync(~0u, u3 ? a0 : a1, 8);
      y += __shfl_xor_sync(~0u, y, 4);
      const bool odd = col & 1;
      const float upd = round_bf16(round_bf16(y) * sg);
      const float o = fmaf(odd ? bf_hi(gbp) : bf_lo(gbp), (odd ? bf_hi(hp) : bf_lo(hp)) + upd, odd ? bf_hi(xp) : bf_lo(xp));
      if (!(lane & 4)) reinterpret_cast<__nv_bfloat16*>(pp.out)[(size_t)key_row(n ? sel.y : sel.x) * D_ + col] = __float2bfloat16_rn(o);
      if (lane == 0) { TRACE(24); TRACE_CLK(54); if (b == 0) pp.cnt[1] = tag; }
    }
  } else {
    const int cw = (warp - 4) >> 2;
    const int wq = warp & 3;
    const int wtid = tid & 127;
    const int gq = lane >> 2, q4 = lane & 3;
    const bool lag = cw == j;
    const bool elect = wtid == 0;
    const uint32_t rel = wtid < 2 ? mapa(BAR(B_EMPTY), wtid) : 0;

    named_bar<0, 384>();
    asm volatile("barrier.cluster.wait.acquire.aligned;" ::: "memory");

    const int mrow = wq * 16 + (lane & 7) + ((lane >> 3) & 1) * 8;
    {
      float acc[128];
      gemm_phase<1, 0, 32>(pp, acc, sb, cw, lag, elect, rel);
      mbar_wait(BAR(B_T1), 0);
      const uint32_t tad = sb + T1_OFF + q4 * 16;
      uint4 tb[16];
#pragma unroll
      for (int c = 0; c < 4; c++) tb[c] = lds128u(tad + c * 64);
      const uint32_t rs0 = lds32u(sb + RS_OFF + (cw * 64 + wq * 16 + gq) * 4), rs1 = lds32u(sb + RS_OFF + (cw * 64 + wq * 16 + gq + 8) * 4);
      const uint32_t dst = sb + cw * 8192 + mrow * 128, pb = BAR(B_PRDY + (lag ? 4 : 0));
      gemm_finish(acc, rel);
      if (elect) { TRACE(lag ? 5 : 4); if (lag) TRACE_CLK(51); }
#pragma unroll
      for (int i = 0; i < 16; i++) {
        uint32_t r[4];
        const int o = 8 * i;
        r[0] = fma_bf2(pack_bf16(acc[o], acc[o + 1]), tb[i].x, mul_bf2(rs0, tb[i].y));
        r[1] = fma_bf2(pack_bf16(acc[o + 2], acc[o + 3]), tb[i].x, mul_bf2(rs1, tb[i].y));
        r[2] = fma_bf2(pack_bf16(acc[o + 4], acc[o + 5]), tb[i].z, mul_bf2(rs0, tb[i].w));
        r[3] = fma_bf2(pack_bf16(acc[o + 6], acc[o + 7]), tb[i].z, mul_bf2(rs1, tb[i].w));
        if (i < 12) tb[i + 4] = lds128u(tad + (i + 4) * 64);
        stsm_x4(dst + (i >> 2) * STAGE + (uint32_t)(((((2 * i) & 7) + (lane >> 4)) ^ (lane & 7)) << 4), r[0], r[1], r[2], r[3]);
        if (i == 3 || i == 15) {
          fence_async_smem();
          __syncwarp();
          if (lane == 0) mbar_arrive(pb + (i >> 2) * 8);
        }
      }
      mbar_wait(pb + 24, 0);
    }
    if (elect) TRACE(lag ? 7 : 6);
    float acc[128];
    gemm_phase<0, 32, 48>(pp, acc, sb, cw, lag, elect, rel);

    if (!lag) {
      const uint32_t rdst = mapa(sb + STAGE + j * 8192 + wtid * 16, j ^ 1), rbar = mapa(BAR(B_RECV), j ^ 1);
      mbar_wait(BAR(B_T2), 0);
      mbar_wait(BAR(B_X), 0);
      uint32_t xf[16][4]; uint4 ga[8];
      auto fetch = [&](int i) {
        ldsm_x4(sb + SPARE + (i >> 2) * 8192 + mrow * 128 + (uint32_t)(((((2 * i) & 7) + (lane >> 4)) ^ (lane & 7)) << 4), xf[i][0], xf[i][1], xf[i][2], xf[i][3]);
        if (!(i & 1)) ga[i >> 1] = lds128u(sb + GA_OFF + ((i >> 1) * 4 + q4) * 16);
      };
      fetch(0); fetch(1); fetch(2);
      gemm_finish(acc, rel);
      if (elect) { mbar_arrive_cluster(rbar + (B_PEER + 1 - B_RECV) * 8); TRACE(12); }
#pragma unroll
      for (int i = 0; i < 16; i++) {
        const int o = 8 * i;
        const uint32_t g0 = (i & 1) ? ga[i >> 1].z : ga[i >> 1].x, g1 = (i & 1) ? ga[i >> 1].w : ga[i >> 1].y;
        const uint32_t w0 = fma_bf2(g0, pack_bf16(acc[o], acc[o + 1]), xf[i][0]), w1 = fma_bf2(g0, pack_bf16(acc[o + 2], acc[o + 3]), xf[i][1]);
        const uint32_t w2 = fma_bf2(g1, pack_bf16(acc[o + 4], acc[o + 5]), xf[i][2]), w3 = fma_bf2(g1, pack_bf16(acc[o + 6], acc[o + 7]), xf[i][3]);
        if (i == 0) { fetch(3); fetch(4); } else if (i < 12) fetch(i + 4);
        if (i == 0) mbar_wait_cluster(BAR(B_PEER), 0);
        if (i == 8) mbar_wait_cluster(BAR(B_PEER + 1), 0);
        if (i == 12) mbar_wait_cluster(BAR(B_EMPTY + 1), 1);
        asm volatile("st.async.weak.shared::cluster.mbarrier::complete_tx::bytes.v4.b32 [%0], {%1, %2, %3, %4}, [%5];"
                     ::"r"(i < 12 ? rdst + (i >> 2) * STAGE + (i & 3) * 2048 : rdst + (1 - 2 * j) * 8192 + (i & 3) * 2048), "r"(w0), "r"(w1), "r"(w2), "r"(w3),
                       "r"(rbar + (i >> 2) * 8) : "memory");
      }
      __syncwarp();
      if (lane == 0) mbar_arrive(BAR(B_XDONE));
      if (elect) TRACE(13);
      if (b < NMOE) {
        uint32_t wf[128];
        mbar_wait(BAR(B_GU), 0);
        const uint32_t box = sb + (wq < 3 ? wq : 4) * SLOT;
        take_box<0>(wf, box, lane);
        take_box<1>(wf, box + 8192, lane);
        if (elect) TRACE(26);
        mbar_wait(BAR(B_SEL), 0);
        gate_up(pp, wf, sb, scr, 4 + wq, lane);
      }
      OutTab tb;
      {
        const uint4* mp = reinterpret_cast<const uint4*>(pp.mod) + m4 * 32 + lane;
        out_tab(tb, ld_msg(mp + 512), ld_msg(mp + 384), ld_msg(mp + 640));
      }
      mbar_wait(BAR(B_SEL), 0);
      const uint2 sel = lds64u(sb + SEL_OFF), cnd = lds64u(sb + TOP_OFF + 32);
      char* odst = pp.out + (size_t)blk * (64 * 2 * D_) + m4 * 512 + lane * 16;
      const int s1 = key_row(sel.x) - blk * 64, s2 = key_row(sel.y) - blk * 64, c1 = key_row(cnd.x) - blk * 64, c2 = key_row(cnd.y) - blk * 64;
#pragma unroll 1
      for (int r = wq * 16; r < wq * 16 + 16; r++) {
        if (r == s1 || r == s2 || ((r & 15) < FK_OSPLIT && r != c1 && r != c2)) continue;
        const uint32_t cn = (uint32_t)clock();
        out_row(tb, sb, scr, r, lane, odst);
        if ((r & 15) < 15) delay_until(cn, FK_OPACE);
      }
      if (elect) TRACE(28);
    } else {
      mbar_wait(BAR(B_T2), 0);
      uint32_t xa[64];
      float dl[2][4], dq[4][4];
#pragma unroll
      for (int i = 0; i < 4; i++) { dl[0][i] = dl[1][i] = dq[0][i] = dq[1][i] = dq[2][i] = dq[3][i] = 0.f; }
      {
        const uint32_t wad = sb + W_OFF + ((gq & 2) ? 128 : (gq & 1) * 64 + q4 * 16), rsrc = sb + STAGE + (1 - j) * 8192 + wtid * 16;
        uint4 rv[16], wb[8], ga[8];
        auto fetch = [&](int i) {
          if (!(i & 3)) mbar_wait_cluster(BAR(B_RECV + (i >> 2)), 0);
          rv[i] = lds128u(i < 12 ? rsrc + (i >> 2) * STAGE + (i & 3) * 2048 : rsrc + (2 * j - 1) * 8192 + (i & 3) * 2048);
          if (!(i & 1)) ga[i >> 1] = lds128u(sb + GA_OFF + ((i >> 1) * 4 + q4) * 16); else wb[i >> 1] = lds128u(wad + (i >> 1) * 144);
        };
        fetch(0); fetch(1);
        gemm_finish(acc, rel);
        if (elect) { TRACE(14); TRACE_CLK(53); }
#pragma unroll
        for (int i = 0; i < 16; i++) {
          const int o = 8 * i;
          const uint32_t g0 = (i & 1) ? ga[i >> 1].z : ga[i >> 1].x, g1 = (i & 1) ? ga[i >> 1].w : ga[i >> 1].y;
          const uint32_t a0 = fma_bf2(g0, pack_bf16(acc[o], acc[o + 1]), rv[i].x), a1 = fma_bf2(g0, pack_bf16(acc[o + 2], acc[o + 3]), rv[i].y);
          const uint32_t a2 = fma_bf2(g1, pack_bf16(acc[o + 4], acc[o + 5]), rv[i].z), a3 = fma_bf2(g1, pack_bf16(acc[o + 6], acc[o + 7]), rv[i].w);
          if (i < 14) fetch(i + 2);
          xa[4 * i] = a0; xa[4 * i + 1] = a1; xa[4 * i + 2] = a2; xa[4 * i + 3] = a3;
          mma_1688(dq[0], a0, a1, a0); mma_1688(dq[1], a0, a1, a1);
          mma_1688(dq[2], a2, a3, a2); mma_1688(dq[3], a2, a3, a3);
          if (i & 1) {
            mma_16816(dl[0], xa[4 * i - 4], xa[4 * i - 3], xa[4 * i - 2], xa[4 * i - 1], wb[i >> 1].x, wb[i >> 1].y);
            mma_16816(dl[1], a0, a1, a2, a3, wb[i >> 1].z, wb[i >> 1].w);
          }
        }
      }
      const float4 cst = lds128(sb + CST_OFF);
      const uint32_t tag = __float_as_uint(cst.z);
      {
        const bool odd = q4 & 1;
        const float l0 = dl[0][0] + dl[1][0], l1 = dl[0][1] + dl[1][1], l2 = dl[0][2] + dl[1][2], l3 = dl[0][3] + dl[1][3];
        const float mine = odd ? l2 : l0 + l1;
        const float other = __shfl_xor_sync(~0u, odd ? l0 : l2 + l3, 1);
        const int dsrc = (lane & ~3) | (gq >> 1);
        const float qa = __shfl_sync(~0u, (gq & 1) ? dq[0][1] + dq[2][1] : dq[0][0] + dq[2][0], dsrc);
        const float qb = __shfl_sync(~0u, (gq & 1) ? dq[1][3] + dq[3][3] : dq[1][2] + dq[3][2], dsrc);
        if (q4 < 2) st_msg(&pp.mail->stats[(blk * 4 + m4) * 64 + wq * 16 + gq + 8 * q4], __float_as_uint(odd ? mine : other), __float_as_uint(odd ? qb : qa),
                           __float_as_uint(odd ? other : mine), tag);
      }
      const uint32_t cpub = (uint32_t)clock();
      if (elect) TRACE(15);
      const uint4* mp = reinterpret_cast<const uint4*>(pp.mod) + m4 * 32 + lane;
      const uint4 cbv = ld_msg(mp + 512), sbv = ld_msg(mp + 384), gbv = ld_msg(mp + 640);
      mbar_wait(BAR(B_EMPTY + 3), 1);
#pragma unroll
      for (int i = 0; i < 16; i++)
        stsm_x4(sb + XST_OFF + mrow * 512 + (uint32_t)(((2 * i + (lane >> 4)) ^ (lane & 7)) << 4), xa[4 * i], xa[4 * i + 1], xa[4 * i + 2], xa[4 * i + 3]);
      uint32_t k1, k2;
      {
        const uint4* src = &pp.mail->stats[(blk * 4 + (lane >> 4) * 2) * 64 + wq * 16 + (lane & 15)];
        uint4 m0, m1; int it = 0;
        delay_until(cpub, FK_E1DLY);
        while (true) {
          m0 = ld_msg(src); m1 = ld_msg(src + 64);
          if (__all_sync(~0u, m0.w == tag && m1.w == tag)) break;
          if (++it > SPIN_LIMIT) SPIN_FAIL(0x209);
        }
        if (elect) TRACE(16);
        float sa = __uint_as_float(m0.x) + __uint_as_float(m1.x), qa = __uint_as_float(m0.y) + __uint_as_float(m1.y), da = __uint_as_float(m0.z) + __uint_as_float(m1.z);
        sa += __shfl_xor_sync(~0u, sa, 16); qa += __shfl_xor_sync(~0u, qa, 16); da += __shfl_xor_sync(~0u, da, 16);
        const float mean = sa * (1.f / D_);
        const float rstd = rsqrtf(fmaxf(fmaf(-mean, mean, qa * (1.f / D_)), 0.f) + 1e-5f);
        const float rme = fmaf(rstd, fmaf(-mean, cst.x, da), cst.y);
        warp_top2(fkey(rme, blk * 64 + wq * 16 + (lane & 15)), 0u, k1, k2);
        if (lane == 0) sts64u(sb + TOP_OFF + wq * 8, k1, k2);
        if (lane < 16) sts64(scr + RST_REL + (wq * 16 + lane) * 8, rstd, -mean * rstd);
        named_bar<2, 128>();
        const uint2 c = lds64u(sb + TOP_OFF + (lane & 3) * 8);
        warp_top2(c.x, c.y, k1, k2);
        if (wq == 0) {
          st_msg8(&pp.mail->cand[(m4 * 32 + lane) * 32 + blk], k1, k2);
          if (lane == 0) sts64u(sb + TOP_OFF + 32, k1, k2);
          named_arrive<7, 64>();
        }
      }
      if (elect) TRACE(17);
      const int c1 = key_row(k1) - blk * 64, c2 = key_row(k2) - blk * 64;
      if (wq >= 2) {
        const int r = wq == 2 ? c1 : c2;
        const uint4 v = lds128u(sb + XST_OFF + r * 512 + ((lane ^ (r & 7)) << 4));
        const float2 st = lds64(scr + RST_REL + r * 8);
        auto h2 = [&](uint32_t xv, uint32_t cv, uint32_t sv) {
          const uint32_t av = add1_bf2(cv);
          return pack_bf16(fmaf(fmaf(bf_lo(xv), st.x, st.y), bf_lo(av), bf_lo(sv)), fmaf(fmaf(bf_hi(xv), st.x, st.y), bf_hi(av), bf_hi(sv)));
        };
        const uint32_t sc = scr + SCR_REL + wq * 512;
        sts128u(sc + lane * 16, h2(v.x, cbv.x, sbv.x), h2(v.y, cbv.y, sbv.y), h2(v.z, cbv.z, sbv.z), h2(v.w, cbv.w, sbv.w));
        __syncwarp();
        const uint32_t fa = sc + gq * 64 + q4 * 4;
        const int o = (blk * 2 + wq - 2) * 128 + m4 * 32 + lane;
        st_msg(&pp.mail->rowh[o], lds32u(fa), lds32u(fa + 16), lds32u(fa + 32), lds32u(fa + 48));
        st_msg(&pp.mail->rowx[o], v.x, v.y, v.z, v.w);
        if (lane == 0 && wq == 3) TRACE(18);
      }
      {
        OutTab tb;
        out_tab(tb, cbv, sbv, gbv);
        char* odst = pp.out + (size_t)blk * (64 * 2 * D_) + m4 * 512 + lane * 16;
#pragma unroll 1
        for (int r = wq * 16; r < wq * 16 + FK_OSPLIT; r++) {
          if (r == c1 || r == c2) continue;
          const uint32_t cn = (uint32_t)clock();
          out_row(tb, sb, scr, r, lane, odst);
          if ((r & 15) < FK_OSPLIT - 1) delay_until(cn, FK_OPACE);
        }
      }
      if (elect) TRACE(25);
      if (b < NMOE) {
        uint32_t wd[128];
        mbar_wait(BAR(B_DN + wq), 0);
        {
          const int fr = (lane & 7) + (lane >> 4) * 8;
          const uint32_t base = sb + dn_box(wq) + fr * 128;
#pragma unroll
          for (int c = 0; c < 4; c++) {
            const uint32_t ad = base + (((uint32_t)(c * 2 + ((lane >> 3) & 1)) ^ (uint32_t)(lane & 7)) << 4);
#pragma unroll
            for (int gI = 0; gI < 4; gI++)
#pragma unroll
              for (int ks = 0; ks < 2; ks++) {
                const int o = ((gI * 4 + c) * 2 + ks) * 4;
                ldsm_x4_t(ad + gI * 4096 + ks * 2048, wd[o], wd[o + 1], wd[o + 2], wd[o + 3]);
              }
          }
        }
        uint4* dst = &pp.mail->part[((size_t)(wq * 32 + q4 * 4 + (gq >> 1)) * NMOE + b) * 2 + (gq & 1)];
        if (lane == 0 && wq == 3) TRACE(27);
        named_bar<4, 384>();
        if (elect) TRACE(21);
        float g0 = 0.f, g1 = 0.f, u0 = 0.f, u1 = 0.f;
#pragma unroll
        for (int w = 0; w < 8; w++) {
          const float2 gv = lds64(scr + PART_REL + w * 512 + lane * 8), uv = lds64(scr + PART_REL + w * 512 + 256 + lane * 8);
          g0 += gv.x; g1 += gv.y; u0 += uv.x; u1 += uv.y;
        }
        const uint32_t act = pack_bf16(round_bf16(silu_f(round_bf16(g0))) * round_bf16(u0), round_bf16(silu_f(round_bf16(g1))) * round_bf16(u1));
        uint32_t ab[4];
#pragma unroll
        for (int u = 0; u < 4; u++) {
          const uint32_t v0 = __shfl_sync(~0u, act, 8 * u + 2 * q4), v1 = __shfl_sync(~0u, act, 8 * u + 2 * q4 + 1);
          ab[u] = __byte_perm(v0, v1, (gq & 1) ? 0x7632 : 0x5410);
        }
        float c[4][4];
#pragma unroll
        for (int v = 0; v < 4; v++) { c[v][0] = c[v][1] = c[v][2] = c[v][3] = 0.f; }
#pragma unroll
        for (int q = 0; q < 4; q++) {
          const uint32_t mk = (gq >> 1) == q ? ~0u : 0u;
          const uint32_t b0 = ab[0] & mk, b1 = ab[1] & mk, b2 = ab[2] & mk, b3 = ab[3] & mk;
#pragma unroll
          for (int v = 0; v < 4; v++) { const int o = (4 * v + q) * 8; mma_16816(c[v], wd[o], wd[o + 1], wd[o + 2], wd[o + 3], b0, b1); }
#pragma unroll
          for (int v = 0; v < 4; v++) { const int o = (4 * v + q) * 8 + 4; mma_16816(c[v], wd[o], wd[o + 1], wd[o + 2], wd[o + 3], b2, b3); }
        }
#pragma unroll
        for (int u = 0; u < 2; u++)
          st_msg(dst + u * (16 * NMOE * 2), pack_bf16(c[2 * u][0], c[2 * u][1]), pack_bf16(c[2 * u][2], c[2 * u][3]),
                 pack_bf16(c[2 * u + 1][0], c[2 * u + 1][1]), pack_bf16(c[2 * u + 1][2], c[2 * u + 1][3]));
        if (elect) TRACE(22);
      }
    }
  }
}

typedef CUresult (*PFN_encodeTiled)(CUtensorMap*, CUtensorMapDataType, cuuint32_t, void*, const cuuint64_t*, const cuuint64_t*,
                                    const cuuint32_t*, const cuuint32_t*, CUtensorMapInterleave, CUtensorMapSwizzle,
                                    CUtensorMapL2promotion, CUtensorMapFloatOOBfill);

static void map2d(PFN_encodeTiled enc, CUtensorMap* m, const void* p, uint64_t rows, uint64_t cols, uint32_t brows, uint32_t bcols, CUtensorMapSwizzle sw,
                  CUtensorMapL2promotion pr = CU_TENSOR_MAP_L2_PROMOTION_L2_128B) {
  cuuint64_t dims[2] = {cols, rows}; cuuint64_t str[1] = {cols * 2}; cuuint32_t box[2] = {bcols, brows}; cuuint32_t es[2] = {1, 1};
  enc(m, CU_TENSOR_MAP_DATA_TYPE_BFLOAT16, 2, (void*)p, dims, str, box, es, CU_TENSOR_MAP_INTERLEAVE_NONE, sw, pr,
      CU_TENSOR_MAP_FLOAT_OOB_FILL_NONE);
}
static void map3d(PFN_encodeTiled enc, CUtensorMap* m, const void* p, uint64_t rows, uint64_t cols, uint32_t brows, uint32_t bgroups) {
  cuuint64_t dims[3] = {64, rows, cols / 64}; cuuint64_t str[2] = {cols * 2, 128}; cuuint32_t box[3] = {64, brows, bgroups}; cuuint32_t es[3] = {1, 1, 1};
  enc(m, CU_TENSOR_MAP_DATA_TYPE_BFLOAT16, 3, (void*)p, dims, str, box, es, CU_TENSOR_MAP_INTERLEAVE_NONE, CU_TENSOR_MAP_SWIZZLE_128B,
      CU_TENSOR_MAP_L2_PROMOTION_L2_128B, CU_TENSOR_MAP_FLOAT_OOB_FILL_NONE);
}

}

extern "C" void kernel_launch(void* const* d_in, const int* in_sizes, int n_in, void* d_out, int out_size) {
  using namespace fk;
  (void)in_sizes; (void)n_in; (void)out_size;
  static PFN_encodeTiled enc = nullptr;
  static int maxClusters = -1;
  static void *pn = nullptr, *pP = nullptr, *pc = nullptr, *pm = nullptr, *pmod = nullptr;
  if (!enc) {
    void* fn = nullptr; cudaDriverEntryPointQueryResult qr;
    cudaGetDriverEntryPoint("cuTensorMapEncodeTiled", &fn, cudaEnableDefault, &qr);
    enc = (PFN_encodeTiled)fn;
    cudaGetSymbolAddress(&pn, g_n);
    cudaGetSymbolAddress(&pP, g_P);
    cudaGetSymbolAddress(&pc, g_cnt);
    cudaGetSymbolAddress(&pm, g_mail);
    cudaGetSymbolAddress(&pmod, g_mod);
    cudaFuncSetAttribute(fused_kernel, cudaFuncAttributeMaxDynamicSharedMemorySize, SMEM_BYTES);
  }
  Maps maps;
  map2d(enc, &maps.ws[0], d_in[1], S_, S_, 128, 64, CU_TENSOR_MAP_SWIZZLE_128B);
  map2d(enc, &maps.ws[1], d_in[2], S_, S_, 128, 64, CU_TENSOR_MAP_SWIZZLE_128B);
  map3d(enc, &maps.n, pn, S_, D_, 64, 4);
  map2d(enc, &maps.p, pP, 2 * S_, D_, 128, 64, CU_TENSOR_MAP_SWIZZLE_128B);
  map2d(enc, &maps.ps, pP, 2 * S_, D_, 32, 64, CU_TENSOR_MAP_SWIZZLE_128B);
  map2d(enc, &maps.wd[0], d_in[3], D_, D_, 256, 64, CU_TENSOR_MAP_SWIZZLE_128B);
  map2d(enc, &maps.wd[1], d_in[4], D_, D_, 256, 64, CU_TENSOR_MAP_SWIZZLE_128B);
  map2d(enc, &maps.x, d_in[0], S_, D_, 64, 64, CU_TENSOR_MAP_SWIZZLE_128B);
  map2d(enc, &maps.wg, d_in[7], D_, F_, 128, 32, CU_TENSOR_MAP_SWIZZLE_64B);
  map2d(enc, &maps.wu, d_in[8], D_, F_, 128, 32, CU_TENSOR_MAP_SWIZZLE_64B);
  map3d(enc, &maps.wdn, d_in[9], F_, D_, 32, 4);
  map2d(enc, &maps.wm, d_in[11], D_, 6 * D_, 64, 48, CU_TENSOR_MAP_SWIZZLE_NONE);

  cudaLaunchConfig_t cfg = {};
  cfg.gridDim = dim3(NCTA); cfg.blockDim = dim3(384); cfg.dynamicSmemBytes = SMEM_BYTES; cfg.stream = cudaStreamPerThread;
  cudaLaunchAttribute at[1];
  at[0].id = cudaLaunchAttributeClusterDimension; at[0].val.clusterDim.x = 2; at[0].val.clusterDim.y = 1; at[0].val.clusterDim.z = 1;
  cfg.attrs = at; cfg.numAttrs = 1;
  Ptrs pp{(const char*)d_in[0], (char*)pn, (unsigned*)pc, 0, 0, (Mail*)pm, (uint32_t*)pmod, (const char*)d_in[10], (const char*)d_in[1], (const char*)d_in[2],
          (const char*)d_in[3], (const char*)d_in[4], (const char*)d_in[6], (const char*)d_in[7], (const char*)d_in[8], (const char*)d_in[9], (const char*)d_in[11], (char*)d_out, nullptr};
  if (maxClusters < 0) {
    cfg.gridDim = dim3(NCTA + NEXTRA);
    if (cudaOccupancyMaxActiveClusters(&maxClusters, fused_kernel, &cfg) != cudaSuccess) maxClusters = 0;
  }
  pp.b0 = -NEXTRA;
  if (maxClusters >= (NCTA + NEXTRA) / 2) {
    cfg.gridDim = dim3(NCTA + NEXTRA);
  } else {
    cfg.gridDim = dim3(NEXTRA);
    cudaLaunchKernelEx(&cfg, fused_kernel, pp, maps);
    cfg.gridDim = dim3(NCTA); pp.b0 = 0;
  }
  cudaLaunchKernelEx(&cfg, fused_kernel, pp, maps);
}
```

```cpp
#include <cuda_runtime.h>
#include <cuda_bf16.h>
#include <cuda.h>
#include <stdint.h>

#define DEVINL __device__ __forceinline__

namespace fk {

constexpr int S_ = 2048, D_ = 1024, F_ = 3584;
constexpr int NCTA = 128;
constexpr int NEXTRA = 4;
constexpr int NMOE = 112;
constexpr int SLOT = 16384;
constexpr int STAGE = 3 * SLOT;
constexpr int SPARE = 4 * STAGE;
constexpr int MISC = SPARE + 32768;
constexpr int SMEM_BYTES = MISC + 3072;
constexpr int BAR_OFF = MISC;
constexpr int CST_OFF = MISC + 480;
constexpr int SEL_OFF = MISC + 496;
constexpr int T1_OFF = MISC + 512;
constexpr int RS_OFF = T1_OFF + 2048;
constexpr int GA_OFF = T1_OFF;
constexpr int W_OFF = GA_OFF + 512;
constexpr int TOP_OFF = GA_OFF + 1792;
constexpr int XST_OFF = 3 * STAGE + SLOT;
constexpr int PART_REL = 0;
constexpr int SCR_REL = 4096;
constexpr int RST_REL = 6144;
enum { B_FULL = 0, B_EMPTY = 4, B_EMPTYH = 8, B_PRDY = 12  , B_PL = 16  , B_WM = 20  , B_RDY = 24  , B_WB = 36  ,
       B_DN = 40  , B_RECV = 44  , B_STAG = 48, B_T1 = 49, B_MODOK = 50, B_PEER = 51  , B_X = 53, B_T2 = 54, B_GU = 55,
       B_XDONE = 56, B_SEL = 57, B_NUM = 58 };

__host__ __device__ constexpr int bar_count(int i) {
  return (i >= B_EMPTY && i < B_EMPTYH) || (i >= B_PRDY && i < B_PL) || i == B_X || i == B_XDONE ? 4
         : (i == B_T1 || i == B_GU || i == B_MODOK || (i >= B_RDY && i < B_RDY + 4)) ? 2 : 1;
}

#define FK_XDEPTH 2
#define FK_G0 8
#define FK_ROW0DLY 500
#define FK_ROWDLY 200
#define FK_WS0DLY 400
#define FK_WS1DLY 1400
#define FK_ADLY 1800
#define FK_L1 2
#define FK_L2 3
#define FK_PF0 19
#define FK_E1DLY 300
#define FK_E2DLY 300
#define FK_E4DLY 3000
#define FK_RSTEP 6
#define FK_MAILQ 14
#define FK_MAP 3
#define FK_PPACE 340
#define FK_PACE0 1000
#define FK_WMPF 0
#define FK_TG 28
#define FK_TU 31
#define FK_BSLEEP 250
#define FK_PFSKIP 0
#define FK_DNWIN 1
#define FK_OPACE 220
#define FK_OSPLIT 7
#define FK_PFDLY 600
#define FK_PACE 2000
constexpr int SPIN_LIMIT = 1 << 22;
constexpr uint32_t SENT = 0xFFFFFFFFu;

struct Maps {
  CUtensorMap ws[2];
  CUtensorMap n;
  CUtensorMap p;
  CUtensorMap ps;
  CUtensorMap wd[2];
  CUtensorMap x;
  CUtensorMap wg, wu;
  CUtensorMap wdn;
  CUtensorMap wm;
};
template <int V> struct IntC { static constexpr int value = V; };
struct Mail;
struct Ptrs { const char* x; char* n; unsigned* cnt; int b0; uint32_t zero; Mail* mail; uint32_t* mod; const char *c, *ws_re, *ws_im, *wd_re, *wd_im, *wr, *wg, *wu, *wdn, *wm, *P; char* out; unsigned long long* trace; };

__device__ __align__(1024) __nv_bfloat16 g_n[S_ * D_];
__device__ __align__(1024) __nv_bfloat16 g_P[2 * S_ * D_];
__device__ __align__(128) uint32_t g_mod[3 * D_];
__device__ __align__(128) unsigned g_cnt[17 * 32];
struct Mail {
  uint4 stats[32 * 4 * 64];
  uint2 cand[128 * 32];
  uint4 rowh[64 * 128];
  uint4 rowx[64 * 128];
  uint4 part[128 * NMOE * 2];
  uint2 rs[2 * 16 * 128];
  unsigned flagP[512 * 8];
};
static_assert(sizeof(Mail) % (16 * NCTA) == 0, "mail size");
static_assert(FK_L2 == 3, "the receive layout assumes a stagger of three k-blocks");
constexpr int MAIL_PER_CTA = sizeof(Mail) / 16 / NCTA;
__device__ __align__(1024) Mail g_mail;

#define SPIN_FAIL(what) __trap()
DEVINL uint32_t smem_u32(const void* p) { return (uint32_t)__cvta_generic_to_shared(p); }
DEVINL void mbar_init(uint32_t bar, uint32_t cnt) { asm volatile("mbarrier.init.shared::cta.b64 [%0], %1;" ::"r"(bar), "r"(cnt) : "memory"); }
DEVINL void mbar_expect_tx(uint32_t bar, uint32_t bytes) { asm volatile("mbarrier.arrive.expect_tx.shared::cta.b64 _, [%0], %1;" ::"r"(bar), "r"(bytes) : "memory"); }
DEVINL void mbar_arrive(uint32_t bar) { asm volatile("mbarrier.arrive.shared::cta.b64 _, [%0];" ::"r"(bar) : "memory"); }
DEVINL void mbar_arrive_cluster(uint32_t bar) { asm volatile("mbarrier.arrive.shared::cluster.b64 _, [%0];" ::"r"(bar) : "memory"); }
DEVINL uint32_t mapa(uint32_t a, uint32_t cta) { uint32_t r; asm("mapa.shared::cluster.u32 %0, %1, %2;" : "=r"(r) : "r"(a), "r"(cta)); return r; }
DEVINL void mbar_wait(uint32_t bar, uint32_t parity) {
  asm volatile("{\n.reg .pred p;\n.reg .u32 c;\nmov.u32 c, 0;\n"
               "LW:\nmbarrier.try_wait.parity.shared::cta.b64 p, [%0], %1;\n@p bra LD;\n"
               "add.u32 c, c, 1;\nsetp.lt.u32 p, c, 4194304;\n@p bra LW;\ntrap;\nLD:\n}" ::"r"(bar), "r"(parity) : "memory");
}
DEVINL void mbar_wait_cluster(uint32_t bar, uint32_t parity) {
  asm volatile("{\n.reg .pred p;\n.reg .u32 c;\nmov.u32 c, 0;\n"
               "LW:\nmbarrier.try_wait.parity.acquire.cluster.shared::cta.b64 p, [%0], %1;\n@p bra LD;\n"
               "add.u32 c, c, 1;\nsetp.lt.u32 p, c, 4194304;\n@p bra LW;\ntrap;\nLD:\n}" ::"r"(bar), "r"(parity) : "memory");
}
DEVINL void fence_async_smem() { asm volatile("fence.proxy.async.shared::cta;" ::: "memory"); }
DEVINL void fence_async_global() { asm volatile("fence.proxy.async.global;" ::: "memory"); }
DEVINL void fence_gpu() { asm volatile("fence.acq_rel.gpu;" ::: "memory"); }
template <int ID, int N> DEVINL void named_bar() { asm volatile("bar.sync %0, %1;" ::"n"(ID), "n"(N) : "memory"); }
template <int ID, int N> DEVINL void named_arrive() { asm volatile("bar.arrive %0, %1;" ::"n"(ID), "n"(N) : "memory"); }

DEVINL void tma_2d(uint32_t dst, const CUtensorMap* m, int x, int y, uint32_t bar) {
  asm volatile("cp.async.bulk.tensor.2d.shared::cluster.global.mbarrier::complete_tx::bytes [%0], [%1, {%3, %4}], [%2];"
               ::"r"(dst), "l"(m), "r"(bar), "r"(x), "r"(y) : "memory");
}
DEVINL void tma_2d_hint(uint32_t dst, const CUtensorMap* m, int x, int y, uint32_t bar, uint64_t pol) {
  asm volatile("cp.async.bulk.tensor.2d.shared::cluster.global.mbarrier::complete_tx::bytes.L2::cache_hint [%0], [%1, {%3, %4}], [%2], %5;"
               ::"r"(dst), "l"(m), "r"(bar), "r"(x), "r"(y), "l"(pol) : "memory");
}
DEVINL void tma_3d(uint32_t dst, const CUtensorMap* m, int x, int y, int z, uint32_t bar) {
  asm volatile("cp.async.bulk.tensor.3d.shared::cluster.global.mbarrier::complete_tx::bytes [%0], [%1, {%3, %4, %5}], [%2];"
               ::"r"(dst), "l"(m), "r"(bar), "r"(x), "r"(y), "r"(z) : "memory");
}
DEVINL void tma_store_2d(const CUtensorMap* m, uint32_t src, int x, int y) {
  asm volatile("cp.async.bulk.tensor.2d.global.shared::cta.bulk_group [%0, {%2, %3}], [%1];" ::"l"(m), "r"(src), "r"(x), "r"(y) : "memory");
}
DEVINL void bulk_load(uint32_t dst, const void* src, uint32_t bytes, uint32_t bar) {
  asm volatile("cp.async.bulk.shared::cluster.global.mbarrier::complete_tx::bytes [%0], [%1], %2, [%3];" ::"r"(dst), "l"(src), "r"(bytes), "r"(bar) : "memory");
}
DEVINL void bulk_store(void* dst, uint32_t src, uint32_t bytes) {
  asm volatile("cp.async.bulk.global.shared::cta.bulk_group [%0], [%1], %2;" ::"l"(dst), "r"(src), "r"(bytes) : "memory");
}
DEVINL void pf_bulk(const void* p, uint32_t bytes) { asm volatile("cp.async.bulk.prefetch.L2.global [%0], %1;" ::"l"(p), "r"(bytes) : "memory"); }
DEVINL void pf_bulk_hint(const void* p, uint32_t bytes, uint64_t pol) {
  asm volatile("cp.async.bulk.prefetch.L2.global.L2::cache_hint [%0], %1, %2;" ::"l"(p), "r"(bytes), "l"(pol) : "memory");
}
DEVINL void pf_2d(const CUtensorMap* m, int x, int y) {
  asm volatile("cp.async.bulk.prefetch.tensor.2d.L2.global [%0, {%1, %2}];" ::"l"(m), "r"(x), "r"(y) : "memory");
}
DEVINL void bulk_commit() { asm volatile("cp.async.bulk.commit_group;" ::: "memory"); }
template <int N> DEVINL void bulk_wait() { asm volatile("cp.async.bulk.wait_group %0;" ::"n"(N) : "memory"); }
template <int N> DEVINL void bulk_wait_read() { asm volatile("cp.async.bulk.wait_group.read %0;" ::"n"(N) : "memory"); }
DEVINL void prefetch_tmap(const CUtensorMap* m) { asm volatile("prefetch.tensormap [%0];" ::"l"(m) : "memory"); }

DEVINL void wg_fence() { asm volatile("wgmma.fence.sync.aligned;" ::: "memory"); }
DEVINL void wg_commit() { asm volatile("wgmma.commit_group.sync.aligned;" ::: "memory"); }
template <int N> DEVINL void wg_wait() { asm volatile("wgmma.wait_group.sync.aligned %0;" ::"n"(N) : "memory"); }

DEVINL uint64_t make_desc(uint32_t addr, uint32_t lbo, uint32_t sbo) {
  return (uint64_t)((addr & 0x3FFFF) >> 4) | ((uint64_t)(lbo >> 4) << 16) | ((uint64_t)(sbo >> 4) << 32) | ((uint64_t)1 << 62);
}

#define R8(a, o) "+f"(a[o]), "+f"(a[o + 1]), "+f"(a[o + 2]), "+f"(a[o + 3]), "+f"(a[o + 4]), "+f"(a[o + 5]), "+f"(a[o + 6]), "+f"(a[o + 7])
#define R128(a) R8(a, 0), R8(a, 8), R8(a, 16), R8(a, 24), R8(a, 32), R8(a, 40), R8(a, 48), R8(a, 56), \
                R8(a, 64), R8(a, 72), R8(a, 80), R8(a, 88), R8(a, 96), R8(a, 104), R8(a, 112), R8(a, 120)
template <int TB>
DEVINL void wgmma_n256(float (&d)[128], uint64_t da, uint64_t db, int scale_d) {
  asm volatile(
      "{\n.reg .pred p;\nsetp.ne.b32 p, %130, 0;\n"
      "wgmma.mma_async.sync.aligned.m64n256k16.f32.bf16.bf16 "
      "{%0, %1, %2, %3, %4, %5, %6, %7, %8, %9, %10, %11, %12, %13, %14, %15, "
      "%16, %17, %18, %19, %20, %21, %22, %23, %24, %25, %26, %27, %28, %29, %30, %31, "
      "%32, %33, %34, %35, %36, %37, %38, %39, %40, %41, %42, %43, %44, %45, %46, %47, "
      "%48, %49, %50, %51, %52, %53, %54, %55, %56, %57, %58, %59, %60, %61, %62, %63, "
      "%64, %65, %66, %67, %68, %69, %70, %71, %72, %73, %74, %75, %76, %77, %78, %79, "
      "%80, %81, %82, %83, %84, %85, %86, %87, %88, %89, %90, %91, %92, %93, %94, %95, "
      "%96, %97, %98, %99, %100, %101, %102, %103, %104, %105, %106, %107, %108, %109, %110, %111, "
      "%112, %113, %114, %115, %116, %117, %118, %119, %120, %121, %122, %123, %124, %125, %126, %127}, "
      "%128, %129, p, 1, 1, 0, %131;\n}\n"
      : R128(d)
      : "l"(da), "l"(db), "r"(scale_d), "n"(TB));
}
DEVINL void reg_fence128(float (&a)[128]) {
#pragma unroll
  for (int i = 0; i < 128; i++) asm volatile("" : "+f"(a[i])::"memory");
}

DEVINL uint32_t pack_bf16(float lo, float hi) {
  uint32_t r;
  asm("cvt.rn.bf16x2.f32 %0, %1, %2;" : "=r"(r) : "f"(hi), "f"(lo));
  return r;
}
DEVINL uint32_t fma_bf2(uint32_t a, uint32_t b, uint32_t c) { uint32_t r; asm("fma.rn.bf16x2 %0, %1, %2, %3;" : "=r"(r) : "r"(a), "r"(b), "r"(c)); return r; }
DEVINL uint32_t mul_bf2(uint32_t a, uint32_t b) { uint32_t r; asm("mul.rn.bf16x2 %0, %1, %2;" : "=r"(r) : "r"(a), "r"(b)); return r; }
DEVINL uint32_t add1_bf2(uint32_t a) { return fma_bf2(a, 0x3F803F80u, 0x3F803F80u); }
DEVINL float bf_lo(uint32_t w) { return __uint_as_float(w << 16); }
DEVINL float bf_hi(uint32_t w) { return __uint_as_float(w & 0xFFFF0000u); }
DEVINL float round_bf16(float v) { return __bfloat162float(__float2bfloat16_rn(v)); }
DEVINL float sigmoid_f(float v) { float r; asm("rcp.approx.ftz.f32 %0, %1;" : "=f"(r) : "f"(1.f + __expf(-v))); return r; }
DEVINL float silu_f(float v) { return v * sigmoid_f(v); }
DEVINL void stsm_x4(uint32_t addr, uint32_t r0, uint32_t r1, uint32_t r2, uint32_t r3) {
  asm volatile("stmatrix.sync.aligned.m8n8.x4.shared.b16 [%0], {%1, %2, %3, %4};" ::"r"(addr), "r"(r0), "r"(r1), "r"(r2), "r"(r3) : "memory");
}
DEVINL void ldsm_x4(uint32_t addr, uint32_t& r0, uint32_t& r1, uint32_t& r2, uint32_t& r3) {
  asm volatile("ldmatrix.sync.aligned.m8n8.x4.shared.b16 {%0, %1, %2, %3}, [%4];" : "=r"(r0), "=r"(r1), "=r"(r2), "=r"(r3) : "r"(addr) : "memory");
}
DEVINL void ldsm_x4_t(uint32_t addr, uint32_t& r0, uint32_t& r1, uint32_t& r2, uint32_t& r3) {
  asm volatile("ldmatrix.sync.aligned.m8n8.x4.trans.shared.b16 {%0, %1, %2, %3}, [%4];" : "=r"(r0), "=r"(r1), "=r"(r2), "=r"(r3) : "r"(addr) : "memory");
}
DEVINL void mma_16816(float (&c)[4], uint32_t a0, uint32_t a1, uint32_t a2, uint32_t a3, uint32_t b0, uint32_t b1) {
  asm("mma.sync.aligned.m16n8k16.row.col.f32.bf16.bf16.f32 {%0, %1, %2, %3}, {%4, %5, %6, %7}, {%8, %9}, {%0, %1, %2, %3};"
      : "+f"(c[0]), "+f"(c[1]), "+f"(c[2]), "+f"(c[3]) : "r"(a0), "r"(a1), "r"(a2), "r"(a3), "r"(b0), "r"(b1));
}
DEVINL void mma_1688(float (&c)[4], uint32_t a0, uint32_t a1, uint32_t b0) {
  asm("mma.sync.aligned.m16n8k8.row.col.f32.bf16.bf16.f32 {%0, %1, %2, %3}, {%4, %5}, {%6}, {%0, %1, %2, %3};"
      : "+f"(c[0]), "+f"(c[1]), "+f"(c[2]), "+f"(c[3]) : "r"(a0), "r"(a1), "r"(b0));
}
DEVINL float4 lds128(uint32_t a) { float4 v; asm volatile("ld.shared.v4.f32 {%0, %1, %2, %3}, [%4];" : "=f"(v.x), "=f"(v.y), "=f"(v.z), "=f"(v.w) : "r"(a)); return v; }
DEVINL uint4 lds128u(uint32_t a) { uint4 v; asm volatile("ld.shared.v4.u32 {%0, %1, %2, %3}, [%4];" : "=r"(v.x), "=r"(v.y), "=r"(v.z), "=r"(v.w) : "r"(a)); return v; }
DEVINL float2 lds64(uint32_t a) { float2 v; asm volatile("ld.shared.v2.f32 {%0, %1}, [%2];" : "=f"(v.x), "=f"(v.y) : "r"(a)); return v; }
DEVINL uint2 lds64u(uint32_t a) { uint2 v; asm volatile("ld.shared.v2.u32 {%0, %1}, [%2];" : "=r"(v.x), "=r"(v.y) : "r"(a)); return v; }
DEVINL float lds32(uint32_t a) { float v; asm volatile("ld.shared.f32 %0, [%1];" : "=f"(v) : "r"(a)); return v; }
DEVINL float lds16f(uint32_t a) { uint32_t v; asm volatile("ld.shared.u16 %0, [%1];" : "=r"(v) : "r"(a)); return __uint_as_float(v << 16); }
DEVINL uint32_t lds32u(uint32_t a) { uint32_t v; asm volatile("ld.shared.u32 %0, [%1];" : "=r"(v) : "r"(a)); return v; }
DEVINL void sts128(uint32_t a, float x, float y, float z, float w) { asm volatile("st.shared.v4.f32 [%0], {%1, %2, %3, %4};" ::"r"(a), "f"(x), "f"(y), "f"(z), "f"(w) : "memory"); }
DEVINL void sts128u(uint32_t a, uint32_t x, uint32_t y, uint32_t z, uint32_t w) { asm volatile("st.shared.v4.u32 [%0], {%1, %2, %3, %4};" ::"r"(a), "r"(x), "r"(y), "r"(z), "r"(w) : "memory"); }
DEVINL void sts64(uint32_t a, float x, float y) { asm volatile("st.shared.v2.f32 [%0], {%1, %2};" ::"r"(a), "f"(x), "f"(y) : "memory"); }
DEVINL void sts64u(uint32_t a, uint32_t x, uint32_t y) { asm volatile("st.shared.v2.u32 [%0], {%1, %2};" ::"r"(a), "r"(x), "r"(y) : "memory"); }
DEVINL void sts32(uint32_t a, float v) { asm volatile("st.shared.f32 [%0], %1;" ::"r"(a), "f"(v) : "memory"); }
DEVINL void sts32u(uint32_t a, uint32_t v) { asm volatile("st.shared.u32 [%0], %1;" ::"r"(a), "r"(v) : "memory"); }

DEVINL uint4 ld_msg(const uint4* p) {
  unsigned long long a, b;
  asm volatile("{\n.reg .b128 r;\nld.relaxed.gpu.global.b128 r, [%2];\nmov.b128 {%0, %1}, r;\n}" : "=l"(a), "=l"(b) : "l"(p) : "memory");
  return make_uint4((uint32_t)a, (uint32_t)(a >> 32), (uint32_t)b, (uint32_t)(b >> 32));
}
DEVINL void st_msg(uint4* p, uint32_t x, uint32_t y, uint32_t z, uint32_t w) {
  unsigned long long a = (unsigned long long)x | ((unsigned long long)y << 32), b = (unsigned long long)z | ((unsigned long long)w << 32);
  asm volatile("{\n.reg .b128 r;\nmov.b128 r, {%1, %2};\nst.relaxed.gpu.global.b128 [%0], r;\n}" ::"l"(p), "l"(a), "l"(b) : "memory");
}
DEVINL uint2 ld_msg8(const void* p) {
  unsigned long long a;
  asm volatile("ld.relaxed.gpu.global.b64 %0, [%1];" : "=l"(a) : "l"(p) : "memory");
  return make_uint2((uint32_t)a, (uint32_t)(a >> 32));
}
DEVINL void st_msg8(uint2* p, uint32_t x, uint32_t y) {
  asm volatile("st.relaxed.gpu.global.b64 [%0], %1;" ::"l"(p), "l"((unsigned long long)x | ((unsigned long long)y << 32)) : "memory");
}
DEVINL unsigned ld_rlx(const void* p) { unsigned v; asm volatile("ld.relaxed.gpu.global.u32 %0, [%1];" : "=r"(v) : "l"(p) : "memory"); return v; }
DEVINL void st_rlx(unsigned* p, unsigned v) { asm volatile("st.relaxed.gpu.global.u32 [%0], %1;" ::"l"(p), "r"(v) : "memory"); }
DEVINL void red_add(unsigned* p, unsigned v) { asm volatile("red.relaxed.gpu.global.add.u32 [%0], %1;" ::"l"(p), "r"(v) : "memory"); }
DEVINL void red_add_release(unsigned* p, unsigned v) { asm volatile("red.release.gpu.global.add.u32 [%0], %1;" ::"l"(p), "r"(v) : "memory"); }
DEVINL uint4 ldg_nc(const void* p) {
  uint4 v;
  asm volatile("ld.global.nc.L1::no_allocate.v4.u32 {%0, %1, %2, %3}, [%4];" : "=r"(v.x), "=r"(v.y), "=r"(v.z), "=r"(v.w) : "l"(p));
  return v;
}
DEVINL void stg128(void* p, uint4 v) { asm volatile("st.global.v4.u32 [%0], {%1, %2, %3, %4};" ::"l"(p), "r"(v.x), "r"(v.y), "r"(v.z), "r"(v.w) : "memory"); }
DEVINL uint32_t landed(uint32_t readback, uint32_t zero) { return __reduce_or_sync(~0u, readback & zero); }
DEVINL void delay_until(uint32_t c0, uint32_t cycles) { while ((uint32_t)clock() - c0 < cycles) {} }

#define TRACE(id)
#define TRACE_CLK(id)

DEVINL const char* piece_addr(const Ptrs& pp, int b, int i) {
  if (i >= 20) return pp.wdn + (size_t)b * 57344 + (i - 20) * 8192;
  if ((i >> 2) == 2) return (b < 64 ? pp.wd_re : pp.wd_im) + (size_t)(b & 63) * 32768 + (i & 3) * 8192;
  return (i < 4 || (i >> 2) == 3 ? pp.wg : pp.wu) + (size_t)((i < 8 ? ((i & 3) ^ 2) * 128 : 512 + (i & 3) * 128) + b) * (2 * F_);
}

DEVINL uint32_t dn_box(int i) { return i == 0 ? STAGE + 2 * SLOT : i == 3 ? SPARE : 2 * STAGE + i * SLOT; }
DEVINL int sibling(int m4, int r) {
  return r < 2 ? m4 ^ r : ((m4 & 2) ^ 2) + r - 2;
}

DEVINL uint32_t fkey(float v, int row) {
  const uint32_t u = __float_as_uint(v);
  return (((u & 0x80000000u) ? ~u : (u | 0x80000000u)) & ~2047u) | (uint32_t)(2047 - row);
}
DEVINL int key_row(uint32_t k) { return 2047 - (int)(k & 2047u); }
DEVINL float key_val(uint32_t k) { k = (k & ~2047u) | 1024u; return __uint_as_float((k & 0x80000000u) ? (k & 0x7FFFFFFFu) : ~k); }
DEVINL uint32_t redux_max(uint32_t v) { uint32_t r; asm volatile("redux.sync.max.u32 %0, %1, 0xffffffff;" : "=r"(r) : "r"(v)); return r; }
DEVINL void warp_top2(uint32_t ka, uint32_t kb, uint32_t& k1, uint32_t& k2) {
  k1 = redux_max(ka);
  k2 = redux_max(ka == k1 ? kb : ka);
}
DEVINL int sel_slot(uint2 sel, int n) {
  const int bA = key_row(sel.x) >> 6, bB = key_row(sel.y) >> 6;
  return n ? bB * 2 + (bA == bB ? 1 : 0) : bA * 2;
}

DEVINL void ln_row(uint4 (&w)[4]) {
  float v[32];
#pragma unroll
  for (int i = 0; i < 4; i++) {
    v[8 * i + 0] = bf_lo(w[i].x); v[8 * i + 1] = bf_hi(w[i].x); v[8 * i + 2] = bf_lo(w[i].y); v[8 * i + 3] = bf_hi(w[i].y);
    v[8 * i + 4] = bf_lo(w[i].z); v[8 * i + 5] = bf_hi(w[i].z); v[8 * i + 6] = bf_lo(w[i].w); v[8 * i + 7] = bf_hi(w[i].w);
  }
  float s[4] = {0.f, 0.f, 0.f, 0.f}, q[4] = {0.f, 0.f, 0.f, 0.f};
#pragma unroll
  for (int i = 0; i < 32; i++) { s[i & 3] += v[i]; q[i & 3] = fmaf(v[i], v[i], q[i & 3]); }
  float sum = (s[0] + s[1]) + (s[2] + s[3]), sq = (q[0] + q[1]) + (q[2] + q[3]);
#pragma unroll
  for (int o = 16; o; o >>= 1) { sum += __shfl_xor_sync(~0u, sum, o); sq += __shfl_xor_sync(~0u, sq, o); }
  const float mean = sum * (1.f / D_);
  const float rstd = rsqrtf(fmaxf(fmaf(-mean, mean, sq * (1.f / D_)), 0.f) + 1e-5f), nmr = -mean * rstd;
#pragma unroll
  for (int i = 0; i < 4; i++) {
    w[i].x = pack_bf16(fmaf(v[8 * i], rstd, nmr), fmaf(v[8 * i + 1], rstd, nmr)); w[i].y = pack_bf16(fmaf(v[8 * i + 2], rstd, nmr), fmaf(v[8 * i + 3], rstd, nmr));
    w[i].z = pack_bf16(fmaf(v[8 * i + 4], rstd, nmr), fmaf(v[8 * i + 5], rstd, nmr)); w[i].w = pack_bf16(fmaf(v[8 * i + 6], rstd, nmr), fmaf(v[8 * i + 7], rstd, nmr));
  }
}
DEVINL float sum8(uint4 u) { return ((bf_lo(u.x) + bf_hi(u.x)) + (bf_lo(u.y) + bf_hi(u.y))) + ((bf_lo(u.z) + bf_hi(u.z)) + (bf_lo(u.w) + bf_hi(u.w))); }

template <int R> DEVINL void take_box(uint32_t (&wf)[128], uint32_t box, int lane) {
  const int kr = (lane & 7) + (lane >> 4) * 8;
  const uint32_t base = box + kr * 64, sw = (uint32_t)((kr >> 1) & 3), hb = (uint32_t)((lane >> 3) & 1);
#pragma unroll
  for (int mt = 0; mt < 2; mt++) {
    const uint32_t ad = base + (((mt * 2 + hb) ^ sw) << 4);
#pragma unroll
    for (int ks = 0; ks < 8; ks++) {
      const int o = (ks * 4 + R * 2 + mt) * 4;
      ldsm_x4_t(ad + ks * 1024, wf[o], wf[o + 1], wf[o + 2], wf[o + 3]);
    }
  }
}
DEVINL void gate_up(const Ptrs& pp, uint32_t (&wf)[128], uint32_t sb, uint32_t scr, int ksl, int lane) {
  const uint2 sel = lds64u(sb + SEL_OFF);
  const int gq = lane >> 2, q4 = lane & 3;
  const uint4* src = &pp.mail->rowh[sel_slot(sel, gq & 1) * 128 + ksl * 16 + q4];
  uint4 bf[4];
  int it = 0;
  while (true) {
#pragma unroll
    for (int u = 0; u < 4; u++) bf[u] = ld_msg(src + u * 4);
    if (__all_sync(~0u, bf[0].x != SENT && bf[1].x != SENT && bf[2].x != SENT && bf[3].x != SENT)) break;
    if (++it > SPIN_LIMIT) SPIN_FAIL(0x207);
  }
  if (lane == 0 && ksl == 4) TRACE(20);
  float acc[8][4];
#pragma unroll
  for (int i = 0; i < 8; i++) { acc[i][0] = acc[i][1] = acc[i][2] = acc[i][3] = 0.f; }
#pragma unroll
  for (int u = 0; u < 4; u++)
#pragma unroll
    for (int mt = 0; mt < 4; mt++) {
      const int o = (2 * u * 4 + mt) * 4;
      mma_16816(acc[mt], wf[o], wf[o + 1], wf[o + 2], wf[o + 3], bf[u].x, bf[u].y);
      mma_16816(acc[4 + mt], wf[o + 16], wf[o + 17], wf[o + 18], wf[o + 19], bf[u].z, bf[u].w);
    }
  if (q4 == 0) {
    const uint32_t pb = scr + PART_REL + ksl * 512 + gq * 8;
#pragma unroll
    for (int mt = 0; mt < 4; mt++) {
      sts64(pb + mt * 128, acc[mt][0] + acc[4 + mt][0], acc[mt][1] + acc[4 + mt][1]);
      sts64(pb + mt * 128 + 64, acc[mt][2] + acc[4 + mt][2], acc[mt][3] + acc[4 + mt][3]);
    }
  }
  named_arrive<4, 384>();
}

struct OutTab { float G[8], H[8]; };
DEVINL void out_tab(OutTab& tb, uint4 cb, uint4 sv, uint4 gb) {
  const uint32_t c4[4] = {cb.x, cb.y, cb.z, cb.w}, s4[4] = {sv.x, sv.y, sv.z, sv.w}, g4[4] = {gb.x, gb.y, gb.z, gb.w};
#pragma unroll
  for (int u = 0; u < 4; u++) {
    const uint32_t A = add1_bf2(c4[u]);
    tb.G[2 * u] = bf_lo(g4[u]) * bf_lo(A); tb.G[2 * u + 1] = bf_hi(g4[u]) * bf_hi(A);
    tb.H[2 * u] = bf_lo(g4[u]) * bf_lo(s4[u]); tb.H[2 * u + 1] = bf_hi(g4[u]) * bf_hi(s4[u]);
  }
}
DEVINL void out_row(const OutTab& tb, uint32_t sb, uint32_t scr, int r, int lane, char* dst) {
  const uint4 v = lds128u(sb + XST_OFF + r * 512 + ((lane ^ (r & 7)) << 4));
  const float2 st = lds64(scr + RST_REL + r * 8);
  const uint32_t x4[4] = {v.x, v.y, v.z, v.w};
  uint32_t o[4];
#pragma unroll
  for (int u = 0; u < 4; u++)
    o[u] = pack_bf16(fmaf(fmaf(bf_lo(x4[u]), st.x, st.y), tb.G[2 * u], bf_lo(x4[u]) + tb.H[2 * u]),
                     fmaf(fmaf(bf_hi(x4[u]), st.x, st.y), tb.G[2 * u + 1], bf_hi(x4[u]) + tb.H[2 * u + 1]));
  stg128(dst + (size_t)r * (2 * D_), make_uint4(o[0], o[1], o[2], o[3]));
}

template <int TB, int G0, int G1>
DEVINL void gemm_phase(const Ptrs& pp, float (&acc)[128], uint32_t sb, int cw, bool lag, bool elect, uint32_t rel) {
  const uint32_t bars = sb + BAR_OFF;
#pragma unroll 1
  for (int g = G0; g < G1; g++) {
    const int s = g & 3;
    mbar_wait(bars + (B_FULL + s) * 8, (g >> 2) & 1);
    const bool hold = lag && g == G1 - (TB ? FK_L1 : FK_L2);
    if (hold) {
      wg_wait<0>();
      if (rel) mbar_arrive_cluster(rel + ((g - 1) & 3) * 8);
      mbar_wait(bars + B_STAG * 8, TB ? 0 : 1);
    }
    const uint32_t sa = sb + s * STAGE;
    const uint64_t da = make_desc(sa + cw * 8192, 16, 1024), db = make_desc(sa + SLOT, TB ? 8192 : 16, 1024);
    constexpr int KB = TB ? 128 : 2;
    wg_fence();
    wgmma_n256<TB>(acc, da, db, g > G0);
    wgmma_n256<TB>(acc, da + 2, db + KB, 1);
    wg_commit();
    wg_wait<1>();
    if (rel && g > G0 && !hold) mbar_arrive_cluster(rel + ((g - 1) & 3) * 8);
    wg_fence();
    wgmma_n256<TB>(acc, da + 4, db + 2 * KB, 1);
    wgmma_n256<TB>(acc, da + 6, db + 3 * KB, 1);
    wg_commit();
  }
  if (!lag) {
    wg_wait<1>();
    if (elect) { mbar_arrive(bars + B_STAG * 8); if (!TB) mbar_arrive_cluster(mapa(bars + B_PEER * 8, cw)); }
  }
}
DEVINL void gemm_finish(float (&acc)[128], uint32_t rel) {
  wg_wait<0>();
  reg_fence128(acc);
  if (rel) mbar_arrive_cluster(rel + 24);
}

__global__ void __launch_bounds__(384, 1)
fused_kernel(const Ptrs pp, const __grid_constant__ Maps maps) {
  extern __shared__ __align__(1024) uint8_t smem_raw[];
  const uint32_t c0 = (uint32_t)clock();
  if (threadIdx.x == 0) TRACE(0);
  const uint32_t sb = smem_u32(smem_raw);
  const int tid = threadIdx.x, lane = tid & 31;
  const int warp = __shfl_sync(~0u, tid >> 5, 0);
  const int rb = (int)blockIdx.x + pp.b0;
  const uint32_t bars = sb + BAR_OFF;
  auto BAR = [&](int i) { return bars + i * 8; };

  if (rb < 0) {
    const uint32_t ring = sb + warp * 16384, rbar = sb + MISC + warp * 64;
    const int row0 = FK_G0 * 128 + ((rb + NEXTRA) * 12 + warp) * 2;
    if (lane == 0) {
#pragma unroll 1
      for (int i = 0; i < 4; i++) mbar_init(rbar + i * 8, 1);
      asm volatile("fence.mbarrier_init.release.cluster;" ::: "memory");
#pragma unroll 1
      for (int i = 0; i < FK_XDEPTH; i++) { mbar_expect_tx(rbar + i * 8, 4096); bulk_load(ring + i * 4096, pp.x + (size_t)(row0 + 96 * i) * (2 * D_), 4096, rbar + i * 8); }
    }
    __syncwarp();
    int row = row0;
#pragma unroll 1
    for (int it = 0; row < S_; it++, row += 96) {
      const uint32_t st = ring + (it & 3) * 4096;
      mbar_wait(rbar + (it & 3) * 8, (it >> 2) & 1);
      uint4 w[4], w2[4];
#pragma unroll
      for (int i = 0; i < 4; i++) { w[i] = lds128u(st + lane * 16 + i * 512); w2[i] = lds128u(st + 2048 + lane * 16 + i * 512); }
      ln_row(w);
      uint32_t rbk = 0;
      if (it) {
        if (lane == 0) bulk_wait<0>();
        __syncwarp();
        rbk = ld_rlx(pp.n + (size_t)(row - 96) * (2 * D_) + lane * 128);
      }
      ln_row(w2);
#pragma unroll
      for (int i = 0; i < 4; i++) { sts128u(st + lane * 16 + i * 512, w[i].x, w[i].y, w[i].z, w[i].w); sts128u(st + 2048 + lane * 16 + i * 512, w2[i].x, w2[i].y, w2[i].z, w2[i].w); }
      fence_async_smem();
      const uint32_t z = landed(rbk, pp.zero);
      if (lane == 0) {
        if (it) red_add(&pp.cnt[((row - 96) >> 7) * 32], 2 + z);
        bulk_store(pp.n + (size_t)row * (2 * D_), st, 4096); bulk_commit();
        if (row + 96 * FK_XDEPTH < S_) {
          const int sn = (it + FK_XDEPTH) & 3;
          mbar_expect_tx(rbar + sn * 8, 4096); bulk_load(ring + sn * 4096, pp.x + (size_t)(row + 96 * FK_XDEPTH) * (2 * D_), 4096, rbar + sn * 8);
        }
      }
      __syncwarp();
    }
    if (lane == 0) bulk_wait<0>();
    __syncwarp();
    const uint32_t z = landed(ld_rlx(pp.n + (size_t)(row - 96) * (2 * D_) + lane * 128), pp.zero);
    if (lane == 0) red_add(&pp.cnt[((row - 96) >> 7) * 32], 2 + z);
    return;
  }
  if (warp > 4) asm volatile("barrier.cluster.arrive.relaxed.aligned;" ::: "memory");
  if ((unsigned)(warp - 4) < FK_G0) {
    const int row = (warp - 4) * 128 + rb;
    uint4 w[4];
    if (warp > 4) delay_until(c0, FK_ROW0DLY + (warp - 5) * FK_ROWDLY);
#pragma unroll
    for (int i = 0; i < 4; i++) w[i] = ldg_nc(pp.x + (size_t)row * (2 * D_) + lane * 16 + i * 512);
    if (tid == 128) TRACE(58);
    if (warp == 4) asm volatile("barrier.cluster.arrive.relaxed.aligned;" ::: "memory");
    ln_row(w);
    char* dst = pp.n + (size_t)row * (2 * D_);
#pragma unroll
    for (int i = 0; i < 4; i++) stg128(dst + lane * 16 + i * 512, w[i]);
    if (tid == 128) TRACE(31);
    const uint32_t z = landed(ld_rlx(dst + (lane & 15) * 128), pp.zero);
    if (lane == 0) {
      red_add(&pp.cnt[(warp - 4) * 32], 1 + z);
      if (warp == 4) TRACE(1);
      if (warp == 3 + FK_G0) TRACE(55);
    }
    __syncwarp();
  }
  int m4, t;
  {
    const int c = (rb >> 1) - 2;
    int g = 8, i = c + 2;
    if (c >= 32) { i = ((c - 32) * 37) >> 8; g = c - 32 - 7 * i; g += g >= 2; i += 4; }
    else if (c >= 0) { g = c & 7; i = c >> 3; }
    if (g == 8) { g = 2; i += 6; } else if (i == 8) { i = 4 + g; g = 2; }
    m4 = (g >> 2) * 2 + (i & 1); t = (g & 3) * 4 + (i >> 1);
  }
  const int j = rb & 1, b = t * 8 + m4 * 2 + j;
  const int blk = t * 2 + j;
  const uint32_t scr = sb + 2 * STAGE + j * 8192;
  if (warp >= 10) {
    delay_until(c0, warp == 10 ? FK_WS0DLY : FK_WS1DLY);
    uint32_t dummy;
    asm volatile("ld.global.nc.L1::no_allocate.L2::256B.u32 %0, [%1];" : "=r"(dummy)
                 : "l"((j ? pp.ws_im : pp.ws_re) + (size_t)(t * 128 + m4 * 32 + lane) * (2 * S_) + (warp - 10) * 256));
    sts32u(sb + SEL_OFF, dummy);
  }

  if (warp < 4) {
    uint32_t tag = ld_rlx(&pp.cnt[1]);
    if (lane == 0) {
      if (warp < 2) {
        if (warp == 0) {
          prefetch_tmap(&maps.ws[j]); prefetch_tmap(&maps.n);
          if (sb & 1023) __trap();
#pragma unroll
          for (int i = 0; i < 8; i++) mbar_init(BAR(i), bar_count(i));
        } else {
#pragma unroll
          for (int i = 8; i < 26; i++) mbar_init(BAR(i), bar_count(i));
        }
      } else if (warp == 2) {
#pragma unroll
        for (int i = 26; i < 44; i++) mbar_init(BAR(i), bar_count(i));
      } else {
#pragma unroll
        for (int i = 44; i < B_NUM; i++) mbar_init(BAR(i), bar_count(i));
#pragma unroll
        for (int i = 0; i < 4; i++) mbar_expect_tx(BAR(B_RECV + i), 8192);
      }
      asm volatile("fence.mbarrier_init.release.cluster;" ::: "memory");
    }
    named_bar<6, 128>();
    named_arrive<0, 384>();
    asm volatile("barrier.cluster.arrive.relaxed.aligned;" ::: "memory");
    uint64_t pol_first;
    asm volatile("createpolicy.fractional.L2::evict_first.b64 %0, 1.0;" : "=l"(pol_first));
    const bool moe = b < NMOE;
    uint32_t wf[128];
    auto take = [&](auto R) {
      constexpr int r = decltype(R)::value;
      const uint32_t box = sb + SPARE + warp * 8192;
      if (moe || r == 0) mbar_wait(BAR(B_WB + warp), r);
      if (moe) take_box<r>(wf, box, lane);
      fence_async_smem();
      __syncwarp();
      if (lane == 0) {
        if (r) { mbar_expect_tx(BAR(B_X), 8192); tma_2d(box, &maps.x, m4 * 256 + warp * 64, t * 128 + (1 - j) * 64, BAR(B_X)); }
        else if (moe) { mbar_expect_tx(BAR(B_WB + warp), 8192); tma_2d_hint(box, &maps.wu, b * 32, warp * 128, BAR(B_WB + warp), pol_first); }
      }
      __syncwarp();
    };

    if (warp == 0) {
      auto loadA = [&](int g) {
        mbar_expect_tx(BAR(B_FULL + (g & 3)), STAGE);
        tma_2d_hint(sb + (g & 3) * STAGE, &maps.ws[j], g * 64, t * 128, BAR(B_FULL + (g & 3)), pol_first);
      };
            auto loadB = [&](int g) { tma_3d(sb + (g & 3) * STAGE + SLOT, &maps.n, 0, g * 64, m4 * 4, BAR(B_FULL + (g & 3))); };
      unsigned ready = 0;
      delay_until(c0, FK_ADLY);
#pragma unroll 1
      for (int gi = 0; gi < 2; gi++) {
        if (lane == 0) { loadA(2 * gi); loadA(2 * gi + 1); }
        if (gi == 0) {
          if (lane == 0) TRACE(63);
          asm volatile("add.u32 %0, %0, 1;" : "+r"(tag)::"memory");
        }
        int it = 0;
        while (!((ready >> gi) & 1)) {
          ready = __ballot_sync(~0u, (int)(ld_rlx(&pp.cnt[(lane & 1) * 32]) - tag * 128u) >= 0) & 3;
          if (++it > SPIN_LIMIT) SPIN_FAIL(0x201);
        }
        fence_async_global();
        if (lane == 0) { if (gi == 0) TRACE(2); loadB(2 * gi); loadB(2 * gi + 1); }
        __syncwarp();
      }
      if (lane == 0) { prefetch_tmap(&maps.p); prefetch_tmap(&maps.wd[j]); }
      const unsigned tgt = tag * 128u;
      unsigned pend = ld_rlx(&pp.cnt[2 * 32]);
      const char* pfa = piece_addr(pp, b, lane);
      const uint32_t pfn = (lane >> 2) == 2 || lane >= 20 ? 8192 : 7168;
      auto produce1 = [&](int g0, int g1) {
#pragma unroll 1
        for (int g = g0; g < g1; g++) {
          mbar_wait(BAR(B_EMPTYH + (g & 3)), ((g >> 2) - 1) & 1);
          mbar_wait(BAR(B_EMPTY + (g & 3)), ((g >> 2) - 1) & 1);
          if (!(g & 1)) {
            if ((int)(pend - tgt) < 0) {
              int it = 0;
              while ((int)(ld_rlx(&pp.cnt[(g >> 1) * 32]) - tgt) < 0) { if (++it > SPIN_LIMIT) SPIN_FAIL(0x20c); }
            }
            fence_async_global();
            pend = ld_rlx(&pp.cnt[((g >> 1) + 1) * 32]);
          }
          if (lane == 0) {
            loadA(g); loadB(g);
          }
          if (lane == g - FK_PF0 && lane >= FK_PFSKIP) pf_bulk(pfa, pfn);
          __syncwarp();
        }
      };
      produce1(4, FK_TG);
      take(IntC<0>{});
      produce1(FK_TG, FK_TU);
      take(IntC<1>{});
      produce1(FK_TU, 32);
      int sib = 0, pc = 0;
      auto produce2 = [&](int q0, int q1) {
#pragma unroll 1
        for (int q = q0; q < q1; q++) {
          const int s = q & 3, k0 = sibling(m4, sib) * 256 + pc * 64;
          const uint32_t sa = sb + s * STAGE;
          mbar_wait(BAR(B_EMPTY + s), ((q >> 2) + 1) & 1);
          if (lane == 0) {
            mbar_expect_tx(BAR(B_FULL + s), q < 4 ? 2 * SLOT : STAGE);
            tma_2d(sa + SLOT, &maps.wd[j], k0, m4 * 256, BAR(B_FULL + s));
          }
          __syncwarp();
          if (q >= 4) {
            mbar_wait(BAR(B_RDY - 4 + q), 0);
            if (lane == 0) tma_2d(sa, &maps.p, k0, j * S_ + t * 128, BAR(B_FULL + s));
            if (++sib == 4) { sib = 1; pc++; }
          } else if (++pc == 4) { pc = 0; sib = 1; }
          if (lane == 32 + q - FK_PF0 && lane < 27) pf_bulk(pfa, pfn);
          if (q == FK_MAILQ && lane == 0) pf_bulk(reinterpret_cast<const char*>(pp.mail) + (size_t)b * (MAIL_PER_CTA * 16), MAIL_PER_CTA * 16);
          __syncwarp();
        }
      };
      produce2(0, 16);
      if (moe) {
        mbar_wait(BAR(B_EMPTY + 0), 1);
        if (lane == 0) {
          mbar_expect_tx(BAR(B_GU), 49152);
#pragma unroll 1
          for (int i = 0; i < 3; i++) {
            tma_2d(sb + i * SLOT, &maps.wg, b * 32, 512 + i * 128, BAR(B_GU));
            tma_2d(sb + i * SLOT + 8192, &maps.wu, b * 32, 512 + i * 128, BAR(B_GU));
          }
        }
        mbar_wait(BAR(B_EMPTY + 1), 1);
        if (lane == 0) {
          mbar_expect_tx(BAR(B_GU), 16384);
          tma_2d(sb + STAGE + SLOT, &maps.wg, b * 32, 896, BAR(B_GU));
          tma_2d(sb + STAGE + SLOT + 8192, &maps.wu, b * 32, 896, BAR(B_GU));
        }
#pragma unroll 1
        for (int i = 0; i < 4; i++) {
          if (i == 1) mbar_wait(BAR(B_EMPTY + 2), 1);
          if (i == 3) mbar_wait(BAR(B_XDONE), 0);
          if (i >= FK_DNWIN) mbar_wait(BAR(B_DN + i - FK_DNWIN), 0);
          if (lane == 0) {
            mbar_expect_tx(BAR(B_DN + i), 16384);
            tma_3d(sb + dn_box(i), &maps.wdn, 0, b * 32, i * 4, BAR(B_DN + i));
          }
        }
      }
      __syncwarp();
    } else if (warp == 1) {
      asm volatile("add.u32 %0, %0, 1;" : "+r"(tag)::"memory");
      if (lane == 0) prefetch_tmap(&maps.ps);
      float a0 = 0.f, a1 = 0.f;
      auto rowsum = [&](int g0, int g1) {
        const uint32_t rb = sb + (m4 * 32 + lane) * 128 + ((lane & 7) << 4);
#pragma unroll 1
        for (int g = g0; g < g1; g++) {
          const int s = g & 3;
          mbar_wait(BAR(B_FULL + s), (g >> 2) & 1);
          uint4 u[8];
#pragma unroll
          for (int c = 0; c < 8; c++) u[c] = lds128u((rb ^ (uint32_t)(c << 4)) + s * STAGE);
#pragma unroll
          for (int c = 0; c < 8; c += 2) { a0 += sum8(u[c]); a1 += sum8(u[c + 1]); }
          if (lane == 0) mbar_arrive(BAR(B_EMPTYH + s) + ((__float_as_uint(a0) | __float_as_uint(a1)) & pp.zero));
        }
      };
      rowsum(0, FK_TG - 2);
      take(IntC<0>{});
      rowsum(FK_TG - 2, 28);
      mbar_wait(BAR(B_MODOK), 0);
      a0 += lds32(sb + RS_OFF + 256 + lane * 4);
      __syncwarp();
      uint2* rsp = &pp.mail->rs[(j * 16 + t) * 128 + lane];
      st_msg8(rsp + m4 * 32, __float_as_uint(a0 + a1), tag);
      {
        uint2 m[4]; int it = 0;
        while (true) {
#pragma unroll
          for (int i = 0; i < 4; i++) m[i] = ld_msg8(rsp + 32 * i);
          if (__all_sync(~0u, m[0].y == tag && m[1].y == tag && m[2].y == tag && m[3].y == tag)) break;
          if (++it > SPIN_LIMIT) SPIN_FAIL(0x208);
        }
#pragma unroll
        for (int i = 0; i < 4; i++) sts32u(sb + RS_OFF + (lane + 32 * i) * 4, pack_bf16(__uint_as_float(m[i].x), __uint_as_float(m[i].x)));
      }
      __syncwarp();
      if (lane == 0) { mbar_arrive(BAR(B_T1)); TRACE(11); }
      take(IntC<1>{});
      {
        uint32_t cn = 0;
#pragma unroll 1
        for (int i = 0; i < 16; i++) {
          const int q = i >> 2, half = (i & 2) ? j : 1 - j;
          if (i < 8) mbar_wait(BAR(B_PRDY + (i & 2) + q), 0);
          if (i) delay_until(cn, FK_PPACE);
          cn = (uint32_t)clock();
          if (lane == 0) {
            tma_store_2d(&maps.ps, sb + q * STAGE + half * 8192 + (i & 1) * 4096, m4 * 256 + q * 64, j * S_ + t * 128 + half * 64 + (i & 1) * 32);
            bulk_commit();
            if ((i & 3) == 3) { bulk_wait<0>(); mbar_arrive(BAR(B_PL + q)); mbar_arrive(BAR(B_RDY + q)); }
          }
          __syncwarp();
        }
        if (lane == 0) TRACE(8);
      }
      named_bar<7, 64>();
      delay_until((uint32_t)clock(), FK_E2DLY);
      uint2 m; int it = 0;
      while (true) {
        m = ld_msg8(&pp.mail->cand[b * 32 + lane]);
        if (__all_sync(~0u, m.y != SENT)) break;
        if (++it > SPIN_LIMIT) SPIN_FAIL(0x206);
      }
      uint32_t k1, k2;
      warp_top2(m.x, m.y, k1, k2);
      if (lane == 0) {
        sts64u(sb + SEL_OFF, k1, k2);
        mbar_arrive(BAR(B_SEL));
        TRACE(19);
      }
    } else {
      const int kh = warp - 2;
      const uint32_t reg = sb + SPARE + kh * 16384;
#pragma unroll 1
      for (int i = 0; i < 2; i++) {
        const uint4 cw4 = ldg_nc(pp.c + (kh * 64 + lane + 32 * i) * 16);
        const uint32_t ad = reg + 12288 + (lane + 32 * i) * 32;
        sts128(ad, round_bf16(silu_f(bf_lo(cw4.x))), round_bf16(silu_f(bf_hi(cw4.x))), round_bf16(silu_f(bf_lo(cw4.y))), round_bf16(silu_f(bf_hi(cw4.y))));
        sts128(ad + 16, round_bf16(silu_f(bf_lo(cw4.z))), round_bf16(silu_f(bf_hi(cw4.z))), round_bf16(silu_f(bf_lo(cw4.w))), round_bf16(silu_f(bf_hi(cw4.w))));
        if (kh) { sts128u(sb + T1_OFF + (lane + 32 * i) * 32, SENT, SENT, SENT, SENT); sts128u(sb + T1_OFF + (lane + 32 * i) * 32 + 16, SENT, SENT, SENT, SENT); }
      }
      asm volatile("add.u32 %0, %0, 1;" : "+r"(tag)::"memory");
      fence_async_smem();
      if (lane == 0) prefetch_tmap(&maps.wm);
      {
        float acc[3][8];
        uint32_t sad[3];
#pragma unroll
        for (int a = 0; a < 3; a++) {
          sad[a] = reg + 12288 + ((32 * a + lane) / 6) * 4;
#pragma unroll
          for (int i = 0; i < 8; i++) acc[a][i] = 0.f;
        }
        const char* wpf = pp.wm + (size_t)kh * (512 * 12 * D_) + b * 6144;
        const char* wsrc = (j ? pp.ws_im : pp.ws_re) + (size_t)(t * 128 + m4 * 32 + kh * 16 - 16) * (2 * S_) + 28 * 128 + lane * 16;
        mbar_wait(BAR(B_FULL), 0);
        if (FK_WMPF && lane == 0) pf_bulk(wpf, 6144);
        uint32_t cn = (uint32_t)clock() + FK_PACE0 + (1 - kh) * (FK_PACE / 2);
        auto request = [&](int c) {
          mbar_expect_tx(BAR(B_WM + kh * 2 + (c & 1)), 6144 + ((__float_as_uint(acc[0][0]) | __float_as_uint(acc[1][0]) | __float_as_uint(acc[2][0])) & pp.zero));
          tma_2d_hint(reg + (c & 1) * 6144, &maps.wm, b * 48, kh * 512 + c * 64, BAR(B_WM + kh * 2 + (c & 1)), pol_first);
        };
        uint4 e[4];
#pragma unroll 1
        for (int c = -2; c < 8; c++) {
          while ((int)((uint32_t)clock() - cn) < 0) __nanosleep(40);
          cn += c < 0 ? FK_PACE0 : FK_PACE;
          if (lane == 0) {
            if (FK_WMPF && c < 5) pf_bulk(wpf + (size_t)(c + 3) * (64 * 12 * D_), 6144);
            if (c == FK_RSTEP && kh) {
              char* mb = reinterpret_cast<char*>(pp.mail) + (size_t)b * (MAIL_PER_CTA * 16);
#pragma unroll 1
              for (int o = 0; o < MAIL_PER_CTA * 16; o += 2048) bulk_store(mb + o, sb + T1_OFF, min(2048, MAIL_PER_CTA * 16 - o));
              bulk_commit();
            }
          }
          __syncwarp();
          if (c < 0) {
            if (lane == 0) request(c + 2);
            __syncwarp();
            continue;
          }
          if (c >= 4) {
            const float v0 = sum8(e[0]), v1 = sum8(e[1]), v2 = sum8(e[2]), v3 = sum8(e[3]);
            const bool u4 = lane & 16, u3 = lane & 8;
            const float w0 = (u4 ? v2 : v0) + __shfl_xor_sync(~0u, u4 ? v0 : v2, 16), w1 = (u4 ? v3 : v1) + __shfl_xor_sync(~0u, u4 ? v1 : v3, 16);
            float v = (u3 ? w1 : w0) + __shfl_xor_sync(~0u, u3 ? w0 : w1, 8);
            v += __shfl_xor_sync(~0u, v, 4); v += __shfl_xor_sync(~0u, v, 2); v += __shfl_xor_sync(~0u, v, 1);
            if (!(lane & 7)) sts32(sb + RS_OFF + 256 + (kh * 16 + c * 4 - 16 + (lane >> 3)) * 4, v);
          }
          if (c >= 3 && c < 7) {
#pragma unroll
            for (int i = 0; i < 4; i++) e[i] = ldg_nc(wsrc + (size_t)(c * 4 + 4 + i) * (2 * S_));
          }
          mbar_wait(BAR(B_WM + kh * 2 + (c & 1)), (c >> 1) & 1);
#pragma unroll
          for (int u = 0; u < 12; u++) {
            const uint4 v = lds128u(reg + (c & 1) * 6144 + lane * 16 + u * 512);
            const float sc = lds32(sad[u % 3] + (u / 3) * 64);
            float (&ac)[8] = acc[u % 3];
            ac[0] = fmaf(sc, bf_lo(v.x), ac[0]); ac[1] = fmaf(sc, bf_hi(v.x), ac[1]);
            ac[2] = fmaf(sc, bf_lo(v.y), ac[2]); ac[3] = fmaf(sc, bf_hi(v.y), ac[3]);
            ac[4] = fmaf(sc, bf_lo(v.z), ac[4]); ac[5] = fmaf(sc, bf_hi(v.z), ac[5]);
            ac[6] = fmaf(sc, bf_lo(v.w), ac[6]); ac[7] = fmaf(sc, bf_hi(v.w), ac[7]);
          }
#pragma unroll
          for (int a = 0; a < 3; a++) sad[a] += 256;
          __syncwarp();
          if (lane == 0 && c < 6) request(c + 2);
        }
        __syncwarp();
#pragma unroll
        for (int a = 0; a < 3; a++) {
          sts128(reg + (32 * a + lane) * 32, acc[a][0], acc[a][1], acc[a][2], acc[a][3]);
          sts128(reg + (32 * a + lane) * 32 + 16, acc[a][4], acc[a][5], acc[a][6], acc[a][7]);
        }
        __syncwarp();
        float s0 = 0.f, s1 = 0.f;
#pragma unroll 8
        for (int m = 0; m < 16; m++) { const float2 v = lds64(reg + (lane < 24 ? lane * 8 : 0) + m * 192); s0 += v.x; s1 += v.y; }
        if (kh == 0) sts64(sb + RS_OFF + lane * 8, s0, s1);
        if (lane == 0) TRACE(80 + kh);
        named_bar<5, 64>();
        if (kh == 1) {
          const float2 p = lds64(sb + RS_OFF + lane * 8);
          __syncwarp();
          sts32u(sb + RS_OFF + lane * 4, pack_bf16(s0 + p.x, s1 + p.y));
          fence_async_smem();
          __syncwarp();
          if (lane == 0) {
            bulk_store(pp.mod + b * 24, sb + RS_OFF, 96); bulk_commit(); bulk_wait<0>();
            fence_gpu();
            red_add(&pp.cnt[16 * 32], 1);
            TRACE(9);
          }
          __syncwarp();
        }
      }
      if (kh == 0) {
        if (lane == 0) { mbar_arrive(BAR(B_MODOK)); TRACE(57); }
#pragma unroll 1
        for (int i = 0; i < 4; i++) {
          const int w = i ^ 2;
          if (lane == 0) {
            if (moe) { mbar_expect_tx(BAR(B_WB + w), 8192); tma_2d_hint(sb + SPARE + w * 8192, &maps.wg, b * 32, w * 128, BAR(B_WB + w), pol_first); }
            else mbar_arrive(BAR(B_WB + w));
          }
          __nanosleep(FK_BSLEEP);
        }
        take(IntC<0>{});
        take(IntC<1>{});
        if (lane == 0) TRACE(98);
        const unsigned* flagAddr = &pp.mail->flagP[(((j * 16 + t) * 4 + sibling(m4, 1 + lane % 3)) * 4 + ((lane / 3) & 3)) * 8];
        mbar_wait(BAR(B_PL), 0);
        delay_until((uint32_t)clock(), FK_PFDLY);
        bool done = lane >= 12; int it = 0;
        while (true) {
          if (!done && ld_rlx(flagAddr) == tag) {
            fence_async_global(); mbar_arrive(BAR(B_RDY + lane)); done = true;
          }
          if (__all_sync(~0u, done)) break;
          if (++it > SPIN_LIMIT) SPIN_FAIL(0x202);
        }
        if (lane == 0) TRACE(99);
      } else {
        take(IntC<0>{});
        {
          const unsigned tgt = tag * 128u; int it = 0;
          while ((int)(ld_rlx(&pp.cnt[16 * 32]) - tgt) < 0) { __nanosleep(100); if (++it > SPIN_LIMIT) SPIN_FAIL(0x204); }
        }
        if (lane == 0) { mbar_arrive(BAR(B_MODOK)); TRACE(10); }
        {
          const uint32_t sgn = j ? 0x80008000u : 0u;
          uint32_t sa[4], ca[4]; uint4 sv[4], cv[4], wr[4];
#pragma unroll
          for (int i = 0; i < 4; i++) {
            const int p = lane + 32 * i;
            sa[i] = ld_rlx(pp.mod + m4 * 128 + p); ca[i] = ld_rlx(pp.mod + 512 + m4 * 128 + p);
            sv[i] = ld_msg(reinterpret_cast<const uint4*>(pp.mod + 1536) + p); cv[i] = ld_msg(reinterpret_cast<const uint4*>(pp.mod + 2048) + p);
            wr[i] = ldg_nc(pp.wr + p * 16);
          }
          float c1 = 0.f, c2 = 0.f;
#pragma unroll
          for (int i = 0; i < 4; i++) {
            const int p = lane + 32 * i;
            sts64(sb + T1_OFF + ((p >> 3) * 4 + (p & 3)) * 16 + ((p >> 2) & 1) * 8, __uint_as_float(add1_bf2(ca[i]) ^ sgn), __uint_as_float(sa[i] ^ sgn));
            const uint32_t s4[4] = {sv[i].x, sv[i].y, sv[i].z, sv[i].w}, c4[4] = {cv[i].x, cv[i].y, cv[i].z, cv[i].w}, w4[4] = {wr[i].x, wr[i].y, wr[i].z, wr[i].w};
#pragma unroll
            for (int u = 0; u < 4; u++) {
              const uint32_t A = add1_bf2(c4[u]);
              c1 = fmaf(bf_lo(A), bf_lo(w4[u]), c1); c1 = fmaf(bf_hi(A), bf_hi(w4[u]), c1);
              c2 = fmaf(bf_lo(s4[u]), bf_lo(w4[u]), c2); c2 = fmaf(bf_hi(s4[u]), bf_hi(w4[u]), c2);
            }
          }
#pragma unroll
          for (int o = 16; o; o >>= 1) { c1 += __shfl_xor_sync(~0u, c1, o); c2 += __shfl_xor_sync(~0u, c2, o); }
          __syncwarp();
          if (lane == 0) { sts128(sb + CST_OFF, c1, c2, __uint_as_float(tag), 0.f); mbar_arrive(BAR(B_T1)); TRACE(30); }
        }
        take(IntC<1>{});
        {
          unsigned* fl = &pp.mail->flagP[(((j * 16 + t) * 4 + m4) * 4) * 8];
          const char* prow = pp.P + (size_t)(j * S_ + t * 128 + lane) * (2 * D_) + m4 * 512;
#pragma unroll 1
          for (int pq = 0; pq < 4; pq++) {
            mbar_wait(BAR(B_PL + pq), 0);
            uint32_t rbk[4];
#pragma unroll
            for (int u = 0; u < 4; u++) rbk[u] = ld_rlx(prow + (size_t)u * (32 * 2 * D_) + pq * 128);
            const uint32_t z = landed(rbk[0] | rbk[1] | rbk[2] | rbk[3], pp.zero);
            if (lane == 0) { st_rlx(fl + pq * 8, tag + z); if (pq == 0) TRACE(29); }
          }
        }
        const int G = lane >> 2, q = lane & 3, p0 = m4 * 128 + G * 16 + q;
        uint32_t ga[4], hi[4], lo[4];
#pragma unroll
        for (int u = 0; u < 4; u++) {
          ga[u] = ld_rlx(pp.mod + 1024 + p0 + 4 * u);
          const uint32_t cb = ld_rlx(pp.mod + 2048 + p0 + 4 * u), wr = __ldg(reinterpret_cast<const uint32_t*>(pp.wr) + p0 + 4 * u);
          const float w0 = bf_lo(add1_bf2(cb)) * bf_lo(wr), w1 = bf_hi(add1_bf2(cb)) * bf_hi(wr);
          hi[u] = pack_bf16(w0, w1);
          lo[u] = pack_bf16(w0 - bf_lo(hi[u]), w1 - bf_hi(hi[u]));
        }
        sts128u(sb + GA_OFF + lane * 16, ga[0], ga[1], ga[2], ga[3]);
        sts128u(sb + W_OFF + G * 144 + q * 16, hi[0], hi[1], hi[2], hi[3]);
        sts128u(sb + W_OFF + G * 144 + 64 + q * 16, lo[0], lo[1], lo[2], lo[3]);
        sts32u(sb + W_OFF + G * 144 + 128 + q * 4, 0x3F803F80u);
        __syncwarp();
        if (lane == 0) mbar_arrive(BAR(B_T2));
      }
    }
    mbar_wait(BAR(B_SEL), 0);
    const uint32_t csel = (uint32_t)clock();
    if (moe) gate_up(pp, wf, sb, scr, warp, lane);
    if (warp == 1) {
      const uint2 sel = lds64u(sb + SEL_OFF);
      const int n = (lane >> 3) & 1;
      const int col = (b >> 4) * 128 + (lane & 1) * 64 + ((b >> 2) & 3) * 16 + (b & 3) * 2 + ((lane >> 1) & 1) + (lane >> 4) * 8;
      const int slot = sel_slot(sel, n) * 512, wofs = slot + ((col >> 5) * 4 + ((col >> 1) & 3)) * 4 + ((col >> 3) & 3);
      const uint32_t gbp = ld_rlx(pp.mod + 2560 + (col >> 1));
      uint32_t hp, xp; int it = 0;
      while (true) {
        hp = ld_rlx(reinterpret_cast<const uint32_t*>(pp.mail->rowh) + wofs); xp = ld_rlx(reinterpret_cast<const uint32_t*>(pp.mail->rowx) + slot + (col >> 1));
        if (__all_sync(~0u, hp != SENT && xp != SENT)) break;
        if (++it > SPIN_LIMIT) SPIN_FAIL(0x2ff);
      }
      const float sg = round_bf16(sigmoid_f(round_bf16(key_val(n ? sel.y : sel.x))));
      const int gq = lane >> 2;
      const uint32_t one = (lane & 1) == (gq >> 2) ? ((gq & 1) ? 0x3F800000u : 0x00003F80u) : 0u;
      const uint32_t s0 = (gq & 2) ? 0u : one, s1 = (gq & 2) ? one : 0u;
      const uint4* src = &pp.mail->part[(size_t)b * (NMOE * 2) + lane];
      uint4 m[7];
      delay_until(csel, FK_E4DLY);
      it = 0;
      while (true) {
        bool ok = true;
#pragma unroll
        for (int i = 0; i < 7; i++) m[i] = ld_msg(src + 32 * i);
#pragma unroll
        for (int i = 0; i < 7; i++) ok &= m[i].x != SENT;
        if (__all_sync(~0u, ok)) break;
        if (++it > SPIN_LIMIT) SPIN_FAIL(0x20b);
      }
      if (lane == 0) TRACE(23);
      float c[3][4];
#pragma unroll
      for (int i = 0; i < 3; i++) { c[i][0] = c[i][1] = c[i][2] = c[i][3] = 0.f; }
#pragma unroll
      for (int i = 0; i < 7; i++) mma_16816(c[i % 3], m[i].x, m[i].y, m[i].z, m[i].w, s0, s1);
#pragma unroll
      for (int i = 0; i < 4; i++) c[0][i] += c[1][i] + c[2][i];
      const bool u4 = lane & 16, u3 = lane & 8;
      const float a0 = (u4 ? c[0][2] : c[0][0]) + __shfl_xor_sync(~0u, u4 ? c[0][0] : c[0][2], 16), a1 = (u4 ? c[0][3] : c[0][1]) + __shfl_xor_sync(~0u, u4 ? c[0][1] : c[0][3], 16);
      float y = (u3 ? a1 : a0) + __shfl_xor_sync(~0u, u3 ? a0 : a1, 8);
      y += __shfl_xor_sync(~0u, y, 4);
      const bool odd = col & 1;
      const float upd = round_bf16(round_bf16(y) * sg);
      const float o = fmaf(odd ? bf_hi(gbp) : bf_lo(gbp), (odd ? bf_hi(hp) : bf_lo(hp)) + upd, odd ? bf_hi(xp) : bf_lo(xp));
      if (!(lane & 4)) reinterpret_cast<__nv_bfloat16*>(pp.out)[(size_t)key_row(n ? sel.y : sel.x) * D_ + col] = __float2bfloat16_rn(o);
      if (lane == 0) { TRACE(24); TRACE_CLK(54); if (b == 0) pp.cnt[1] = tag; }
    }
  } else {
    const int cw = (warp - 4) >> 2;
    const int wq = warp & 3;
    const int wtid = tid & 127;
    const int gq = lane >> 2, q4 = lane & 3;
    const bool lag = cw == j;
    const bool elect = wtid == 0;
    const uint32_t rel = wtid < 2 ? mapa(BAR(B_EMPTY), wtid) : 0;

    named_bar<0, 384>();
    asm volatile("barrier.cluster.wait.acquire.aligned;" ::: "memory");

    const int mrow = wq * 16 + (lane & 7) + ((lane >> 3) & 1) * 8;
    {
      float acc[128];
      gemm_phase<1, 0, 32>(pp, acc, sb, cw, lag, elect, rel);
      mbar_wait(BAR(B_T1), 0);
      const uint32_t tad = sb + T1_OFF + q4 * 16;
      uint4 tb[16];
#pragma unroll
      for (int c = 0; c < 4; c++) tb[c] = lds128u(tad + c * 64);
      const uint32_t rs0 = lds32u(sb + RS_OFF + (cw * 64 + wq * 16 + gq) * 4), rs1 = lds32u(sb + RS_OFF + (cw * 64 + wq * 16 + gq + 8) * 4);
      const uint32_t dst = sb + cw * 8192 + mrow * 128, pb = BAR(B_PRDY + (lag ? 2 : 0));
      gemm_finish(acc, rel);
      if (elect) { TRACE(lag ? 5 : 4); if (lag) TRACE_CLK(51); }
#pragma unroll
      for (int i = 0; i < 16; i++) {
        uint32_t r[4];
        const int o = 8 * i;
        r[0] = fma_bf2(pack_bf16(acc[o], acc[o + 1]), tb[i].x, mul_bf2(rs0, tb[i].y));
        r[1] = fma_bf2(pack_bf16(acc[o + 2], acc[o + 3]), tb[i].x, mul_bf2(rs1, tb[i].y));
        r[2] = fma_bf2(pack_bf16(acc[o + 4], acc[o + 5]), tb[i].z, mul_bf2(rs0, tb[i].w));
        r[3] = fma_bf2(pack_bf16(acc[o + 6], acc[o + 7]), tb[i].z, mul_bf2(rs1, tb[i].w));
        if (i < 12) tb[i + 4] = lds128u(tad + (i + 4) * 64);
        stsm_x4(dst + (i >> 2) * STAGE + (uint32_t)(((((2 * i) & 7) + (lane >> 4)) ^ (lane & 7)) << 4), r[0], r[1], r[2], r[3]);
        if (i == 3 || i == 15) {
          fence_async_smem();
          __syncwarp();
          if (lane == 0) mbar_arrive(pb + (i >> 3) * 8);
        }
      }
      mbar_wait(pb + 8, 0);
    }
    if (elect) TRACE(lag ? 7 : 6);
    float acc[128];
    gemm_phase<0, 32, 48>(pp, acc, sb, cw, lag, elect, rel);

    if (!lag) {
      const uint32_t rdst = mapa(sb + STAGE + j * 8192 + wtid * 16, j ^ 1), rbar = mapa(BAR(B_RECV), j ^ 1);
      mbar_wait(BAR(B_T2), 0);
      mbar_wait(BAR(B_X), 0);
      uint32_t xf[16][4]; uint4 ga[8];
      auto fetch = [&](int i) {
        ldsm_x4(sb + SPARE + (i >> 2) * 8192 + mrow * 128 + (uint32_t)(((((2 * i) & 7) + (lane >> 4)) ^ (lane & 7)) << 4), xf[i][0], xf[i][1], xf[i][2], xf[i][3]);
        if (!(i & 1)) ga[i >> 1] = lds128u(sb + GA_OFF + ((i >> 1) * 4 + q4) * 16);
      };
      fetch(0); fetch(1); fetch(2);
      gemm_finish(acc, rel);
      if (elect) { mbar_arrive_cluster(rbar + (B_PEER + 1 - B_RECV) * 8); TRACE(12); }
#pragma unroll
      for (int i = 0; i < 16; i++) {
        const int o = 8 * i;
        const uint32_t g0 = (i & 1) ? ga[i >> 1].z : ga[i >> 1].x, g1 = (i & 1) ? ga[i >> 1].w : ga[i >> 1].y;
        const uint32_t w0 = fma_bf2(g0, pack_bf16(acc[o], acc[o + 1]), xf[i][0]), w1 = fma_bf2(g0, pack_bf16(acc[o + 2], acc[o + 3]), xf[i][1]);
        const uint32_t w2 = fma_bf2(g1, pack_bf16(acc[o + 4], acc[o + 5]), xf[i][2]), w3 = fma_bf2(g1, pack_bf16(acc[o + 6], acc[o + 7]), xf[i][3]);
        if (i == 0) { fetch(3); fetch(4); } else if (i < 12) fetch(i + 4);
        if (i == 0) mbar_wait_cluster(BAR(B_PEER), 0);
        if (i == 8) mbar_wait_cluster(BAR(B_PEER + 1), 0);
        if (i == 12) mbar_wait_cluster(BAR(B_EMPTY + 1), 1);
        asm volatile("st.async.weak.shared::cluster.mbarrier::complete_tx::bytes.v4.b32 [%0], {%1, %2, %3, %4}, [%5];"
                     ::"r"(i < 12 ? rdst + (i >> 2) * STAGE + (i & 3) * 2048 : rdst + (1 - 2 * j) * 8192 + (i & 3) * 2048), "r"(w0), "r"(w1), "r"(w2), "r"(w3),
                       "r"(rbar + (i >> 2) * 8) : "memory");
      }
      __syncwarp();
      if (lane == 0) mbar_arrive(BAR(B_XDONE));
      if (elect) TRACE(13);
      if (b < NMOE) {
        uint32_t wf[128];
        mbar_wait(BAR(B_GU), 0);
        const uint32_t box = sb + (wq < 3 ? wq : 4) * SLOT;
        take_box<0>(wf, box, lane);
        take_box<1>(wf, box + 8192, lane);
        if (elect) TRACE(26);
        mbar_wait(BAR(B_SEL), 0);
        gate_up(pp, wf, sb, scr, 4 + wq, lane);
      }
      OutTab tb;
      {
        const uint4* mp = reinterpret_cast<const uint4*>(pp.mod) + m4 * 32 + lane;
        out_tab(tb, ld_msg(mp + 512), ld_msg(mp + 384), ld_msg(mp + 640));
      }
      mbar_wait(BAR(B_SEL), 0);
      const uint2 sel = lds64u(sb + SEL_OFF), cnd = lds64u(sb + TOP_OFF + 32);
      char* odst = pp.out + (size_t)blk * (64 * 2 * D_) + m4 * 512 + lane * 16;
      const int s1 = key_row(sel.x) - blk * 64, s2 = key_row(sel.y) - blk * 64, c1 = key_row(cnd.x) - blk * 64, c2 = key_row(cnd.y) - blk * 64;
#pragma unroll 1
      for (int r = wq * 16; r < wq * 16 + 16; r++) {
        if (r == s1 || r == s2 || ((r & 15) < FK_OSPLIT && r != c1 && r != c2)) continue;
        const uint32_t cn = (uint32_t)clock();
        out_row(tb, sb, scr, r, lane, odst);
        if ((r & 15) < 15) delay_until(cn, FK_OPACE);
      }
      if (elect) TRACE(28);
    } else {
      mbar_wait(BAR(B_T2), 0);
      uint32_t xa[64];
      float dl[2][4], dq[4][4];
#pragma unroll
      for (int i = 0; i < 4; i++) { dl[0][i] = dl[1][i] = dq[0][i] = dq[1][i] = dq[2][i] = dq[3][i] = 0.f; }
      {
        const uint32_t wad = sb + W_OFF + ((gq & 2) ? 128 : (gq & 1) * 64 + q4 * 16), rsrc = sb + STAGE + (1 - j) * 8192 + wtid * 16;
        uint4 rv[16], wb[8], ga[8];
        auto fetch = [&](int i) {
          if (!(i & 3)) mbar_wait_cluster(BAR(B_RECV + (i >> 2)), 0);
          rv[i] = lds128u(i < 12 ? rsrc + (i >> 2) * STAGE + (i & 3) * 2048 : rsrc + (2 * j - 1) * 8192 + (i & 3) * 2048);
          if (!(i & 1)) ga[i >> 1] = lds128u(sb + GA_OFF + ((i >> 1) * 4 + q4) * 16); else wb[i >> 1] = lds128u(wad + (i >> 1) * 144);
        };
        fetch(0); fetch(1);
        gemm_finish(acc, rel);
        if (elect) { TRACE(14); TRACE_CLK(53); }
#pragma unroll
        for (int i = 0; i < 16; i++) {
          const int o = 8 * i;
          const uint32_t g0 = (i & 1) ? ga[i >> 1].z : ga[i >> 1].x, g1 = (i & 1) ? ga[i >> 1].w : ga[i >> 1].y;
          const uint32_t a0 = fma_bf2(g0, pack_bf16(acc[o], acc[o + 1]), rv[i].x), a1 = fma_bf2(g0, pack_bf16(acc[o + 2], acc[o + 3]), rv[i].y);
          const uint32_t a2 = fma_bf2(g1, pack_bf16(acc[o + 4], acc[o + 5]), rv[i].z), a3 = fma_bf2(g1, pack_bf16(acc[o + 6], acc[o + 7]), rv[i].w);
          if (i < 14) fetch(i + 2);
          xa[4 * i] = a0; xa[4 * i + 1] = a1; xa[4 * i + 2] = a2; xa[4 * i + 3] = a3;
          mma_1688(dq[0], a0, a1, a0); mma_1688(dq[1], a0, a1, a1);
          mma_1688(dq[2], a2, a3, a2); mma_1688(dq[3], a2, a3, a3);
          if (i & 1) {
            mma_16816(dl[0], xa[4 * i - 4], xa[4 * i - 3], xa[4 * i - 2], xa[4 * i - 1], wb[i >> 1].x, wb[i >> 1].y);
            mma_16816(dl[1], a0, a1, a2, a3, wb[i >> 1].z, wb[i >> 1].w);
          }
        }
      }
      const float4 cst = lds128(sb + CST_OFF);
      const uint32_t tag = __float_as_uint(cst.z);
      {
        const bool odd = q4 & 1;
        const float l0 = dl[0][0] + dl[1][0], l1 = dl[0][1] + dl[1][1], l2 = dl[0][2] + dl[1][2], l3 = dl[0][3] + dl[1][3];
        const float mine = odd ? l2 : l0 + l1;
        const float other = __shfl_xor_sync(~0u, odd ? l0 : l2 + l3, 1);
        const int dsrc = (lane & ~3) | (gq >> 1);
        const float qa = __shfl_sync(~0u, (gq & 1) ? dq[0][1] + dq[2][1] : dq[0][0] + dq[2][0], dsrc);
        const float qb = __shfl_sync(~0u, (gq & 1) ? dq[1][3] + dq[3][3] : dq[1][2] + dq[3][2], dsrc);
        if (q4 < 2) st_msg(&pp.mail->stats[(blk * 4 + m4) * 64 + wq * 16 + gq + 8 * q4], __float_as_uint(odd ? mine : other), __float_as_uint(odd ? qb : qa),
                           __float_as_uint(odd ? other : mine), tag);
      }
      const uint32_t cpub = (uint32_t)clock();
      if (elect) TRACE(15);
      const uint4* mp = reinterpret_cast<const uint4*>(pp.mod) + m4 * 32 + lane;
      const uint4 cbv = ld_msg(mp + 512), sbv = ld_msg(mp + 384), gbv = ld_msg(mp + 640);
      mbar_wait(BAR(B_EMPTY + 3), 1);
#pragma unroll
      for (int i = 0; i < 16; i++)
        stsm_x4(sb + XST_OFF + mrow * 512 + (uint32_t)(((2 * i + (lane >> 4)) ^ (lane & 7)) << 4), xa[4 * i], xa[4 * i + 1], xa[4 * i + 2], xa[4 * i + 3]);
      uint32_t k1, k2;
      {
        const uint4* src = &pp.mail->stats[(blk * 4 + (lane >> 4) * 2) * 64 + wq * 16 + (lane & 15)];
        uint4 m0, m1; int it = 0;
        delay_until(cpub, FK_E1DLY);
        while (true) {
          m0 = ld_msg(src); m1 = ld_msg(src + 64);
          if (__all_sync(~0u, m0.w == tag && m1.w == tag)) break;
          if (++it > SPIN_LIMIT) SPIN_FAIL(0x209);
        }
        if (elect) TRACE(16);
        float sa = __uint_as_float(m0.x) + __uint_as_float(m1.x), qa = __uint_as_float(m0.y) + __uint_as_float(m1.y), da = __uint_as_float(m0.z) + __uint_as_float(m1.z);
        sa += __shfl_xor_sync(~0u, sa, 16); qa += __shfl_xor_sync(~0u, qa, 16); da += __shfl_xor_sync(~0u, da, 16);
        const float mean = sa * (1.f / D_);
        const float rstd = rsqrtf(fmaxf(fmaf(-mean, mean, qa * (1.f / D_)), 0.f) + 1e-5f);
        const float rme = fmaf(rstd, fmaf(-mean, cst.x, da), cst.y);
        warp_top2(fkey(rme, blk * 64 + wq * 16 + (lane & 15)), 0u, k1, k2);
        if (lane == 0) sts64u(sb + TOP_OFF + wq * 8, k1, k2);
        if (lane < 16) sts64(scr + RST_REL + (wq * 16 + lane) * 8, rstd, -mean * rstd);
        named_bar<2, 128>();
        const uint2 c = lds64u(sb + TOP_OFF + (lane & 3) * 8);
        warp_top2(c.x, c.y, k1, k2);
        if (wq == 0) {
          st_msg8(&pp.mail->cand[(m4 * 32 + lane) * 32 + blk], k1, k2);
          if (lane == 0) sts64u(sb + TOP_OFF + 32, k1, k2);
          named_arrive<7, 64>();
        }
      }
      if (elect) TRACE(17);
      const int c1 = key_row(k1) - blk * 64, c2 = key_row(k2) - blk * 64;
      if (wq >= 2) {
        const int r = wq == 2 ? c1 : c2;
        const uint4 v = lds128u(sb + XST_OFF + r * 512 + ((lane ^ (r & 7)) << 4));
        const float2 st = lds64(scr + RST_REL + r * 8);
        auto h2 = [&](uint32_t xv, uint32_t cv, uint32_t sv) {
          const uint32_t av = add1_bf2(cv);
          return pack_bf16(fmaf(fmaf(bf_lo(xv), st.x, st.y), bf_lo(av), bf_lo(sv)), fmaf(fmaf(bf_hi(xv), st.x, st.y), bf_hi(av), bf_hi(sv)));
        };
        const uint32_t sc = scr + SCR_REL + wq * 512;
        sts128u(sc + lane * 16, h2(v.x, cbv.x, sbv.x), h2(v.y, cbv.y, sbv.y), h2(v.z, cbv.z, sbv.z), h2(v.w, cbv.w, sbv.w));
        __syncwarp();
        const uint32_t fa = sc + gq * 64 + q4 * 4;
        const int o = (blk * 2 + wq - 2) * 128 + m4 * 32 + lane;
        st_msg(&pp.mail->rowh[o], lds32u(fa), lds32u(fa + 16), lds32u(fa + 32), lds32u(fa + 48));
        st_msg(&pp.mail->rowx[o], v.x, v.y, v.z, v.w);
        if (lane == 0 && wq == 3) TRACE(18);
      }
      {
        OutTab tb;
        out_tab(tb, cbv, sbv, gbv);
        char* odst = pp.out + (size_t)blk * (64 * 2 * D_) + m4 * 512 + lane * 16;
#pragma unroll 1
        for (int r = wq * 16; r < wq * 16 + FK_OSPLIT; r++) {
          if (r == c1 || r == c2) continue;
          const uint32_t cn = (uint32_t)clock();
          out_row(tb, sb, scr, r, lane, odst);
          if ((r & 15) < FK_OSPLIT - 1) delay_until(cn, FK_OPACE);
        }
      }
      if (elect) TRACE(25);
      if (b < NMOE) {
        uint32_t wd[128];
        mbar_wait(BAR(B_DN + wq), 0);
        {
          const int fr = (lane & 7) + (lane >> 4) * 8;
          const uint32_t base = sb + dn_box(wq) + fr * 128;
#pragma unroll
          for (int c = 0; c < 4; c++) {
            const uint32_t ad = base + (((uint32_t)(c * 2 + ((lane >> 3) & 1)) ^ (uint32_t)(lane & 7)) << 4);
#pragma unroll
            for (int gI = 0; gI < 4; gI++)
#pragma unroll
              for (int ks = 0; ks < 2; ks++) {
                const int o = ((gI * 4 + c) * 2 + ks) * 4;
                ldsm_x4_t(ad + gI * 4096 + ks * 2048, wd[o], wd[o + 1], wd[o + 2], wd[o + 3]);
              }
          }
        }
        uint4* dst = &pp.mail->part[((size_t)(wq * 32 + q4 * 4 + (gq >> 1)) * NMOE + b) * 2 + (gq & 1)];
        if (lane == 0 && wq == 3) TRACE(27);
        named_bar<4, 384>();
        if (elect) TRACE(21);
        float g0 = 0.f, g1 = 0.f, u0 = 0.f, u1 = 0.f;
#pragma unroll
        for (int w = 0; w < 8; w++) {
          const float2 gv = lds64(scr + PART_REL + w * 512 + lane * 8), uv = lds64(scr + PART_REL + w * 512 + 256 + lane * 8);
          g0 += gv.x; g1 += gv.y; u0 += uv.x; u1 += uv.y;
        }
        const uint32_t act = pack_bf16(round_bf16(silu_f(round_bf16(g0))) * round_bf16(u0), round_bf16(silu_f(round_bf16(g1))) * round_bf16(u1));
        uint32_t ab[4];
#pragma unroll
        for (int u = 0; u < 4; u++) {
          const uint32_t v0 = __shfl_sync(~0u, act, 8 * u + 2 * q4), v1 = __shfl_sync(~0u, act, 8 * u + 2 * q4 + 1);
          ab[u] = __byte_perm(v0, v1, (gq & 1) ? 0x7632 : 0x5410);
        }
        float c[4][4];
#pragma unroll
        for (int v = 0; v < 4; v++) { c[v][0] = c[v][1] = c[v][2] = c[v][3] = 0.f; }
#pragma unroll
        for (int q = 0; q < 4; q++) {
          const uint32_t mk = (gq >> 1) == q ? ~0u : 0u;
          const uint32_t b0 = ab[0] & mk, b1 = ab[1] & mk, b2 = ab[2] & mk, b3 = ab[3] & mk;
#pragma unroll
          for (int v = 0; v < 4; v++) { const int o = (4 * v + q) * 8; mma_16816(c[v], wd[o], wd[o + 1], wd[o + 2], wd[o + 3], b0, b1); }
#pragma unroll
          for (int v = 0; v < 4; v++) { const int o = (4 * v + q) * 8 + 4; mma_16816(c[v], wd[o], wd[o + 1], wd[o + 2], wd[o + 3], b2, b3); }
        }
#pragma unroll
        for (int u = 0; u < 2; u++)
          st_msg(dst + u * (16 * NMOE * 2), pack_bf16(c[2 * u][0], c[2 * u][1]), pack_bf16(c[2 * u][2], c[2 * u][3]),
                 pack_bf16(c[2 * u + 1][0], c[2 * u + 1][1]), pack_bf16(c[2 * u + 1][2], c[2 * u + 1][3]));
        if (elect) TRACE(22);
      }
    }
  }
}

typedef CUresult (*PFN_encodeTiled)(CUtensorMap*, CUtensorMapDataType, cuuint32_t, void*, const cuuint64_t*, const cuuint64_t*,
                                    const cuuint32_t*, const cuuint32_t*, CUtensorMapInterleave, CUtensorMapSwizzle,
                                    CUtensorMapL2promotion, CUtensorMapFloatOOBfill);

static void map2d(PFN_encodeTiled enc, CUtensorMap* m, const void* p, uint64_t rows, uint64_t cols, uint32_t brows, uint32_t bcols, CUtensorMapSwizzle sw,
                  CUtensorMapL2promotion pr = CU_TENSOR_MAP_L2_PROMOTION_L2_128B) {
  cuuint64_t dims[2] = {cols, rows}; cuuint64_t str[1] = {cols * 2}; cuuint32_t box[2] = {bcols, brows}; cuuint32_t es[2] = {1, 1};
  enc(m, CU_TENSOR_MAP_DATA_TYPE_BFLOAT16, 2, (void*)p, dims, str, box, es, CU_TENSOR_MAP_INTERLEAVE_NONE, sw, pr,
      CU_TENSOR_MAP_FLOAT_OOB_FILL_NONE);
}
static void map3d(PFN_encodeTiled enc, CUtensorMap* m, const void* p, uint64_t rows, uint64_t cols, uint32_t brows, uint32_t bgroups) {
  cuuint64_t dims[3] = {64, rows, cols / 64}; cuuint64_t str[2] = {cols * 2, 128}; cuuint32_t box[3] = {64, brows, bgroups}; cuuint32_t es[3] = {1, 1, 1};
  enc(m, CU_TENSOR_MAP_DATA_TYPE_BFLOAT16, 3, (void*)p, dims, str, box, es, CU_TENSOR_MAP_INTERLEAVE_NONE, CU_TENSOR_MAP_SWIZZLE_128B,
      CU_TENSOR_MAP_L2_PROMOTION_L2_128B, CU_TENSOR_MAP_FLOAT_OOB_FILL_NONE);
}

}

extern "C" void kernel_launch(void* const* d_in, const int* in_sizes, int n_in, void* d_out, int out_size) {
  using namespace fk;
  (void)in_sizes; (void)n_in; (void)out_size;
  static PFN_encodeTiled enc = nullptr;
  static int maxClusters = -1;
  static void *pn = nullptr, *pP = nullptr, *pc = nullptr, *pm = nullptr, *pmod = nullptr;
  if (!enc) {
    void* fn = nullptr; cudaDriverEntryPointQueryResult qr;
    cudaGetDriverEntryPoint("cuTensorMapEncodeTiled", &fn, cudaEnableDefault, &qr);
    enc = (PFN_encodeTiled)fn;
    cudaGetSymbolAddress(&pn, g_n);
    cudaGetSymbolAddress(&pP, g_P);
    cudaGetSymbolAddress(&pc, g_cnt);
    cudaGetSymbolAddress(&pm, g_mail);
    cudaGetSymbolAddress(&pmod, g_mod);
    cudaFuncSetAttribute(fused_kernel, cudaFuncAttributeMaxDynamicSharedMemorySize, SMEM_BYTES);
  }
  Maps maps;
  map2d(enc, &maps.ws[0], d_in[1], S_, S_, 128, 64, CU_TENSOR_MAP_SWIZZLE_128B);
  map2d(enc, &maps.ws[1], d_in[2], S_, S_, 128, 64, CU_TENSOR_MAP_SWIZZLE_128B);
  map3d(enc, &maps.n, pn, S_, D_, 64, 4);
  map2d(enc, &maps.p, pP, 2 * S_, D_, 128, 64, CU_TENSOR_MAP_SWIZZLE_128B);
  map2d(enc, &maps.ps, pP, 2 * S_, D_, 32, 64, CU_TENSOR_MAP_SWIZZLE_128B);
  map2d(enc, &maps.wd[0], d_in[3], D_, D_, 256, 64, CU_TENSOR_MAP_SWIZZLE_128B);
  map2d(enc, &maps.wd[1], d_in[4], D_, D_, 256, 64, CU_TENSOR_MAP_SWIZZLE_128B);
  map2d(enc, &maps.x, d_in[0], S_, D_, 64, 64, CU_TENSOR_MAP_SWIZZLE_128B);
  map2d(enc, &maps.wg, d_in[7], D_, F_, 128, 32, CU_TENSOR_MAP_SWIZZLE_64B);
  map2d(enc, &maps.wu, d_in[8], D_, F_, 128, 32, CU_TENSOR_MAP_SWIZZLE_64B);
  map3d(enc, &maps.wdn, d_in[9], F_, D_, 32, 4);
  map2d(enc, &maps.wm, d_in[11], D_, 6 * D_, 64, 48, CU_TENSOR_MAP_SWIZZLE_NONE);

  cudaLaunchConfig_t cfg = {};
  cfg.gridDim = dim3(NCTA); cfg.blockDim = dim3(384); cfg.dynamicSmemBytes = SMEM_BYTES; cfg.stream = cudaStreamPerThread;
  cudaLaunchAttribute at[1];
  at[0].id = cudaLaunchAttributeClusterDimension; at[0].val.clusterDim.x = 2; at[0].val.clusterDim.y = 1; at[0].val.clusterDim.z = 1;
  cfg.attrs = at; cfg.numAttrs = 1;
  Ptrs pp{(const char*)d_in[0], (char*)pn, (unsigned*)pc, 0, 0, (Mail*)pm, (uint32_t*)pmod, (const char*)d_in[10], (const char*)d_in[1], (const char*)d_in[2],
          (const char*)d_in[3], (const char*)d_in[4], (const char*)d_in[6], (const char*)d_in[7], (const char*)d_in[8], (const char*)d_in[9], (const char*)d_in[11], (const char*)pP, (char*)d_out, nullptr};
  if (maxClusters < 0) {
    cfg.gridDim = dim3(NCTA + NEXTRA);
    if (cudaOccupancyMaxActiveClusters(&maxClusters, fused_kernel, &cfg) != cudaSuccess) maxClusters = 0;
  }
  pp.b0 = -NEXTRA;
  if (maxClusters >= (NCTA + NEXTRA) / 2) {
    cfg.gridDim = dim3(NCTA + NEXTRA);
  } else {
    cfg.gridDim = dim3(NEXTRA);
    cudaLaunchKernelEx(&cfg, fused_kernel, pp, maps);
    cfg.gridDim = dim3(NCTA); pp.b0 = 0;
  }
  cudaLaunchKernelEx(&cfg, fused_kernel, pp, maps);
}
```

```cpp
#include <cuda_runtime.h>
#include <cuda_bf16.h>
#include <cuda.h>
#include <stdint.h>

#define DEVINL __device__ __forceinline__

namespace fk {

constexpr int S_ = 2048, D_ = 1024, F_ = 3584;
constexpr int NCTA = 128;
constexpr int NEXTRA = 4;
constexpr int NMOE = 112;
constexpr int SLOT = 16384;
constexpr int STAGE = 3 * SLOT;
constexpr int SPARE = 4 * STAGE;
constexpr int MISC = SPARE + 32768;
constexpr int SMEM_BYTES = MISC + 3072;
constexpr int BAR_OFF = MISC;
constexpr int CST_OFF = MISC + 480;
constexpr int SEL_OFF = MISC + 496;
constexpr int T1_OFF = MISC + 512;
constexpr int RS_OFF = T1_OFF + 2048;
constexpr int GA_OFF = T1_OFF;
constexpr int W_OFF = GA_OFF + 512;
constexpr int TOP_OFF = GA_OFF + 1792;
constexpr int XST_OFF = 3 * STAGE + SLOT;
constexpr int PART_REL = 0;
constexpr int SCR_REL = 4096;
constexpr int RST_REL = 6144;
enum { B_FULL = 0, B_EMPTY = 4, B_EMPTYH = 8, B_PRDY = 12  , B_PL = 16  , B_WM = 20  , B_LAND = 24  ,
       B_WB = 28  , B_DN = 32  , B_RECV = 36  , B_STAG = 40, B_T1 = 41, B_MODOK = 42, B_PEER = 43  , B_X = 45, B_T2 = 46,
       B_GU = 47, B_XDONE = 48, B_SEL = 49, B_NUM = 50 };

__host__ __device__ constexpr int bar_count(int i) {
  return (i >= B_EMPTY && i < B_EMPTYH) || (i >= B_PRDY && i < B_PL) || i == B_X || i == B_XDONE ? 4
         : (i < B_EMPTY || i == B_T1 || i == B_GU || i == B_MODOK) ? 2 : 1;
}

#define FK_XDEPTH 2
#define FK_G0 8
#define FK_ROW1DLY 700
#define FK_ROW2DLY 1300
#define FK_HINT 0
#define FK_A1EARLY 0
#define FK_XDLY 600
#define FK_ROW4DLY 2600
#define FK_WS0DLY 500
#define FK_WS1DLY 1600
#define FK_ADLY 1800
#define FK_L1 2
#define FK_L2 3
#define FK_PF0 19
#define FK_E1DLY 0
#define FK_E2DLY 300
#define FK_E4DLY 3000
#define FK_MAP 3
#define FK_PPACE 620
#define FK_PACE0 1000
#define FK_WMPF 0
#define FK_TG 28
#define FK_TU 31
#define FK_BSLEEP 250
#define FK_PFSKIP 0
#define FK_DNWIN 1
#define FK_OPACE 150
#define FK_OSPLIT 5
#define FK_SB 0x12
#define FK_WGATE -1
#define FK_RSLEEP 1000
#define FK_PGAP 150
#define FK_GX 10
#define FK_ROW8DLY 3600
#define FK_GSTART 7000
#define FK_PACE 2000
constexpr int SPIN_LIMIT = 1 << 22;
constexpr uint32_t SENT = 0xFFFFFFFFu;

struct Maps {
  CUtensorMap ws[2];
  CUtensorMap n;
  CUtensorMap p;
  CUtensorMap ps;
  CUtensorMap wd[2];
  CUtensorMap x;
  CUtensorMap wg, wu;
  CUtensorMap wdn;
  CUtensorMap wm;
};
template <int V> struct IntC { static constexpr int value = V; };
struct Mail;
struct Ptrs { const char* x; char* n; unsigned* cnt; int b0; uint32_t zero; Mail* mail; uint32_t* mod; const char *c, *ws_re, *ws_im, *wd_re, *wd_im, *wr, *wg, *wu, *wdn, *wm; char* out; unsigned long long* trace; };

__device__ __align__(1024) __nv_bfloat16 g_n[S_ * D_];
__device__ __align__(1024) __nv_bfloat16 g_P[2 * S_ * D_];
__device__ __align__(128) uint32_t g_mod[3 * D_];
__device__ __align__(128) unsigned g_cnt[18 * 32];
struct Mail {
  uint4 stats[32 * 4 * 64];
  uint4 cand[128 * 32 * 2];
  uint4 rowh[64 * 128];
  uint4 rowx[64 * 128];
  uint4 part[128 * NMOE * 2];
  uint2 rs[2 * 16 * 128];
};
static_assert(FK_L2 == 3, "the receive layout assumes a stagger of three k-blocks");
__device__ __align__(1024) Mail g_mail;

#define SPIN_FAIL(what) __trap()
DEVINL uint32_t smem_u32(const void* p) { return (uint32_t)__cvta_generic_to_shared(p); }
DEVINL void mbar_init(uint32_t bar, uint32_t cnt) { asm volatile("mbarrier.init.shared::cta.b64 [%0], %1;" ::"r"(bar), "r"(cnt) : "memory"); }
DEVINL void mbar_expect_tx(uint32_t bar, uint32_t bytes) { asm volatile("mbarrier.arrive.expect_tx.shared::cta.b64 _, [%0], %1;" ::"r"(bar), "r"(bytes) : "memory"); }
DEVINL void mbar_arrive(uint32_t bar) { asm volatile("mbarrier.arrive.shared::cta.b64 _, [%0];" ::"r"(bar) : "memory"); }
DEVINL void mbar_arrive_cluster(uint32_t bar) { asm volatile("mbarrier.arrive.shared::cluster.b64 _, [%0];" ::"r"(bar) : "memory"); }
DEVINL uint32_t mapa(uint32_t a, uint32_t cta) { uint32_t r; asm("mapa.shared::cluster.u32 %0, %1, %2;" : "=r"(r) : "r"(a), "r"(cta)); return r; }
DEVINL void mbar_wait(uint32_t bar, uint32_t parity) {
  asm volatile("{\n.reg .pred p;\n.reg .u32 c;\nmov.u32 c, 0;\n"
               "LW:\nmbarrier.try_wait.parity.shared::cta.b64 p, [%0], %1;\n@p bra LD;\n"
               "add.u32 c, c, 1;\nsetp.lt.u32 p, c, 4194304;\n@p bra LW;\ntrap;\nLD:\n}" ::"r"(bar), "r"(parity) : "memory");
}
DEVINL void fence_async_smem() { asm volatile("fence.proxy.async.shared::cta;" ::: "memory"); }
DEVINL void fence_async_global() { asm volatile("fence.proxy.async.global;" ::: "memory"); }
DEVINL void fence_gpu() { asm volatile("fence.acq_rel.gpu;" ::: "memory"); }
template <int ID, int N> DEVINL void named_bar() { asm volatile("bar.sync %0, %1;" ::"n"(ID), "n"(N) : "memory"); }
template <int ID, int N> DEVINL void named_arrive() { asm volatile("bar.arrive %0, %1;" ::"n"(ID), "n"(N) : "memory"); }

DEVINL void tma_2d(uint32_t dst, const CUtensorMap* m, int x, int y, uint32_t bar) {
  asm volatile("cp.async.bulk.tensor.2d.shared::cluster.global.mbarrier::complete_tx::bytes [%0], [%1, {%3, %4}], [%2];"
               ::"r"(dst), "l"(m), "r"(bar), "r"(x), "r"(y) : "memory");
}
DEVINL void tma_2d_hint(uint32_t dst, const CUtensorMap* m, int x, int y, uint32_t bar, uint64_t pol) {
  asm volatile("cp.async.bulk.tensor.2d.shared::cluster.global.mbarrier::complete_tx::bytes.L2::cache_hint [%0], [%1, {%3, %4}], [%2], %5;"
               ::"r"(dst), "l"(m), "r"(bar), "r"(x), "r"(y), "l"(pol) : "memory");
}
DEVINL void tma_3d(uint32_t dst, const CUtensorMap* m, int x, int y, int z, uint32_t bar) {
  asm volatile("cp.async.bulk.tensor.3d.shared::cluster.global.mbarrier::complete_tx::bytes [%0], [%1, {%3, %4, %5}], [%2];"
               ::"r"(dst), "l"(m), "r"(bar), "r"(x), "r"(y), "r"(z) : "memory");
}
DEVINL void tma_store_2d(const CUtensorMap* m, uint32_t src, int x, int y) {
  asm volatile("cp.async.bulk.tensor.2d.global.shared::cta.bulk_group [%0, {%2, %3}], [%1];" ::"l"(m), "r"(src), "r"(x), "r"(y) : "memory");
}
DEVINL void bulk_load(uint32_t dst, const void* src, uint32_t bytes, uint32_t bar) {
  asm volatile("cp.async.bulk.shared::cluster.global.mbarrier::complete_tx::bytes [%0], [%1], %2, [%3];" ::"r"(dst), "l"(src), "r"(bytes), "r"(bar) : "memory");
}
DEVINL void bulk_store(void* dst, uint32_t src, uint32_t bytes) {
  asm volatile("cp.async.bulk.global.shared::cta.bulk_group [%0], [%1], %2;" ::"l"(dst), "r"(src), "r"(bytes) : "memory");
}
DEVINL void pf_bulk(const void* p, uint32_t bytes) { asm volatile("cp.async.bulk.prefetch.L2.global [%0], %1;" ::"l"(p), "r"(bytes) : "memory"); }
DEVINL void pf_bulk_hint(const void* p, uint32_t bytes, uint64_t pol) {
  asm volatile("cp.async.bulk.prefetch.L2.global.L2::cache_hint [%0], %1, %2;" ::"l"(p), "r"(bytes), "l"(pol) : "memory");
}
DEVINL void pf_2d(const CUtensorMap* m, int x, int y) {
  asm volatile("cp.async.bulk.prefetch.tensor.2d.L2.global [%0, {%1, %2}];" ::"l"(m), "r"(x), "r"(y) : "memory");
}
DEVINL void bulk_commit() { asm volatile("cp.async.bulk.commit_group;" ::: "memory"); }
template <int N> DEVINL void bulk_wait() { asm volatile("cp.async.bulk.wait_group %0;" ::"n"(N) : "memory"); }
template <int N> DEVINL void bulk_wait_read() { asm volatile("cp.async.bulk.wait_group.read %0;" ::"n"(N) : "memory"); }
DEVINL void prefetch_tmap(const CUtensorMap* m) { asm volatile("prefetch.tensormap [%0];" ::"l"(m) : "memory"); }

DEVINL void wg_fence() { asm volatile("wgmma.fence.sync.aligned;" ::: "memory"); }
DEVINL void wg_commit() { asm volatile("wgmma.commit_group.sync.aligned;" ::: "memory"); }
template <int N> DEVINL void wg_wait() { asm volatile("wgmma.wait_group.sync.aligned %0;" ::"n"(N) : "memory"); }

DEVINL uint64_t make_desc(uint32_t addr, uint32_t lbo, uint32_t sbo) {
  return (uint64_t)((addr & 0x3FFFF) >> 4) | ((uint64_t)(lbo >> 4) << 16) | ((uint64_t)(sbo >> 4) << 32) | ((uint64_t)1 << 62);
}

#define R8(a, o) "+f"(a[o]), "+f"(a[o + 1]), "+f"(a[o + 2]), "+f"(a[o + 3]), "+f"(a[o + 4]), "+f"(a[o + 5]), "+f"(a[o + 6]), "+f"(a[o + 7])
#define R128(a) R8(a, 0), R8(a, 8), R8(a, 16), R8(a, 24), R8(a, 32), R8(a, 40), R8(a, 48), R8(a, 56), \
                R8(a, 64), R8(a, 72), R8(a, 80), R8(a, 88), R8(a, 96), R8(a, 104), R8(a, 112), R8(a, 120)
template <int TB>
DEVINL void wgmma_n256(float (&d)[128], uint64_t da, uint64_t db, int scale_d) {
  asm volatile(
      "{\n.reg .pred p;\nsetp.ne.b32 p, %130, 0;\n"
      "wgmma.mma_async.sync.aligned.m64n256k16.f32.bf16.bf16 "
      "{%0, %1, %2, %3, %4, %5, %6, %7, %8, %9, %10, %11, %12, %13, %14, %15, "
      "%16, %17, %18, %19, %20, %21, %22, %23, %24, %25, %26, %27, %28, %29, %30, %31, "
      "%32, %33, %34, %35, %36, %37, %38, %39, %40, %41, %42, %43, %44, %45, %46, %47, "
      "%48, %49, %50, %51, %52, %53, %54, %55, %56, %57, %58, %59, %60, %61, %62, %63, "
      "%64, %65, %66, %67, %68, %69, %70, %71, %72, %73, %74, %75, %76, %77, %78, %79, "
      "%80, %81, %82, %83, %84, %85, %86, %87, %88, %89, %90, %91, %92, %93, %94, %95, "
      "%96, %97, %98, %99, %100, %101, %102, %103, %104, %105, %106, %107, %108, %109, %110, %111, "
      "%112, %113, %114, %115, %116, %117, %118, %119, %120, %121, %122, %123, %124, %125, %126, %127}, "
      "%128, %129, p, 1, 1, 0, %131;\n}\n"
      : R128(d)
      : "l"(da), "l"(db), "r"(scale_d), "n"(TB));
}
DEVINL void reg_fence128(float (&a)[128]) {
#pragma unroll
  for (int i = 0; i < 128; i++) asm volatile("" : "+f"(a[i])::"memory");
}

DEVINL uint32_t pack_bf16(float lo, float hi) {
  uint32_t r;
  asm("cvt.rn.bf16x2.f32 %0, %1, %2;" : "=r"(r) : "f"(hi), "f"(lo));
  return r;
}
DEVINL uint32_t fma_bf2(uint32_t a, uint32_t b, uint32_t c) { uint32_t r; asm("fma.rn.bf16x2 %0, %1, %2, %3;" : "=r"(r) : "r"(a), "r"(b), "r"(c)); return r; }
DEVINL uint32_t mul_bf2(uint32_t a, uint32_t b) { uint32_t r; asm("mul.rn.bf16x2 %0, %1, %2;" : "=r"(r) : "r"(a), "r"(b)); return r; }
DEVINL uint32_t add1_bf2(uint32_t a) { return fma_bf2(a, 0x3F803F80u, 0x3F803F80u); }
DEVINL float bf_lo(uint32_t w) { return __uint_as_float(w << 16); }
DEVINL float bf_hi(uint32_t w) { return __uint_as_float(w & 0xFFFF0000u); }
DEVINL float round_bf16(float v) { return __bfloat162float(__float2bfloat16_rn(v)); }
DEVINL float sigmoid_f(float v) { float r; asm("rcp.approx.ftz.f32 %0, %1;" : "=f"(r) : "f"(1.f + __expf(-v))); return r; }
DEVINL float silu_f(float v) { return v * sigmoid_f(v); }
DEVINL void stsm_x4(uint32_t addr, uint32_t r0, uint32_t r1, uint32_t r2, uint32_t r3) {
  asm volatile("stmatrix.sync.aligned.m8n8.x4.shared.b16 [%0], {%1, %2, %3, %4};" ::"r"(addr), "r"(r0), "r"(r1), "r"(r2), "r"(r3) : "memory");
}
DEVINL void ldsm_x4(uint32_t addr, uint32_t& r0, uint32_t& r1, uint32_t& r2, uint32_t& r3) {
  asm volatile("ldmatrix.sync.aligned.m8n8.x4.shared.b16 {%0, %1, %2, %3}, [%4];" : "=r"(r0), "=r"(r1), "=r"(r2), "=r"(r3) : "r"(addr) : "memory");
}
DEVINL void ldsm_x4_t(uint32_t addr, uint32_t& r0, uint32_t& r1, uint32_t& r2, uint32_t& r3) {
  asm volatile("ldmatrix.sync.aligned.m8n8.x4.trans.shared.b16 {%0, %1, %2, %3}, [%4];" : "=r"(r0), "=r"(r1), "=r"(r2), "=r"(r3) : "r"(addr) : "memory");
}
DEVINL void mma_16816(float (&c)[4], uint32_t a0, uint32_t a1, uint32_t a2, uint32_t a3, uint32_t b0, uint32_t b1) {
  asm("mma.sync.aligned.m16n8k16.row.col.f32.bf16.bf16.f32 {%0, %1, %2, %3}, {%4, %5, %6, %7}, {%8, %9}, {%0, %1, %2, %3};"
      : "+f"(c[0]), "+f"(c[1]), "+f"(c[2]), "+f"(c[3]) : "r"(a0), "r"(a1), "r"(a2), "r"(a3), "r"(b0), "r"(b1));
}
DEVINL void mma_1688(float (&c)[4], uint32_t a0, uint32_t a1, uint32_t b0) {
  asm("mma.sync.aligned.m16n8k8.row.col.f32.bf16.bf16.f32 {%0, %1, %2, %3}, {%4, %5}, {%6}, {%0, %1, %2, %3};"
      : "+f"(c[0]), "+f"(c[1]), "+f"(c[2]), "+f"(c[3]) : "r"(a0), "r"(a1), "r"(b0));
}
DEVINL float4 lds128(uint32_t a) { float4 v; asm volatile("ld.shared.v4.f32 {%0, %1, %2, %3}, [%4];" : "=f"(v.x), "=f"(v.y), "=f"(v.z), "=f"(v.w) : "r"(a)); return v; }
DEVINL uint4 lds128u(uint32_t a) { uint4 v; asm volatile("ld.shared.v4.u32 {%0, %1, %2, %3}, [%4];" : "=r"(v.x), "=r"(v.y), "=r"(v.z), "=r"(v.w) : "r"(a)); return v; }
DEVINL float2 lds64(uint32_t a) { float2 v; asm volatile("ld.shared.v2.f32 {%0, %1}, [%2];" : "=f"(v.x), "=f"(v.y) : "r"(a)); return v; }
DEVINL uint2 lds64u(uint32_t a) { uint2 v; asm volatile("ld.shared.v2.u32 {%0, %1}, [%2];" : "=r"(v.x), "=r"(v.y) : "r"(a)); return v; }
DEVINL float lds32(uint32_t a) { float v; asm volatile("ld.shared.f32 %0, [%1];" : "=f"(v) : "r"(a)); return v; }
DEVINL float lds16f(uint32_t a) { uint32_t v; asm volatile("ld.shared.u16 %0, [%1];" : "=r"(v) : "r"(a)); return __uint_as_float(v << 16); }
DEVINL uint32_t lds32u(uint32_t a) { uint32_t v; asm volatile("ld.shared.u32 %0, [%1];" : "=r"(v) : "r"(a)); return v; }
DEVINL void sts128(uint32_t a, float x, float y, float z, float w) { asm volatile("st.shared.v4.f32 [%0], {%1, %2, %3, %4};" ::"r"(a), "f"(x), "f"(y), "f"(z), "f"(w) : "memory"); }
DEVINL void sts128u(uint32_t a, uint32_t x, uint32_t y, uint32_t z, uint32_t w) { asm volatile("st.shared.v4.u32 [%0], {%1, %2, %3, %4};" ::"r"(a), "r"(x), "r"(y), "r"(z), "r"(w) : "memory"); }
DEVINL void sts64(uint32_t a, float x, float y) { asm volatile("st.shared.v2.f32 [%0], {%1, %2};" ::"r"(a), "f"(x), "f"(y) : "memory"); }
DEVINL void sts64u(uint32_t a, uint32_t x, uint32_t y) { asm volatile("st.shared.v2.u32 [%0], {%1, %2};" ::"r"(a), "r"(x), "r"(y) : "memory"); }
DEVINL void sts32(uint32_t a, float v) { asm volatile("st.shared.f32 [%0], %1;" ::"r"(a), "f"(v) : "memory"); }
DEVINL void sts32u(uint32_t a, uint32_t v) { asm volatile("st.shared.u32 [%0], %1;" ::"r"(a), "r"(v) : "memory"); }

DEVINL uint4 ld_msg(const uint4* p) {
  unsigned long long a, b;
  asm volatile("{\n.reg .b128 r;\nld.relaxed.gpu.global.b128 r, [%2];\nmov.b128 {%0, %1}, r;\n}" : "=l"(a), "=l"(b) : "l"(p) : "memory");
  return make_uint4((uint32_t)a, (uint32_t)(a >> 32), (uint32_t)b, (uint32_t)(b >> 32));
}
DEVINL void st_msg(uint4* p, uint32_t x, uint32_t y, uint32_t z, uint32_t w) {
  unsigned long long a = (unsigned long long)x | ((unsigned long long)y << 32), b = (unsigned long long)z | ((unsigned long long)w << 32);
  asm volatile("{\n.reg .b128 r;\nmov.b128 r, {%1, %2};\nst.relaxed.gpu.global.b128 [%0], r;\n}" ::"l"(p), "l"(a), "l"(b) : "memory");
}
DEVINL uint2 ld_msg8(const void* p) {
  unsigned long long a;
  asm volatile("ld.relaxed.gpu.global.b64 %0, [%1];" : "=l"(a) : "l"(p) : "memory");
  return make_uint2((uint32_t)a, (uint32_t)(a >> 32));
}
DEVINL void st_msg8(uint2* p, uint32_t x, uint32_t y) {
  asm volatile("st.relaxed.gpu.global.b64 [%0], %1;" ::"l"(p), "l"((unsigned long long)x | ((unsigned long long)y << 32)) : "memory");
}
DEVINL unsigned ld_rlx(const void* p) { unsigned v; asm volatile("ld.relaxed.gpu.global.u32 %0, [%1];" : "=r"(v) : "l"(p) : "memory"); return v; }
DEVINL void st_rlx(unsigned* p, unsigned v) { asm volatile("st.relaxed.gpu.global.u32 [%0], %1;" ::"l"(p), "r"(v) : "memory"); }
DEVINL void red_add(unsigned* p, unsigned v) { asm volatile("red.relaxed.gpu.global.add.u32 [%0], %1;" ::"l"(p), "r"(v) : "memory"); }
DEVINL void red_add_release(unsigned* p, unsigned v) { asm volatile("red.release.gpu.global.add.u32 [%0], %1;" ::"l"(p), "r"(v) : "memory"); }
DEVINL uint4 ldg_nc(const void* p) {
  uint4 v;
  asm volatile("ld.global.nc.L1::no_allocate.v4.u32 {%0, %1, %2, %3}, [%4];" : "=r"(v.x), "=r"(v.y), "=r"(v.z), "=r"(v.w) : "l"(p));
  return v;
}
DEVINL uint4 ldg128(const void* p) {
  uint4 v;
  asm volatile("ld.global.v4.u32 {%0, %1, %2, %3}, [%4];" : "=r"(v.x), "=r"(v.y), "=r"(v.z), "=r"(v.w) : "l"(p) : "memory");
  return v;
}
DEVINL void stg128(void* p, uint4 v) { asm volatile("st.global.v4.u32 [%0], {%1, %2, %3, %4};" ::"l"(p), "r"(v.x), "r"(v.y), "r"(v.z), "r"(v.w) : "memory"); }
DEVINL uint32_t landed(uint32_t readback, uint32_t zero) { return __reduce_or_sync(~0u, readback & zero); }
DEVINL void delay_until(uint32_t c0, uint32_t cycles) { while ((uint32_t)clock() - c0 < cycles) {} }

#define TRACE(id)
#define TRACE_CLK(id)

DEVINL const char* piece_addr(const Ptrs& pp, int b, int i) {
  if (i >= 20) return pp.wdn + (size_t)b * 57344 + (i - 20) * 8192;
  if ((i >> 2) == 2) return (b < 64 ? pp.wd_re : pp.wd_im) + (size_t)(b & 63) * 32768 + (i & 3) * 8192;
  return (i < 4 || (i >> 2) == 3 ? pp.wg : pp.wu) + (size_t)((i < 8 ? ((i & 3) ^ 2) * 128 : 512 + (i & 3) * 128) + b) * (2 * F_);
}

DEVINL uint32_t dn_box(int i) { return i == 0 ? STAGE + 2 * SLOT : i == 3 ? SPARE : 2 * STAGE + i * SLOT; }
DEVINL int sibling(int m4, int r) {
  return r < 2 ? m4 ^ r : ((m4 & 2) ^ 2) + r - 2;
}

DEVINL uint32_t fkey(float v, int row) {
  const uint32_t u = __float_as_uint(v);
  return (((u & 0x80000000u) ? ~u : (u | 0x80000000u)) & ~2047u) | (uint32_t)(2047 - row);
}
DEVINL int key_row(uint32_t k) { return 2047 - (int)(k & 2047u); }
DEVINL float key_val(uint32_t k) { k = (k & ~2047u) | 1024u; return __uint_as_float((k & 0x80000000u) ? (k & 0x7FFFFFFFu) : ~k); }
DEVINL uint32_t redux_max(uint32_t v) { uint32_t r; asm volatile("redux.sync.max.u32 %0, %1, 0xffffffff;" : "=r"(r) : "r"(v)); return r; }
DEVINL void warp_top2(uint32_t ka, uint32_t kb, uint32_t& k1, uint32_t& k2) {
  k1 = redux_max(ka);
  k2 = redux_max(ka == k1 ? kb : ka);
}
DEVINL int sel_slot(uint2 sel, int n) {
  const int bA = key_row(sel.x) >> 6, bB = key_row(sel.y) >> 6;
  return n ? bB * 2 + (bA == bB ? 1 : 0) : bA * 2;
}

DEVINL void ln_stats(const uint4 (&w)[4], float (&v)[32], float& rstd, float& nmr) {
#pragma unroll
  for (int i = 0; i < 4; i++) {
    v[8 * i + 0] = bf_lo(w[i].x); v[8 * i + 1] = bf_hi(w[i].x); v[8 * i + 2] = bf_lo(w[i].y); v[8 * i + 3] = bf_hi(w[i].y);
    v[8 * i + 4] = bf_lo(w[i].z); v[8 * i + 5] = bf_hi(w[i].z); v[8 * i + 6] = bf_lo(w[i].w); v[8 * i + 7] = bf_hi(w[i].w);
  }
  float s[4] = {0.f, 0.f, 0.f, 0.f}, q[4] = {0.f, 0.f, 0.f, 0.f};
#pragma unroll
  for (int i = 0; i < 32; i++) { s[i & 3] += v[i]; q[i & 3] = fmaf(v[i], v[i], q[i & 3]); }
  rstd = (s[0] + s[1]) + (s[2] + s[3]); nmr = (q[0] + q[1]) + (q[2] + q[3]);
}
DEVINL void ln_apply(uint4 (&w)[4], const float (&v)[32], float sum, float sq) {
#pragma unroll
  for (int o = 16; o; o >>= 1) { sum += __shfl_xor_sync(~0u, sum, o); sq += __shfl_xor_sync(~0u, sq, o); }
  const float mean = sum * (1.f / D_);
  const float rstd = rsqrtf(fmaxf(fmaf(-mean, mean, sq * (1.f / D_)), 0.f) + 1e-5f), nmr = -mean * rstd;
#pragma unroll
  for (int i = 0; i < 4; i++) {
    w[i].x = pack_bf16(fmaf(v[8 * i], rstd, nmr), fmaf(v[8 * i + 1], rstd, nmr)); w[i].y = pack_bf16(fmaf(v[8 * i + 2], rstd, nmr), fmaf(v[8 * i + 3], rstd, nmr));
    w[i].z = pack_bf16(fmaf(v[8 * i + 4], rstd, nmr), fmaf(v[8 * i + 5], rstd, nmr)); w[i].w = pack_bf16(fmaf(v[8 * i + 6], rstd, nmr), fmaf(v[8 * i + 7], rstd, nmr));
  }
}
DEVINL void ln_row(uint4 (&w)[4]) { float v[32], s, q; ln_stats(w, v, s, q); ln_apply(w, v, s, q); }
DEVINL float sum8(uint4 u) { return ((bf_lo(u.x) + bf_hi(u.x)) + (bf_lo(u.y) + bf_hi(u.y))) + ((bf_lo(u.z) + bf_hi(u.z)) + (bf_lo(u.w) + bf_hi(u.w))); }

template <int R> DEVINL void take_box(uint32_t (&wf)[128], uint32_t box, int lane) {
  const int kr = (lane & 7) + (lane >> 4) * 8;
  const uint32_t base = box + kr * 64, sw = (uint32_t)((kr >> 1) & 3), hb = (uint32_t)((lane >> 3) & 1);
#pragma unroll
  for (int mt = 0; mt < 2; mt++) {
    const uint32_t ad = base + (((mt * 2 + hb) ^ sw) << 4);
#pragma unroll
    for (int ks = 0; ks < 8; ks++) {
      const int o = (ks * 4 + R * 2 + mt) * 4;
      ldsm_x4_t(ad + ks * 1024, wf[o], wf[o + 1], wf[o + 2], wf[o + 3]);
    }
  }
}
DEVINL void gate_up(const Ptrs& pp, uint32_t (&wf)[128], uint32_t sb, uint32_t scr, int ksl, int lane) {
  const uint2 sel = lds64u(sb + SEL_OFF);
  const int gq = lane >> 2, q4 = lane & 3;
  const uint4* src = &pp.mail->rowh[sel_slot(sel, gq & 1) * 128 + ksl * 16 + q4];
  uint4 bf[4];
  int it = 0;
  while (true) {
#pragma unroll
    for (int u = 0; u < 4; u++) bf[u] = ld_msg(src + u * 4);
    if (__all_sync(~0u, bf[0].x != SENT && bf[1].x != SENT && bf[2].x != SENT && bf[3].x != SENT)) break;
    if (++it > SPIN_LIMIT) SPIN_FAIL(0x207);
  }
  if (lane == 0 && ksl == 4) TRACE(20);
  float acc[8][4];
#pragma unroll
  for (int i = 0; i < 8; i++) { acc[i][0] = acc[i][1] = acc[i][2] = acc[i][3] = 0.f; }
#pragma unroll
  for (int u = 0; u < 4; u++)
#pragma unroll
    for (int mt = 0; mt < 4; mt++) {
      const int o = (2 * u * 4 + mt) * 4;
      mma_16816(acc[mt], wf[o], wf[o + 1], wf[o + 2], wf[o + 3], bf[u].x, bf[u].y);
      mma_16816(acc[4 + mt], wf[o + 16], wf[o + 17], wf[o + 18], wf[o + 19], bf[u].z, bf[u].w);
    }
  if (q4 == 0) {
    const uint32_t pb = scr + PART_REL + ksl * 512 + gq * 8;
#pragma unroll
    for (int mt = 0; mt < 4; mt++) {
      sts64(pb + mt * 128, acc[mt][0] + acc[4 + mt][0], acc[mt][1] + acc[4 + mt][1]);
      sts64(pb + mt * 128 + 64, acc[mt][2] + acc[4 + mt][2], acc[mt][3] + acc[4 + mt][3]);
    }
  }
  named_arrive<4, 384>();
}

struct OutTab { float G[8], H[8]; };
DEVINL void out_tab(OutTab& tb, uint4 cb, uint4 sv, uint4 gb) {
  const uint32_t c4[4] = {cb.x, cb.y, cb.z, cb.w}, s4[4] = {sv.x, sv.y, sv.z, sv.w}, g4[4] = {gb.x, gb.y, gb.z, gb.w};
#pragma unroll
  for (int u = 0; u < 4; u++) {
    const uint32_t A = add1_bf2(c4[u]);
    tb.G[2 * u] = bf_lo(g4[u]) * bf_lo(A); tb.G[2 * u + 1] = bf_hi(g4[u]) * bf_hi(A);
    tb.H[2 * u] = bf_lo(g4[u]) * bf_lo(s4[u]); tb.H[2 * u + 1] = bf_hi(g4[u]) * bf_hi(s4[u]);
  }
}
DEVINL void out_row(const OutTab& tb, uint32_t sb, uint32_t scr, int r, int lane, char* dst) {
  const uint4 v = lds128u(sb + XST_OFF + r * 512 + ((lane ^ (r & 7)) << 4));
  const float2 st = lds64(scr + RST_REL + r * 8);
  const uint32_t x4[4] = {v.x, v.y, v.z, v.w};
  uint32_t o[4];
#pragma unroll
  for (int u = 0; u < 4; u++)
    o[u] = pack_bf16(fmaf(fmaf(bf_lo(x4[u]), st.x, st.y), tb.G[2 * u], bf_lo(x4[u]) + tb.H[2 * u]),
                     fmaf(fmaf(bf_hi(x4[u]), st.x, st.y), tb.G[2 * u + 1], bf_hi(x4[u]) + tb.H[2 * u + 1]));
  stg128(dst + (size_t)r * (2 * D_), make_uint4(o[0], o[1], o[2], o[3]));
}

template <int TB, int G0, int G1>
DEVINL void gemm_phase(const Ptrs& pp, float (&acc)[128], uint32_t sb, int cw, bool lag, bool elect, uint32_t rel) {
  const uint32_t bars = sb + BAR_OFF;
#pragma unroll 1
  for (int g = G0; g < G1; g++) {
    const int s = g & 3;
    mbar_wait(bars + (B_FULL + s) * 8, (g >> 2) & 1);
    const bool hold = lag && g == G1 - (TB ? FK_L1 : FK_L2);
    if (hold) {
      wg_wait<0>();
      if (rel) mbar_arrive_cluster(rel + ((g - 1) & 3) * 8);
      mbar_wait(bars + B_STAG * 8, TB ? 0 : 1);
    }
    const uint32_t sa = sb + s * STAGE;
    const uint64_t da = make_desc(sa + cw * 8192, 16, 1024), db = make_desc(sa + SLOT, TB ? 8192 : 16, 1024);
    constexpr int KB = TB ? 128 : 2;
    wg_fence();
    wgmma_n256<TB>(acc, da, db, g > G0);
    wgmma_n256<TB>(acc, da + 2, db + KB, 1);
    wg_commit();
    wg_wait<1>();
    if (rel && g > G0 && !hold) mbar_arrive_cluster(rel + ((g - 1) & 3) * 8);
    wg_fence();
    wgmma_n256<TB>(acc, da + 4, db + 2 * KB, 1);
    wgmma_n256<TB>(acc, da + 6, db + 3 * KB, 1);
    wg_commit();
  }
  if (!lag) {
    wg_wait<1>();
    if (elect) { mbar_arrive(bars + B_STAG * 8); if (!TB) mbar_arrive_cluster(mapa(bars + B_PEER * 8, cw)); }
  }
}
DEVINL void gemm_finish(float (&acc)[128], uint32_t rel) {
  wg_wait<0>();
  reg_fence128(acc);
  if (rel) mbar_arrive_cluster(rel + 24);
}

__global__ void __launch_bounds__(384, 1)
fused_kernel(const Ptrs pp, const __grid_constant__ Maps maps) {
  extern __shared__ __align__(1024) uint8_t smem_raw[];
  const uint32_t c0 = (uint32_t)clock();
  if (threadIdx.x == 0 && blockIdx.x >= NEXTRA) TRACE(0);
  const uint32_t sb = smem_u32(smem_raw);
  const int tid = threadIdx.x, lane = tid & 31;
  const int warp = __shfl_sync(~0u, tid >> 5, 0);
  const int rb = (int)blockIdx.x + pp.b0;
  const uint32_t bars = sb + BAR_OFF;
  auto BAR = [&](int i) { return bars + i * 8; };

  if (rb < 0) {
    const uint32_t ring = sb + warp * 16384, rbar = sb + MISC + warp * 64;
    const int row0 = FK_GX * 128 + ((rb + NEXTRA) * 12 + warp) * 2;
    if (lane == 0) {
#pragma unroll 1
      for (int i = 0; i < 4; i++) mbar_init(rbar + i * 8, 1);
      asm volatile("fence.mbarrier_init.release.cluster;" ::: "memory");
      delay_until(c0, FK_XDLY);
#pragma unroll 1
      for (int i = 0; i < FK_XDEPTH; i++) { mbar_expect_tx(rbar + i * 8, 4096); bulk_load(ring + i * 4096, pp.x + (size_t)(row0 + 96 * i) * (2 * D_), 4096, rbar + i * 8); }
    }
    __syncwarp();
    int row = row0;
#pragma unroll 1
    for (int it = 0; row < S_; it++, row += 96) {
      const uint32_t st = ring + (it & 3) * 4096;
      mbar_wait(rbar + (it & 3) * 8, (it >> 2) & 1);
      uint4 w[4], w2[4];
#pragma unroll
      for (int i = 0; i < 4; i++) { w[i] = lds128u(st + lane * 16 + i * 512); w2[i] = lds128u(st + 2048 + lane * 16 + i * 512); }
      ln_row(w);
      uint32_t rbk = 0;
      if (it) {
        if (lane == 0) bulk_wait<0>();
        __syncwarp();
        rbk = ld_rlx(pp.n + (size_t)(row - 96) * (2 * D_) + lane * 128);
      }
      ln_row(w2);
#pragma unroll
      for (int i = 0; i < 4; i++) { sts128u(st + lane * 16 + i * 512, w[i].x, w[i].y, w[i].z, w[i].w); sts128u(st + 2048 + lane * 16 + i * 512, w2[i].x, w2[i].y, w2[i].z, w2[i].w); }
      fence_async_smem();
      const uint32_t z = landed(rbk, pp.zero);
      if (lane == 0) {
        if (it) red_add(&pp.cnt[((row - 96) >> 7) * 32], 2 + z);
        bulk_store(pp.n + (size_t)row * (2 * D_), st, 4096); bulk_commit();
        if (row + 96 * FK_XDEPTH < S_) {
          const int sn = (it + FK_XDEPTH) & 3;
          mbar_expect_tx(rbar + sn * 8, 4096); bulk_load(ring + sn * 4096, pp.x + (size_t)(row + 96 * FK_XDEPTH) * (2 * D_), 4096, rbar + sn * 8);
        }
      }
      __syncwarp();
    }
    if (lane == 0) bulk_wait<0>();
    __syncwarp();
    const uint32_t z = landed(ld_rlx(pp.n + (size_t)(row - 96) * (2 * D_) + lane * 128), pp.zero);
    if (lane == 0) red_add(&pp.cnt[((row - 96) >> 7) * 32], 2 + z);
    return;
  }
  if (warp > 4) asm volatile("barrier.cluster.arrive.relaxed.aligned;" ::: "memory");
  if ((unsigned)(warp - 4) < FK_G0) {
    const int row = (warp - 4) * 128 + rb;
    uint4 w[4];
    if (warp > 4) delay_until(c0, warp == 5 ? FK_ROW1DLY : warp < 8 ? FK_ROW2DLY : FK_ROW4DLY);
#pragma unroll
    for (int i = 0; i < 4; i++) w[i] = ldg_nc(pp.x + (size_t)row * (2 * D_) + lane * 16 + i * 512);
    if (warp == 4) asm volatile("barrier.cluster.arrive.relaxed.aligned;" ::: "memory");
    const bool first = warp < 6;
    uint32_t pm = 0, par = 0;
    if (first) {
      par = ld_rlx(&pp.cnt[17 * 32]) + 1;
      pm = (lane & 7) ? 0u : 1u;
      const uint32_t z = landed(w[0].x | w[1].x | w[2].x | w[3].x | par, pp.zero);
      if (lane == 0) { red_add(&pp.cnt[(warp - 4) * 32], 1 + z); if (warp == 4) TRACE(1); }
    }
    ln_row(w);
    char* dst = pp.n + (size_t)row * (2 * D_);
#pragma unroll
    for (int i = 0; i < 4; i++) { w[i].x = (w[i].x & ~pm) | (par & pm); stg128(dst + lane * 16 + i * 512, w[i]); }
    if (tid == 128) TRACE(31);
    if (lane == 0 && warp == 3 + FK_G0) TRACE(55);
    if (!first) { if (warp < 8) named_arrive<8, 96>(); else named_arrive<9, 32 * (FK_G0 - 3)>(); }
  }
  int m4, t;
  {
    const int c = (rb >> 1) - 2;
    int g = 8, i = c + 2;
    if (c >= 32) { i = ((c - 32) * 37) >> 8; g = c - 32 - 7 * i; g += g >= 2; i += 4; }
    else if (c >= 0) { g = c & 7; i = c >> 3; }
    if (g == 8) { g = 2; i += 6; } else if (i == 8) { i = 4 + g; g = 2; }
    m4 = (g >> 2) * 2 + (i & 1); t = (g & 3) * 4 + (i >> 1);
  }
  const int j = rb & 1, b = t * 8 + m4 * 2 + j;
  const int blk = t * 2 + j;
  const uint32_t scr = sb + 2 * STAGE + j * 8192;
  if (warp < 4) {
    uint32_t tag = ld_rlx(&pp.cnt[17 * 32]);
    auto ws_touch = [&](int o) {
      uint32_t v;
      asm volatile("ld.global.nc.L1::no_allocate.L2::128B.u32 %0, [%1];" : "=r"(v)
                   : "l"((j ? pp.ws_im : pp.ws_re) + (size_t)(t * 128 + m4 * 32 + lane) * (2 * S_) + o));
      return v;
    };
    uint32_t early = 0;
    if (warp == 1) { delay_until(c0, FK_WS0DLY); early = ws_touch(0); if (lane == 0) TRACE(126); }
    if (warp == 0) early = ld_rlx(&pp.cnt[(lane & 1) * 32]);
    if (lane == 0) {
      if (warp < 2) {
        if (warp == 0) {
          prefetch_tmap(&maps.ws[j]); prefetch_tmap(&maps.n);
          if (sb & 1023) __trap();
#pragma unroll
          for (int i = 0; i < 8; i++) mbar_init(BAR(i), bar_count(i));
        } else {
#pragma unroll
          for (int i = 8; i < 22; i++) mbar_init(BAR(i), bar_count(i));
        }
      } else if (warp == 2) {
#pragma unroll
        for (int i = 22; i < 36; i++) mbar_init(BAR(i), bar_count(i));
      } else {
#pragma unroll
        for (int i = 36; i < B_NUM; i++) mbar_init(BAR(i), bar_count(i));
#pragma unroll
        for (int i = 0; i < 4; i++) mbar_expect_tx(BAR(B_RECV + i), 8192);
      }
      asm volatile("fence.mbarrier_init.release.cluster;" ::: "memory");
    }
    named_bar<6, 128>();
    named_arrive<0, 256>(); named_arrive<3, 256>();
    asm volatile("barrier.cluster.arrive.relaxed.aligned;" ::: "memory");
    uint64_t pol_first;
    asm volatile("createpolicy.fractional.L2::evict_first.b64 %0, 1.0;" : "=l"(pol_first));
    const bool moe = b < NMOE;
    uint32_t wf[128];
    auto take = [&](auto R) {
      constexpr int r = decltype(R)::value;
      const uint32_t box = sb + SPARE + warp * 8192;
      if (moe || r == 0) mbar_wait(BAR(B_WB + warp), r);
      if (moe) take_box<r>(wf, box, lane);
      fence_async_smem();
      __syncwarp();
      if (lane == 0) {
        if (r) { mbar_expect_tx(BAR(B_X), 8192); tma_2d(box, &maps.x, m4 * 256 + warp * 64, t * 128 + (1 - j) * 64, BAR(B_X)); }
        else if (moe) { mbar_expect_tx(BAR(B_WB + warp), 8192); tma_2d_hint(box, &maps.wu, b * 32, warp * 128, BAR(B_WB + warp), pol_first); }
      }
      __syncwarp();
    };

    if (warp == 0) {
      auto loadA = [&](int g) {
        mbar_expect_tx(BAR(B_FULL + (g & 3)), SLOT);
        tma_2d_hint(sb + (g & 3) * STAGE, &maps.ws[j], g * 64, t * 128, BAR(B_FULL + (g & 3)), pol_first);
      };
      auto loadB = [&](int g, int bar) { mbar_expect_tx(BAR(bar + (g & 3)), 2 * SLOT); tma_3d(sb + (g & 3) * STAGE + SLOT, &maps.n, 0, g * 64, m4 * 4, BAR(bar + (g & 3))); };
      delay_until(c0, FK_ADLY);
      if (lane == 0) { loadA(0); if (FK_A1EARLY) loadA(1); TRACE(63); }
      asm volatile("add.u32 %0, %0, 1;" : "+r"(tag)::"memory");
#pragma unroll 1
      for (int gi = 0; gi < 2; gi++) {
        int it = 0;
        const unsigned* cp = &pp.cnt[(lane & 1) * 32];
        while (true) {
          delay_until((uint32_t)clock(), FK_PGAP);
          const uint32_t e2 = ld_rlx(cp);
          if ((__ballot_sync(~0u, (int)(early - tag * 128u) >= 0) >> gi) & 1) break;
          delay_until((uint32_t)clock(), FK_PGAP);
          early = ld_rlx(cp);
          if ((__ballot_sync(~0u, (int)(e2 - tag * 128u) >= 0) >> gi) & 1) break;
          if (++it > SPIN_LIMIT) SPIN_FAIL(0x201);
        }
        if (lane == 0) {
          if (gi == 0) TRACE(2);
          loadB(2 * gi, B_LAND);
          if (gi) loadA(2);
          if (gi || !FK_A1EARLY) loadA(2 * gi + 1);
          loadB(2 * gi + 1, B_LAND);
        }
        __syncwarp();
      }
      if (lane == 0) { prefetch_tmap(&maps.p); prefetch_tmap(&maps.wd[j]); }
      const unsigned tgt = tag * 128u;
      unsigned pend = ld_rlx(&pp.cnt[2 * 32]);
      const char* pfa = piece_addr(pp, b, lane);
      const uint32_t pfn = (lane >> 2) == 2 || lane >= 20 ? 8192 : 7168;
      auto produce1 = [&](int g0, int g1) {
#pragma unroll 1
        for (int g = g0; g < g1; g++) {
          mbar_wait(BAR(B_EMPTYH + (g & 3)), ((g >> 2) - 1) & 1);
          mbar_wait(BAR(B_EMPTY + (g & 3)), ((g >> 2) - 1) & 1);
          if (!(g & 1)) {
            if ((int)(pend - tgt) < 0) {
              int it = 0;
              while ((int)(ld_rlx(&pp.cnt[(g >> 1) * 32]) - tgt) < 0) { if (++it > SPIN_LIMIT) SPIN_FAIL(0x20c); }
            }
            fence_async_global();
            pend = ld_rlx(&pp.cnt[((g >> 1) + 1) * 32]);
          }
          if (lane == 0) {
            loadA(g); loadB(g, B_FULL);
          }
          if (lane == g - FK_PF0 && lane >= FK_PFSKIP) pf_bulk(pfa, pfn);
          __syncwarp();
        }
      };
      produce1(4, FK_TG);
      take(IntC<0>{});
      produce1(FK_TG, FK_TU);
      take(IntC<1>{});
      produce1(FK_TU, 32);
      int sib = 0, pc = 0;
      auto produce2 = [&](int q0, int q1) {
#pragma unroll 1
        for (int q = q0; q < q1; q++) {
          const int s = q & 3, k0 = sibling(m4, sib) * 256 + pc * 64;
          const uint32_t sa = sb + s * STAGE;
          mbar_wait(BAR(B_EMPTY + s), ((q >> 2) + 1) & 1);
          if (lane == 0) {
            mbar_expect_tx(BAR(B_FULL + s), 2 * SLOT);
            tma_2d(sa + SLOT, &maps.wd[j], k0, m4 * 256, BAR(B_FULL + s));
            if (q < 4) mbar_arrive(BAR(B_FULL + s));
          }
          __syncwarp();
          if (q >= 4) {
            mbar_wait(BAR(B_PL + s), 0);
            if (lane == 0) { mbar_expect_tx(BAR(B_LAND + s), SLOT); tma_2d(sa, &maps.p, k0, j * S_ + t * 128, BAR(B_LAND + s)); }
            if (++sib == 4) { sib = 1; pc++; }
          } else if (++pc == 4) { pc = 0; sib = 1; }
          if (lane == 32 + q - FK_PF0 && lane < 27) pf_bulk(pfa, pfn);
          __syncwarp();
        }
      };
      produce2(0, 16);
      if (moe) {
        mbar_wait(BAR(B_EMPTY + 0), 1);
        if (lane == 0) {
          mbar_expect_tx(BAR(B_GU), 49152);
#pragma unroll 1
          for (int i = 0; i < 3; i++) {
            tma_2d(sb + i * SLOT, &maps.wg, b * 32, 512 + i * 128, BAR(B_GU));
            tma_2d(sb + i * SLOT + 8192, &maps.wu, b * 32, 512 + i * 128, BAR(B_GU));
          }
        }
        mbar_wait(BAR(B_EMPTY + 1), 1);
        if (FK_WGATE >= 0) mbar_wait(BAR(B_RECV + FK_WGATE), 0);
        if (lane == 0) {
          mbar_expect_tx(BAR(B_GU), 16384);
          tma_2d(sb + STAGE + SLOT, &maps.wg, b * 32, 896, BAR(B_GU));
          tma_2d(sb + STAGE + SLOT + 8192, &maps.wu, b * 32, 896, BAR(B_GU));
        }
#pragma unroll 1
        for (int i = 0; i < 4; i++) {
          if (i == 1) mbar_wait(BAR(B_EMPTY + 2), 1);
          if (i == 3) mbar_wait(BAR(B_XDONE), 0);
          if (i >= FK_DNWIN) mbar_wait(BAR(B_DN + i - FK_DNWIN), 0);
          if (lane == 0) {
            mbar_expect_tx(BAR(B_DN + i), 16384);
            tma_3d(sb + dn_box(i), &maps.wdn, 0, b * 32, i * 4, BAR(B_DN + i));
          }
        }
      }
      __syncwarp();
    } else if (warp == 1) {
      asm volatile("add.u32 %0, %0, 1;" : "+r"(tag)::"memory");
      if (lane == 0) prefetch_tmap(&maps.ps);
      delay_until(c0, FK_WS1DLY);
      float a0 = __uint_as_float(early & pp.zero), a1 = __uint_as_float(ws_touch(128) & pp.zero);
      auto rowsum = [&](int g0, int g1) {
        const uint32_t rb = sb + (m4 * 32 + lane) * 128 + ((lane & 7) << 4);
#pragma unroll 1
        for (int g = g0; g < g1; g++) {
          const int s = g & 3;
          mbar_wait(BAR(B_FULL + s), (g >> 2) & 1);
          uint4 u[8];
#pragma unroll
          for (int c = 0; c < 8; c++) u[c] = lds128u((rb ^ (uint32_t)(c << 4)) + s * STAGE);
#pragma unroll
          for (int c = 0; c < 8; c += 2) { a0 += sum8(u[c]); a1 += sum8(u[c + 1]); }
          if (lane == 0) mbar_arrive(BAR(B_EMPTYH + s) + ((__float_as_uint(a0) | __float_as_uint(a1)) & pp.zero));
        }
      };
      rowsum(0, FK_TG - 2);
      take(IntC<0>{});
      rowsum(FK_TG - 2, 28);
      mbar_wait(BAR(B_MODOK), 0);
      a0 += lds32(sb + RS_OFF + 256 + lane * 4);
      __syncwarp();
      uint2* rsp = &pp.mail->rs[(j * 16 + t) * 128 + lane];
      st_msg8(rsp + m4 * 32, __float_as_uint(a0 + a1), tag);
      {
        uint2 m[4]; int it = 0;
        while (true) {
#pragma unroll
          for (int i = 0; i < 4; i++) m[i] = ld_msg8(rsp + 32 * i);
          if (__all_sync(~0u, m[0].y == tag && m[1].y == tag && m[2].y == tag && m[3].y == tag)) break;
          if (++it > SPIN_LIMIT) SPIN_FAIL(0x208);
        }
#pragma unroll
        for (int i = 0; i < 4; i++) sts32u(sb + RS_OFF + (lane + 32 * i) * 4, pack_bf16(__uint_as_float(m[i].x), __uint_as_float(m[i].x)));
      }
      __syncwarp();
      if (lane == 0) { mbar_arrive(BAR(B_T1)); TRACE(11); }
      take(IntC<1>{});
      {
        uint32_t cn = 0;
#pragma unroll 1
        for (int i = 0; i < 8; i++) {
          const int q = i >> 1, half = (i & 1) ? j : 1 - j;
          if (i < 4) mbar_wait(BAR(B_PRDY + (i & 1) * 2 + q), 0);
          if (i) delay_until(cn, FK_PPACE);
          cn = (uint32_t)clock();
          if (lane == 0) {
            tma_store_2d(&maps.ps, sb + q * STAGE + half * 8192, m4 * 256 + q * 64, j * S_ + t * 128 + half * 64);
            bulk_commit();
            if (i && !(i & 1)) { bulk_wait_read<1>(); mbar_arrive(BAR(B_PL + q - 1)); }
          }
          __syncwarp();
        }
        if (lane == 0) { bulk_wait_read<0>(); mbar_arrive(BAR(B_PL + 3)); }
        if (lane == 0) TRACE(8);
      }
      named_bar<7, 64>();
      delay_until((uint32_t)clock(), FK_E2DLY);
      uint4 m; int it = 0;
      while (true) {
        m = ld_msg(&pp.mail->cand[(b * 32 + lane) * 2]);
        if (__all_sync(~0u, m.z == tag)) break;
        if (++it > SPIN_LIMIT) SPIN_FAIL(0x206);
      }
      uint32_t k1, k2;
      warp_top2(m.x, m.y, k1, k2);
      if (lane == 0) {
        sts64u(sb + SEL_OFF, k1, k2);
        mbar_arrive(BAR(B_SEL));
        TRACE(19);
      }
    } else {
      const int kh = warp - 2;
      const uint32_t reg = sb + SPARE + kh * 16384;
      const uint4 cw0 = ldg_nc(pp.c + (kh * 64 + lane) * 16), cw1 = ldg_nc(pp.c + (kh * 64 + lane + 32) * 16);
#pragma unroll 1
      for (int i = 0; i < 2; i++) {
        const uint4 cw4 = i ? cw1 : cw0;
        const uint32_t ad = reg + 12288 + (lane + 32 * i) * 32;
        sts128(ad, round_bf16(silu_f(bf_lo(cw4.x))), round_bf16(silu_f(bf_hi(cw4.x))), round_bf16(silu_f(bf_lo(cw4.y))), round_bf16(silu_f(bf_hi(cw4.y))));
        sts128(ad + 16, round_bf16(silu_f(bf_lo(cw4.z))), round_bf16(silu_f(bf_hi(cw4.z))), round_bf16(silu_f(bf_lo(cw4.w))), round_bf16(silu_f(bf_hi(cw4.w))));
      }
      asm volatile("add.u32 %0, %0, 1;" : "+r"(tag)::"memory");
      if (lane == 0) prefetch_tmap(&maps.wm);
      unsigned ph = 0;
      if (kh == 0) {
#pragma unroll 1
        for (int s = 0; s < 4; s++) {
          const uint32_t ra = sb + s * STAGE + SLOT + lane * 128 + ((lane & 7) << 4);
          int it = 0;
          while (true) {
            mbar_wait(BAR(B_LAND + s), (ph >> s) & 1);
            ph ^= 1u << s;
            if (lane == 0 && it == 0) TRACE(120 + s);
            uint32_t bad = 0;
#pragma unroll
            for (int u = 0; u < 8; u++) bad |= lds32u(ra + u * 4096) ^ tag;
            if (!__any_sync(~0u, bad & 1)) break;
            if (lane == 0) { mbar_expect_tx(BAR(B_LAND + s), 2 * SLOT); tma_3d(sb + s * STAGE + SLOT, &maps.n, 0, s * 64, m4 * 4, BAR(B_LAND + s)); TRACE(92 + s); }
            if (++it > (1 << 16)) SPIN_FAIL(0x203);
          }
          if (lane == 0) mbar_arrive(BAR(B_FULL + s));
        }
      } else {
        named_bar<8, 96>();
        uint32_t rbk = ld_rlx(pp.n + (size_t)((2 + (lane >> 4)) * 128 + rb) * (2 * D_) + (lane & 15) * 128);
        uint4 w[FK_GX - FK_G0][4];
        delay_until(c0, FK_ROW8DLY);
#pragma unroll
        for (int k = 0; k < FK_GX - FK_G0; k++)
#pragma unroll
          for (int i = 0; i < 4; i++) w[k][i] = ldg_nc(pp.x + (size_t)((FK_G0 + k) * 128 + rb) * (2 * D_) + lane * 16 + i * 512);
        uint32_t z = landed(rbk, pp.zero);
        if (lane < 2) red_add(&pp.cnt[(2 + lane) * 32], 1 + z);
        named_bar<9, 32 * (FK_G0 - 3)>();
        rbk = 0;
#pragma unroll
        for (int g = 4; g < FK_G0; g += 2) rbk |= ld_rlx(pp.n + (size_t)(min(g + (lane >> 4), FK_G0 - 1) * 128 + rb) * (2 * D_) + (lane & 15) * 128);
        z = landed(rbk, pp.zero);
        if (lane >= 4 && lane < FK_G0) red_add(&pp.cnt[lane * 32], 1 + z);
#pragma unroll
        for (int k = 0; k < FK_GX - FK_G0; k++) {
          ln_row(w[k]);
#pragma unroll
          for (int i = 0; i < 4; i++) stg128(pp.n + (size_t)((FK_G0 + k) * 128 + rb) * (2 * D_) + lane * 16 + i * 512, w[k][i]);
        }
        z = landed(ld_rlx(pp.n + (size_t)(min(FK_G0 + (lane >> 4), FK_GX - 1) * 128 + rb) * (2 * D_) + (lane & 15) * 128), pp.zero);
        if (lane >= FK_G0 && lane < FK_GX) red_add(&pp.cnt[lane * 32], 1 + z);
        if (lane == 0) TRACE(56);
      }
      {
        float acc[3][8];
        uint32_t sad[3];
#pragma unroll
        for (int a = 0; a < 3; a++) {
          sad[a] = reg + 12288 + ((32 * a + lane) / 6) * 4;
#pragma unroll
          for (int i = 0; i < 8; i++) acc[a][i] = 0.f;
        }
        const char* wpf = pp.wm + (size_t)kh * (512 * 12 * D_) + b * 6144;
        const char* wsrc = (j ? pp.ws_im : pp.ws_re) + (size_t)(t * 128 + m4 * 32 + kh * 16 - 16) * (2 * S_) + 28 * 128 + lane * 16;
        if (FK_WMPF && lane == 0) pf_bulk(wpf, 6144);
        uint32_t cn = c0 + FK_GSTART + kh * (FK_PACE / 2);
        auto request = [&](int c) {
          mbar_expect_tx(BAR(B_WM + kh * 2 + (c & 1)), 6144 + ((__float_as_uint(acc[0][0]) | __float_as_uint(acc[1][0]) | __float_as_uint(acc[2][0])) & pp.zero));
          tma_2d_hint(reg + (c & 1) * 6144, &maps.wm, b * 48, kh * 512 + c * 64, BAR(B_WM + kh * 2 + (c & 1)), pol_first);
        };
        uint4 e[4];
#pragma unroll 1
        for (int c = -2; c < 8; c++) {
          while ((int)((uint32_t)clock() - cn) < 0) __nanosleep(40);
          cn += c < 0 ? FK_PACE0 : FK_PACE;
          if (lane == 0) {
            if (FK_WMPF && c < 5) pf_bulk(wpf + (size_t)(c + 3) * (64 * 12 * D_), 6144);
          }
          __syncwarp();
          if (c < 0) {
            if (lane == 0) request(c + 2);
            __syncwarp();
            continue;
          }
          if (c >= 4) {
            const float v0 = sum8(e[0]), v1 = sum8(e[1]), v2 = sum8(e[2]), v3 = sum8(e[3]);
            const bool u4 = lane & 16, u3 = lane & 8;
            const float w0 = (u4 ? v2 : v0) + __shfl_xor_sync(~0u, u4 ? v0 : v2, 16), w1 = (u4 ? v3 : v1) + __shfl_xor_sync(~0u, u4 ? v1 : v3, 16);
            float v = (u3 ? w1 : w0) + __shfl_xor_sync(~0u, u3 ? w0 : w1, 8);
            v += __shfl_xor_sync(~0u, v, 4); v += __shfl_xor_sync(~0u, v, 2); v += __shfl_xor_sync(~0u, v, 1);
            if (!(lane & 7)) sts32(sb + RS_OFF + 256 + (kh * 16 + c * 4 - 16 + (lane >> 3)) * 4, v);
          }
          if (c >= 3 && c < 7) {
#pragma unroll
            for (int i = 0; i < 4; i++) e[i] = ldg_nc(wsrc + (size_t)(c * 4 + 4 + i) * (2 * S_));
          }
          mbar_wait(BAR(B_WM + kh * 2 + (c & 1)), (c >> 1) & 1);
#pragma unroll
          for (int u = 0; u < 12; u++) {
            const uint4 v = lds128u(reg + (c & 1) * 6144 + lane * 16 + u * 512);
            const float sc = lds32(sad[u % 3] + (u / 3) * 64);
            float (&ac)[8] = acc[u % 3];
            ac[0] = fmaf(sc, bf_lo(v.x), ac[0]); ac[1] = fmaf(sc, bf_hi(v.x), ac[1]);
            ac[2] = fmaf(sc, bf_lo(v.y), ac[2]); ac[3] = fmaf(sc, bf_hi(v.y), ac[3]);
            ac[4] = fmaf(sc, bf_lo(v.z), ac[4]); ac[5] = fmaf(sc, bf_hi(v.z), ac[5]);
            ac[6] = fmaf(sc, bf_lo(v.w), ac[6]); ac[7] = fmaf(sc, bf_hi(v.w), ac[7]);
          }
#pragma unroll
          for (int a = 0; a < 3; a++) sad[a] += 256;
          __syncwarp();
          if (lane == 0 && c < 6) request(c + 2);
        }
        __syncwarp();
#pragma unroll
        for (int a = 0; a < 3; a++) {
          sts128(reg + (32 * a + lane) * 32, acc[a][0], acc[a][1], acc[a][2], acc[a][3]);
          sts128(reg + (32 * a + lane) * 32 + 16, acc[a][4], acc[a][5], acc[a][6], acc[a][7]);
        }
        __syncwarp();
        float s0 = 0.f, s1 = 0.f;
#pragma unroll 8
        for (int m = 0; m < 16; m++) { const float2 v = lds64(reg + (lane < 24 ? lane * 8 : 0) + m * 192); s0 += v.x; s1 += v.y; }
        if (kh == 0) sts64(sb + RS_OFF + lane * 8, s0, s1);
        if (lane == 0) TRACE(80 + kh);
        named_bar<5, 64>();
        if (kh == 1) {
          const float2 p = lds64(sb + RS_OFF + lane * 8);
          unsigned* dst = pp.mod + b * 24 + (lane < 24 ? lane : 0);
          if (lane < 24) st_rlx(dst, pack_bf16(s0 + p.x, s1 + p.y));
          const uint32_t z = landed(ld_rlx(dst), pp.zero);
          if (lane == 0) { red_add(&pp.cnt[16 * 32], 1 + z); mbar_arrive(BAR(B_MODOK)); TRACE(9); }
          __syncwarp();
        }
      }
      if (kh == 0) {
        if (lane == 0) { mbar_arrive(BAR(B_MODOK)); TRACE(57); }
#pragma unroll 1
        for (int i = 0; i < 4; i++) {
          const int w = i ^ 2;
          if (lane == 0) {
            if (moe) { mbar_expect_tx(BAR(B_WB + w), 8192); tma_2d_hint(sb + SPARE + w * 8192, &maps.wg, b * 32, w * 128, BAR(B_WB + w), pol_first); }
            else mbar_arrive(BAR(B_WB + w));
          }
          __nanosleep(FK_BSLEEP);
        }
        take(IntC<0>{});
        take(IntC<1>{});
        if (lane == 0) TRACE(98);
        int sib = 1, pc = 0;
#pragma unroll 1
        for (int q = 4; q < 16; q++) {
          const int s = q & 3;
          const uint32_t ra = sb + s * STAGE + lane * 128 + ((lane & 7) << 4);
          int it = 0;
          while (true) {
            mbar_wait(BAR(B_LAND + s), (ph >> s) & 1);
            ph ^= 1u << s;
            const uint32_t bad = ((lds32u(ra) ^ tag) | (lds32u(ra + 4096) ^ tag) | (lds32u(ra + 8192) ^ tag) | (lds32u(ra + 12288) ^ tag)) & 1;
            if (!__any_sync(~0u, bad)) break;
            if (lane == 0) {
              mbar_expect_tx(BAR(B_LAND + s), SLOT);
              tma_2d(sb + s * STAGE, &maps.p, sibling(m4, sib) * 256 + pc * 64, j * S_ + t * 128, BAR(B_LAND + s));
            }
            if (++it > (1 << 16)) SPIN_FAIL(0x202);
          }
          if (lane == 0) mbar_arrive(BAR(B_FULL + s));
          if (++sib == 4) { sib = 1; pc++; }
        }
        if (lane == 0) TRACE(99);
      } else {
        take(IntC<0>{});
        {
          const unsigned tgt = tag * 128u; int it = 0;
          while ((int)(ld_rlx(&pp.cnt[16 * 32]) - tgt) < 0) { __nanosleep(100); if (++it > SPIN_LIMIT) SPIN_FAIL(0x204); }
        }
        if (lane == 0) TRACE(10);
        {
          const uint32_t sgn = j ? 0x80008000u : 0u;
          uint32_t sa[4], ca[4]; uint4 sv[4], cv[4], wr[4];
#pragma unroll
          for (int i = 0; i < 4; i++) {
            const int p = lane + 32 * i;
            sa[i] = ld_rlx(pp.mod + m4 * 128 + p); ca[i] = ld_rlx(pp.mod + 512 + m4 * 128 + p);
            sv[i] = ld_msg(reinterpret_cast<const uint4*>(pp.mod + 1536) + p); cv[i] = ld_msg(reinterpret_cast<const uint4*>(pp.mod + 2048) + p);
            wr[i] = ldg_nc(pp.wr + p * 16);
          }
          float c1 = 0.f, c2 = 0.f;
#pragma unroll
          for (int i = 0; i < 4; i++) {
            const int p = lane + 32 * i;
            sts64(sb + T1_OFF + ((p >> 3) * 4 + (p & 3)) * 16 + ((p >> 2) & 1) * 8, __uint_as_float(add1_bf2(ca[i]) ^ sgn), __uint_as_float(sa[i] ^ sgn));
            const uint32_t s4[4] = {sv[i].x, sv[i].y, sv[i].z, sv[i].w}, c4[4] = {cv[i].x, cv[i].y, cv[i].z, cv[i].w}, w4[4] = {wr[i].x, wr[i].y, wr[i].z, wr[i].w};
#pragma unroll
            for (int u = 0; u < 4; u++) {
              const uint32_t A = add1_bf2(c4[u]);
              c1 = fmaf(bf_lo(A), bf_lo(w4[u]), c1); c1 = fmaf(bf_hi(A), bf_hi(w4[u]), c1);
              c2 = fmaf(bf_lo(s4[u]), bf_lo(w4[u]), c2); c2 = fmaf(bf_hi(s4[u]), bf_hi(w4[u]), c2);
            }
          }
#pragma unroll
          for (int o = 16; o; o >>= 1) { c1 += __shfl_xor_sync(~0u, c1, o); c2 += __shfl_xor_sync(~0u, c2, o); }
          __syncwarp();
          if (lane == 0) { sts128(sb + CST_OFF, c1, c2, __uint_as_float(tag), 0.f); mbar_arrive(BAR(B_T1)); TRACE(30); }
        }
        take(IntC<1>{});
        const int G = lane >> 2, q = lane & 3, p0 = m4 * 128 + G * 16 + q;
        mbar_wait(BAR(B_PRDY + 1), 0);
        mbar_wait(BAR(B_PRDY + 3), 0);
        uint32_t ga[4], hi[4], lo[4];
#pragma unroll
        for (int u = 0; u < 4; u++) {
          ga[u] = ld_rlx(pp.mod + 1024 + p0 + 4 * u);
          const uint32_t cb = ld_rlx(pp.mod + 2048 + p0 + 4 * u), wr = __ldg(reinterpret_cast<const uint32_t*>(pp.wr) + p0 + 4 * u);
          const float w0 = bf_lo(add1_bf2(cb)) * bf_lo(wr), w1 = bf_hi(add1_bf2(cb)) * bf_hi(wr);
          hi[u] = pack_bf16(w0, w1);
          lo[u] = pack_bf16(w0 - bf_lo(hi[u]), w1 - bf_hi(hi[u]));
        }
        sts128u(sb + GA_OFF + lane * 16, ga[0], ga[1], ga[2], ga[3]);
        sts128u(sb + W_OFF + G * 144 + q * 16, hi[0], hi[1], hi[2], hi[3]);
        sts128u(sb + W_OFF + G * 144 + 64 + q * 16, lo[0], lo[1], lo[2], lo[3]);
        sts32u(sb + W_OFF + G * 144 + 128 + q * 4, 0x3F803F80u);
        mbar_wait(BAR(B_PL + 3), 0);
        __nanosleep(FK_RSLEEP);
        const uint4 sv = make_uint4(SENT, SENT, SENT, SENT);
#pragma unroll 1
        for (int i = 0; i < 7; i++) stg128(&pp.mail->part[(size_t)b * (NMOE * 2) + lane + 32 * i], sv);
#pragma unroll 1
        for (int i = 0; i < 2; i++) {
          stg128(&pp.mail->stats[(blk * 4 + m4) * 64 + lane + 32 * i], sv);
          stg128(&pp.mail->rowh[(blk * 2 + i) * 128 + m4 * 32 + lane], sv);
          stg128(&pp.mail->rowx[(blk * 2 + i) * 128 + m4 * 32 + lane], sv);
          stg128(&pp.mail->cand[((m4 * 32 + i * 16 + (lane >> 1)) * 32 + blk) * 2 + (lane & 1)], sv);
        }
        __syncwarp();
        if (lane == 0) { fence_gpu(); mbar_arrive(BAR(B_T2)); TRACE(97); }
      }
    }
    mbar_wait(BAR(B_SEL), 0);
    const uint32_t csel = (uint32_t)clock();
    if (moe) gate_up(pp, wf, sb, scr, warp, lane);
    if (warp == 1) {
      const uint2 sel = lds64u(sb + SEL_OFF);
      const int n = (lane >> 3) & 1;
      const int col = (b >> 4) * 128 + (lane & 1) * 64 + ((b >> 2) & 3) * 16 + (b & 3) * 2 + ((lane >> 1) & 1) + (lane >> 4) * 8;
      const int slot = sel_slot(sel, n) * 512, wofs = slot + ((col >> 5) * 4 + ((col >> 1) & 3)) * 4 + ((col >> 3) & 3);
      const uint32_t gbp = ld_rlx(pp.mod + 2560 + (col >> 1));
      uint32_t hp, xp; int it = 0;
      while (true) {
        hp = ld_rlx(reinterpret_cast<const uint32_t*>(pp.mail->rowh) + wofs); xp = ld_rlx(reinterpret_cast<const uint32_t*>(pp.mail->rowx) + slot + (col >> 1));
        if (__all_sync(~0u, hp != SENT && xp != SENT)) break;
        if (++it > SPIN_LIMIT) SPIN_FAIL(0x2ff);
      }
      const float sg = round_bf16(sigmoid_f(round_bf16(key_val(n ? sel.y : sel.x))));
      const int gq = lane >> 2;
      const uint32_t one = (lane & 1) == (gq >> 2) ? ((gq & 1) ? 0x3F800000u : 0x00003F80u) : 0u;
      const uint32_t s0 = (gq & 2) ? 0u : one, s1 = (gq & 2) ? one : 0u;
      const uint4* src = &pp.mail->part[(size_t)b * (NMOE * 2) + lane];
      uint4 m[7];
      delay_until(csel, FK_E4DLY);
      it = 0;
      while (true) {
        bool ok = true;
#pragma unroll
        for (int i = 0; i < 7; i++) m[i] = ld_msg(src + 32 * i);
#pragma unroll
        for (int i = 0; i < 7; i++) ok &= m[i].x != SENT;
        if (__all_sync(~0u, ok)) break;
        if (++it > SPIN_LIMIT) SPIN_FAIL(0x20b);
      }
      if (lane == 0) TRACE(23);
      float c[3][4];
#pragma unroll
      for (int i = 0; i < 3; i++) { c[i][0] = c[i][1] = c[i][2] = c[i][3] = 0.f; }
#pragma unroll
      for (int i = 0; i < 7; i++) mma_16816(c[i % 3], m[i].x, m[i].y, m[i].z, m[i].w, s0, s1);
#pragma unroll
      for (int i = 0; i < 4; i++) c[0][i] += c[1][i] + c[2][i];
      const bool u4 = lane & 16, u3 = lane & 8;
      const float a0 = (u4 ? c[0][2] : c[0][0]) + __shfl_xor_sync(~0u, u4 ? c[0][0] : c[0][2], 16), a1 = (u4 ? c[0][3] : c[0][1]) + __shfl_xor_sync(~0u, u4 ? c[0][1] : c[0][3], 16);
      float y = (u3 ? a1 : a0) + __shfl_xor_sync(~0u, u3 ? a0 : a1, 8);
      y += __shfl_xor_sync(~0u, y, 4);
      const bool odd = col & 1;
      const float upd = round_bf16(round_bf16(y) * sg);
      const float o = fmaf(odd ? bf_hi(gbp) : bf_lo(gbp), (odd ? bf_hi(hp) : bf_lo(hp)) + upd, odd ? bf_hi(xp) : bf_lo(xp));
      if (!(lane & 4)) reinterpret_cast<__nv_bfloat16*>(pp.out)[(size_t)key_row(n ? sel.y : sel.x) * D_ + col] = __float2bfloat16_rn(o);
      if (lane == 0) { TRACE(24); TRACE_CLK(54); if (b == 0) pp.cnt[17 * 32] = tag; }
    }
  } else {
    const int cw = (warp - 4) >> 2;
    const int wq = warp & 3;
    const int wtid = tid & 127;
    const int gq = lane >> 2, q4 = lane & 3;
    const bool lag = cw == j;
    const bool elect = wtid == 0;
    const uint32_t rel = wtid < 2 ? mapa(BAR(B_EMPTY), wtid) : 0;

    if (cw) named_bar<3, 256>(); else named_bar<0, 256>();
    if (tid == 128) TRACE(124);
    asm volatile("barrier.cluster.wait.acquire.aligned;" ::: "memory");
    if (tid == 128) TRACE(125);

    const int mrow = wq * 16 + (lane & 7) + ((lane >> 3) & 1) * 8;
    {
      float acc[128];
      gemm_phase<1, 0, 32>(pp, acc, sb, cw, lag, elect, rel);
      mbar_wait(BAR(B_T1), 0);
      const uint32_t tad = sb + T1_OFF + q4 * 16;
      uint4 tb[16];
#pragma unroll
      for (int c = 0; c < 4; c++) tb[c] = lds128u(tad + c * 64);
      const uint32_t rs0 = lds32u(sb + RS_OFF + (cw * 64 + wq * 16 + gq) * 4), rs1 = lds32u(sb + RS_OFF + (cw * 64 + wq * 16 + gq + 8) * 4);
      const uint32_t dst = sb + cw * 8192 + mrow * 128, pb = BAR(B_PRDY + (lag ? 2 : 0));
      const uint32_t pmask = q4 ? 0u : 1u, par = lds32u(sb + CST_OFF + 8);
      gemm_finish(acc, rel);
      if (elect) { TRACE(lag ? 5 : 4); if (lag) TRACE_CLK(51); }
#pragma unroll
      for (int i = 0; i < 16; i++) {
        uint32_t r[4];
        const int o = 8 * i;
        r[0] = fma_bf2(pack_bf16(acc[o], acc[o + 1]), tb[i].x, mul_bf2(rs0, tb[i].y));
        r[1] = fma_bf2(pack_bf16(acc[o + 2], acc[o + 3]), tb[i].x, mul_bf2(rs1, tb[i].y));
        r[2] = fma_bf2(pack_bf16(acc[o + 4], acc[o + 5]), tb[i].z, mul_bf2(rs0, tb[i].w));
        r[3] = fma_bf2(pack_bf16(acc[o + 6], acc[o + 7]), tb[i].z, mul_bf2(rs1, tb[i].w));
        if (!(i & 3)) { r[0] = (r[0] & ~pmask) | (par & pmask); r[1] = (r[1] & ~pmask) | (par & pmask); }
        if (i < 12) tb[i + 4] = lds128u(tad + (i + 4) * 64);
        stsm_x4(dst + (i >> 2) * STAGE + (uint32_t)(((((2 * i) & 7) + (lane >> 4)) ^ (lane & 7)) << 4), r[0], r[1], r[2], r[3]);
        if (i == 3 || i == 15) {
          fence_async_smem();
          __syncwarp();
          if (lane == 0) mbar_arrive(pb + (i >> 3) * 8);
        }
      }
      mbar_wait(pb + 8, 0);
    }
    if (elect) TRACE(lag ? 7 : 6);
    float acc[128];
    gemm_phase<0, 32, 48>(pp, acc, sb, cw, lag, elect, rel);

    if (!lag) {
      const uint32_t rdst = mapa(sb + STAGE + j * 8192 + wtid * 16, j ^ 1), rbar = mapa(BAR(B_RECV), j ^ 1);
      mbar_wait(BAR(B_T2), 0);
      mbar_wait(BAR(B_X), 0);
      uint32_t xf[16][4]; uint4 ga[8];
      auto fetch = [&](int i) {
        ldsm_x4(sb + SPARE + (i >> 2) * 8192 + mrow * 128 + (uint32_t)(((((2 * i) & 7) + (lane >> 4)) ^ (lane & 7)) << 4), xf[i][0], xf[i][1], xf[i][2], xf[i][3]);
        if (!(i & 1)) ga[i >> 1] = lds128u(sb + GA_OFF + ((i >> 1) * 4 + q4) * 16);
      };
      fetch(0); fetch(1); fetch(2);
      mbar_wait(BAR(B_PEER), 0);
      gemm_finish(acc, rel);
      if (elect) { mbar_arrive_cluster(rbar + (B_PEER + 1 - B_RECV) * 8); TRACE(12); }
#pragma unroll
      for (int i = 0; i < 16; i++) {
        const int o = 8 * i;
        const uint32_t g0 = (i & 1) ? ga[i >> 1].z : ga[i >> 1].x, g1 = (i & 1) ? ga[i >> 1].w : ga[i >> 1].y;
        const uint32_t w0 = fma_bf2(g0, pack_bf16(acc[o], acc[o + 1]), xf[i][0]), w1 = fma_bf2(g0, pack_bf16(acc[o + 2], acc[o + 3]), xf[i][1]);
        const uint32_t w2 = fma_bf2(g1, pack_bf16(acc[o + 4], acc[o + 5]), xf[i][2]), w3 = fma_bf2(g1, pack_bf16(acc[o + 6], acc[o + 7]), xf[i][3]);
        if (i == 0) { fetch(3); fetch(4); } else if (i < 12) fetch(i + 4);
        if (i < 8 && ((FK_SB >> i) & 1)) mbar_wait(BAR(B_PEER), 0);
        if (i == 8) mbar_wait(BAR(B_PEER + 1), 0);
        if (i == 12) mbar_wait(BAR(B_EMPTY + 1), 1);
        asm volatile("st.async.weak.shared::cluster.mbarrier::complete_tx::bytes.v4.b32 [%0], {%1, %2, %3, %4}, [%5];"
                     ::"r"(i < 12 ? rdst + (i >> 2) * STAGE + (i & 3) * 2048 : rdst + (1 - 2 * j) * 8192 + (i & 3) * 2048), "r"(w0), "r"(w1), "r"(w2), "r"(w3),
                       "r"(rbar + (i >> 2) * 8) : "memory");
      }
      __syncwarp();
      if (lane == 0) mbar_arrive(BAR(B_XDONE));
      if (elect) TRACE(13);
      if (b < NMOE) {
        uint32_t wf[128];
        named_bar<1, 256>();
        mbar_wait(BAR(B_GU), 0);
        const uint32_t box = sb + (wq < 3 ? wq : 4) * SLOT;
        take_box<0>(wf, box, lane);
        take_box<1>(wf, box + 8192, lane);
        if (elect) TRACE(26);
        mbar_wait(BAR(B_SEL), 0);
        gate_up(pp, wf, sb, scr, 4 + wq, lane);
      }
      OutTab tb;
      {
        const uint4* mp = reinterpret_cast<const uint4*>(pp.mod) + m4 * 32 + lane;
        out_tab(tb, ldg128(mp + 512), ldg128(mp + 384), ldg128(mp + 640));
      }
      mbar_wait(BAR(B_SEL), 0);
      const uint2 sel = lds64u(sb + SEL_OFF), cnd = lds64u(sb + TOP_OFF + 32);
      char* odst = pp.out + (size_t)blk * (64 * 2 * D_) + m4 * 512 + lane * 16;
      const int s1 = key_row(sel.x) - blk * 64, s2 = key_row(sel.y) - blk * 64, c1 = key_row(cnd.x) - blk * 64, c2 = key_row(cnd.y) - blk * 64;
#pragma unroll 1
      for (int r = wq * 16; r < wq * 16 + 16; r++) {
        if (r == s1 || r == s2 || ((r & 15) < FK_OSPLIT && r != c1 && r != c2)) continue;
        const uint32_t cn = (uint32_t)clock();
        out_row(tb, sb, scr, r, lane, odst);
        if ((r & 15) < 15) delay_until(cn, FK_OPACE);
      }
      if (elect) TRACE(28);
    } else {
      mbar_wait(BAR(B_T2), 0);
      uint32_t xa[64];
      float dl[2][4], dq[4][4];
#pragma unroll
      for (int i = 0; i < 4; i++) { dl[0][i] = dl[1][i] = dq[0][i] = dq[1][i] = dq[2][i] = dq[3][i] = 0.f; }
      {
        const uint32_t wad = sb + W_OFF + ((gq & 2) ? 128 : (gq & 1) * 64 + q4 * 16), rsrc = sb + STAGE + (1 - j) * 8192 + wtid * 16;
        uint4 rv[16], wb[8], ga[8];
        auto fetch = [&](int i) {
          rv[i] = lds128u(i < 12 ? rsrc + (i >> 2) * STAGE + (i & 3) * 2048 : rsrc + (2 * j - 1) * 8192 + (i & 3) * 2048);
          if (!(i & 1)) ga[i >> 1] = lds128u(sb + GA_OFF + ((i >> 1) * 4 + q4) * 16); else wb[i >> 1] = lds128u(wad + (i >> 1) * 144);
        };
        mbar_wait(BAR(B_RECV), 0);
        fetch(0); fetch(1);
        gemm_finish(acc, rel);
        if (elect) { TRACE(14); TRACE_CLK(53); }
        uint32_t pk[64];
#pragma unroll
        for (int i = 0; i < 16; i++) {
          if (i == 0) {
#pragma unroll
            for (int u = 0; u < 32; u++) { pk[u] = pack_bf16(acc[2 * u], acc[2 * u + 1]); if (u == 7 || u == 15) fetch(2 + (u >> 3)); }
          }
          if (i == 2) {
#pragma unroll
            for (int u = 32; u < 64; u++) pk[u] = pack_bf16(acc[2 * u], acc[2 * u + 1]);
          }
          if (i == 2 || i == 6 || i == 10) {
            mbar_wait(BAR(B_RECV + 1 + (i >> 2)), 0);
#pragma unroll
            for (int u = 0; u < 4; u++) fetch(i + 2 + u);
          }
          const uint32_t g0 = (i & 1) ? ga[i >> 1].z : ga[i >> 1].x, g1 = (i & 1) ? ga[i >> 1].w : ga[i >> 1].y;
          const uint32_t a0 = fma_bf2(g0, pk[4 * i], rv[i].x), a1 = fma_bf2(g0, pk[4 * i + 1], rv[i].y);
          const uint32_t a2 = fma_bf2(g1, pk[4 * i + 2], rv[i].z), a3 = fma_bf2(g1, pk[4 * i + 3], rv[i].w);
          xa[4 * i] = a0; xa[4 * i + 1] = a1; xa[4 * i + 2] = a2; xa[4 * i + 3] = a3;
          mma_1688(dq[0], a0, a1, a0); mma_1688(dq[1], a0, a1, a1);
          mma_1688(dq[2], a2, a3, a2); mma_1688(dq[3], a2, a3, a3);
          if (i & 1) {
            mma_16816(dl[0], xa[4 * i - 4], xa[4 * i - 3], xa[4 * i - 2], xa[4 * i - 1], wb[i >> 1].x, wb[i >> 1].y);
            mma_16816(dl[1], a0, a1, a2, a3, wb[i >> 1].z, wb[i >> 1].w);
          }
        }
      }
      const float4 cst = lds128(sb + CST_OFF);
      const uint32_t tag = __float_as_uint(cst.z);
      uint4 own;
      {
        const bool odd = q4 & 1;
        const float l0 = dl[0][0] + dl[1][0], l1 = dl[0][1] + dl[1][1], l2 = dl[0][2] + dl[1][2], l3 = dl[0][3] + dl[1][3];
        const float mine = odd ? l2 : l0 + l1;
        const float other = __shfl_xor_sync(~0u, odd ? l0 : l2 + l3, 1);
        const int dsrc = (lane & ~3) | (gq >> 1);
        const float qa = __shfl_sync(~0u, (gq & 1) ? dq[0][1] + dq[2][1] : dq[0][0] + dq[2][0], dsrc);
        const float qb = __shfl_sync(~0u, (gq & 1) ? dq[1][3] + dq[3][3] : dq[1][2] + dq[3][2], dsrc);
        own = make_uint4(__float_as_uint(odd ? mine : other), __float_as_uint(odd ? qb : qa), __float_as_uint(odd ? other : mine), tag);
        if (q4 < 2) st_msg(&pp.mail->stats[(blk * 4 + m4) * 64 + wq * 16 + gq + 8 * q4], own.x, own.y, own.z, tag);
      }
      if (elect) TRACE(15);
      const int srow = wq * 16 + gq + 8 * (q4 & 1);
      const uint4* src0 = &pp.mail->stats[(blk * 4 + (m4 ^ (q4 | 1))) * 64 + srow];
      const uint4* src1 = &pp.mail->stats[(blk * 4 + (m4 ^ 2)) * 64 + srow];
      if (FK_E1DLY) delay_until((uint32_t)clock(), FK_E1DLY);
      uint4 m0 = ld_msg(src0), m1 = own;
      if (q4 >= 2) m1 = ld_msg(src1);
      mbar_wait(BAR(B_EMPTY + 3), 1);
#pragma unroll
      for (int i = 0; i < 16; i++)
        stsm_x4(sb + XST_OFF + mrow * 512 + (i >> 2) * 128 + (uint32_t)(((((2 * i) & 7) + (lane >> 4)) ^ (lane & 7)) << 4), xa[4 * i], xa[4 * i + 1], xa[4 * i + 2], xa[4 * i + 3]);
      uint4 cbv, sbv, gbv;
      uint32_t k1, k2;
      {
        int it = 0;
        while (!__all_sync(~0u, m0.w == tag && m1.w == tag)) {
          m0 = ld_msg(src0);
          if (q4 >= 2) m1 = ld_msg(src1);
          if (++it > SPIN_LIMIT) SPIN_FAIL(0x209);
        }
        if (elect) TRACE(16);
        const uint4* mp = reinterpret_cast<const uint4*>(pp.mod) + m4 * 32 + lane;
        cbv = ldg128(mp + 512); sbv = ldg128(mp + 384); gbv = ldg128(mp + 640);
        float sa = __uint_as_float(m0.x) + __uint_as_float(m1.x), qa = __uint_as_float(m0.y) + __uint_as_float(m1.y), da = __uint_as_float(m0.z) + __uint_as_float(m1.z);
        sa += __shfl_xor_sync(~0u, sa, 2); qa += __shfl_xor_sync(~0u, qa, 2); da += __shfl_xor_sync(~0u, da, 2);
        const float mean = sa * (1.f / D_);
        const float rstd = rsqrtf(fmaxf(fmaf(-mean, mean, qa * (1.f / D_)), 0.f) + 1e-5f);
        const float rme = fmaf(rstd, fmaf(-mean, cst.x, da), cst.y);
        warp_top2(fkey(rme, blk * 64 + srow), 0u, k1, k2);
        if (lane == 0) sts64u(sb + TOP_OFF + wq * 8, k1, k2);
        if (q4 < 2) sts64(scr + RST_REL + srow * 8, rstd, -mean * rstd);
        named_bar<2, 128>();
        const uint2 c = lds64u(sb + TOP_OFF + (lane & 3) * 8);
        warp_top2(c.x, c.y, k1, k2);
        if (wq == 0) {
          st_msg(&pp.mail->cand[((m4 * 32 + lane) * 32 + blk) * 2], k1, k2, tag, 0);
          if (lane == 0) sts64u(sb + TOP_OFF + 32, k1, k2);
          named_arrive<7, 64>();
        }
      }
      if (b < NMOE) named_arrive<1, 256>();
      if (elect) TRACE(17);
      const int c1 = key_row(k1) - blk * 64, c2 = key_row(k2) - blk * 64;
      if (wq >= 2) {
        const int r = wq == 2 ? c1 : c2;
        const uint4 v = lds128u(sb + XST_OFF + r * 512 + ((lane ^ (r & 7)) << 4));
        const float2 st = lds64(scr + RST_REL + r * 8);
        auto h2 = [&](uint32_t xv, uint32_t cv, uint32_t sv) {
          const uint32_t av = add1_bf2(cv);
          return pack_bf16(fmaf(fmaf(bf_lo(xv), st.x, st.y), bf_lo(av), bf_lo(sv)), fmaf(fmaf(bf_hi(xv), st.x, st.y), bf_hi(av), bf_hi(sv)));
        };
        const uint32_t sc = scr + SCR_REL + wq * 512;
        sts128u(sc + lane * 16, h2(v.x, cbv.x, sbv.x), h2(v.y, cbv.y, sbv.y), h2(v.z, cbv.z, sbv.z), h2(v.w, cbv.w, sbv.w));
        __syncwarp();
        const uint32_t fa = sc + gq * 64 + q4 * 4;
        const int o = (blk * 2 + wq - 2) * 128 + m4 * 32 + lane;
        st_msg(&pp.mail->rowh[o], lds32u(fa), lds32u(fa + 16), lds32u(fa + 32), lds32u(fa + 48));
        st_msg(&pp.mail->rowx[o], v.x, v.y, v.z, v.w);
        if (lane == 0 && wq == 3) TRACE(18);
      }
      {
        OutTab tb;
        out_tab(tb, cbv, sbv, gbv);
        char* odst = pp.out + (size_t)blk * (64 * 2 * D_) + m4 * 512 + lane * 16;
#pragma unroll 1
        for (int r = wq * 16; r < wq * 16 + FK_OSPLIT; r++) {
          if (r == c1 || r == c2) continue;
          const uint32_t cn = (uint32_t)clock();
          out_row(tb, sb, scr, r, lane, odst);
          if ((r & 15) < FK_OSPLIT - 1) delay_until(cn, FK_OPACE);
        }
      }
      if (elect) TRACE(25);
      if (b < NMOE) {
        uint32_t wd[128];
        mbar_wait(BAR(B_DN + wq), 0);
        {
          const int fr = (lane & 7) + (lane >> 4) * 8;
          const uint32_t base = sb + dn_box(wq) + fr * 128;
#pragma unroll
          for (int c = 0; c < 4; c++) {
            const uint32_t ad = base + (((uint32_t)(c * 2 + ((lane >> 3) & 1)) ^ (uint32_t)(lane & 7)) << 4);
#pragma unroll
            for (int gI = 0; gI < 4; gI++)
#pragma unroll
              for (int ks = 0; ks < 2; ks++) {
                const int o = ((gI * 4 + c) * 2 + ks) * 4;
                ldsm_x4_t(ad + gI * 4096 + ks * 2048, wd[o], wd[o + 1], wd[o + 2], wd[o + 3]);
              }
          }
        }
        uint4* dst = &pp.mail->part[((size_t)(wq * 32 + q4 * 4 + (gq >> 1)) * NMOE + b) * 2 + (gq & 1)];
        if (lane == 0 && wq == 3) TRACE(27);
        named_bar<4, 384>();
        if (elect) TRACE(21);
        float g0 = 0.f, g1 = 0.f, u0 = 0.f, u1 = 0.f;
#pragma unroll
        for (int w = 0; w < 8; w++) {
          const float2 gv = lds64(scr + PART_REL + w * 512 + lane * 8), uv = lds64(scr + PART_REL + w * 512 + 256 + lane * 8);
          g0 += gv.x; g1 += gv.y; u0 += uv.x; u1 += uv.y;
        }
        const uint32_t act = pack_bf16(round_bf16(silu_f(round_bf16(g0))) * round_bf16(u0), round_bf16(silu_f(round_bf16(g1))) * round_bf16(u1));
        uint32_t ab[4];
#pragma unroll
        for (int u = 0; u < 4; u++) {
          const uint32_t v0 = __shfl_sync(~0u, act, 8 * u + 2 * q4), v1 = __shfl_sync(~0u, act, 8 * u + 2 * q4 + 1);
          ab[u] = __byte_perm(v0, v1, (gq & 1) ? 0x7632 : 0x5410);
        }
        float c[4][4];
#pragma unroll
        for (int v = 0; v < 4; v++) { c[v][0] = c[v][1] = c[v][2] = c[v][3] = 0.f; }
#pragma unroll
        for (int q = 0; q < 4; q++) {
          const uint32_t mk = (gq >> 1) == q ? ~0u : 0u;
          const uint32_t b0 = ab[0] & mk, b1 = ab[1] & mk, b2 = ab[2] & mk, b3 = ab[3] & mk;
#pragma unroll
          for (int v = 0; v < 4; v++) { const int o = (4 * v + q) * 8; mma_16816(c[v], wd[o], wd[o + 1], wd[o + 2], wd[o + 3], b0, b1); }
#pragma unroll
          for (int v = 0; v < 4; v++) { const int o = (4 * v + q) * 8 + 4; mma_16816(c[v], wd[o], wd[o + 1], wd[o + 2], wd[o + 3], b2, b3); }
        }
#pragma unroll
        for (int u = 0; u < 2; u++)
          st_msg(dst + u * (16 * NMOE * 2), pack_bf16(c[2 * u][0], c[2 * u][1]), pack_bf16(c[2 * u][2], c[2 * u][3]),
                 pack_bf16(c[2 * u + 1][0], c[2 * u + 1][1]), pack_bf16(c[2 * u + 1][2], c[2 * u + 1][3]));
        if (elect) TRACE(22);
      }
    }
  }
}

typedef CUresult (*PFN_encodeTiled)(CUtensorMap*, CUtensorMapDataType, cuuint32_t, void*, const cuuint64_t*, const cuuint64_t*,
                                    const cuuint32_t*, const cuuint32_t*, CUtensorMapInterleave, CUtensorMapSwizzle,
                                    CUtensorMapL2promotion, CUtensorMapFloatOOBfill);

static void map2d(PFN_encodeTiled enc, CUtensorMap* m, const void* p, uint64_t rows, uint64_t cols, uint32_t brows, uint32_t bcols, CUtensorMapSwizzle sw,
                  CUtensorMapL2promotion pr = CU_TENSOR_MAP_L2_PROMOTION_L2_128B) {
  cuuint64_t dims[2] = {cols, rows}; cuuint64_t str[1] = {cols * 2}; cuuint32_t box[2] = {bcols, brows}; cuuint32_t es[2] = {1, 1};
  enc(m, CU_TENSOR_MAP_DATA_TYPE_BFLOAT16, 2, (void*)p, dims, str, box, es, CU_TENSOR_MAP_INTERLEAVE_NONE, sw, pr,
      CU_TENSOR_MAP_FLOAT_OOB_FILL_NONE);
}
static void map3d(PFN_encodeTiled enc, CUtensorMap* m, const void* p, uint64_t rows, uint64_t cols, uint32_t brows, uint32_t bgroups) {
  cuuint64_t dims[3] = {64, rows, cols / 64}; cuuint64_t str[2] = {cols * 2, 128}; cuuint32_t box[3] = {64, brows, bgroups}; cuuint32_t es[3] = {1, 1, 1};
  enc(m, CU_TENSOR_MAP_DATA_TYPE_BFLOAT16, 3, (void*)p, dims, str, box, es, CU_TENSOR_MAP_INTERLEAVE_NONE, CU_TENSOR_MAP_SWIZZLE_128B,
      CU_TENSOR_MAP_L2_PROMOTION_L2_128B, CU_TENSOR_MAP_FLOAT_OOB_FILL_NONE);
}

}

extern "C" void kernel_launch(void* const* d_in, const int* in_sizes, int n_in, void* d_out, int out_size) {
  using namespace fk;
  (void)in_sizes; (void)n_in; (void)out_size;
  static PFN_encodeTiled enc = nullptr;
  static int maxClusters = -1;
  static void *pn = nullptr, *pP = nullptr, *pc = nullptr, *pm = nullptr, *pmod = nullptr;
  if (!enc) {
    void* fn = nullptr; cudaDriverEntryPointQueryResult qr;
    cudaGetDriverEntryPoint("cuTensorMapEncodeTiled", &fn, cudaEnableDefault, &qr);
    enc = (PFN_encodeTiled)fn;
    cudaGetSymbolAddress(&pn, g_n);
    cudaGetSymbolAddress(&pP, g_P);
    cudaGetSymbolAddress(&pc, g_cnt);
    cudaGetSymbolAddress(&pm, g_mail);
    cudaGetSymbolAddress(&pmod, g_mod);
    cudaFuncSetAttribute(fused_kernel, cudaFuncAttributeMaxDynamicSharedMemorySize, SMEM_BYTES);
  }
  Maps maps;
  map2d(enc, &maps.ws[0], d_in[1], S_, S_, 128, 64, CU_TENSOR_MAP_SWIZZLE_128B);
  map2d(enc, &maps.ws[1], d_in[2], S_, S_, 128, 64, CU_TENSOR_MAP_SWIZZLE_128B);
  map3d(enc, &maps.n, pn, S_, D_, 64, 4);
  map2d(enc, &maps.p, pP, 2 * S_, D_, 128, 64, CU_TENSOR_MAP_SWIZZLE_128B);
  map2d(enc, &maps.ps, pP, 2 * S_, D_, 64, 64, CU_TENSOR_MAP_SWIZZLE_128B);
  map2d(enc, &maps.wd[0], d_in[3], D_, D_, 256, 64, CU_TENSOR_MAP_SWIZZLE_128B);
  map2d(enc, &maps.wd[1], d_in[4], D_, D_, 256, 64, CU_TENSOR_MAP_SWIZZLE_128B);
  map2d(enc, &maps.x, d_in[0], S_, D_, 64, 64, CU_TENSOR_MAP_SWIZZLE_128B);
  map2d(enc, &maps.wg, d_in[7], D_, F_, 128, 32, CU_TENSOR_MAP_SWIZZLE_64B);
  map2d(enc, &maps.wu, d_in[8], D_, F_, 128, 32, CU_TENSOR_MAP_SWIZZLE_64B);
  map3d(enc, &maps.wdn, d_in[9], F_, D_, 32, 4);
  map2d(enc, &maps.wm, d_in[11], D_, 6 * D_, 64, 48, CU_TENSOR_MAP_SWIZZLE_NONE);

  cudaLaunchConfig_t cfg = {};
  cfg.gridDim = dim3(NCTA); cfg.blockDim = dim3(384); cfg.dynamicSmemBytes = SMEM_BYTES; cfg.stream = cudaStreamPerThread;
  cudaLaunchAttribute at[1];
  at[0].id = cudaLaunchAttributeClusterDimension; at[0].val.clusterDim.x = 2; at[0].val.clusterDim.y = 1; at[0].val.clusterDim.z = 1;
  cfg.attrs = at; cfg.numAttrs = 1;
  Ptrs pp{(const char*)d_in[0], (char*)pn, (unsigned*)pc, 0, 0, (Mail*)pm, (uint32_t*)pmod, (const char*)d_in[10], (const char*)d_in[1], (const char*)d_in[2],
          (const char*)d_in[3], (const char*)d_in[4], (const char*)d_in[6], (const char*)d_in[7], (const char*)d_in[8], (const char*)d_in[9], (const char*)d_in[11], (char*)d_out, nullptr};
  if (maxClusters < 0) {
    cfg.gridDim = dim3(NCTA + NEXTRA);
    if (cudaOccupancyMaxActiveClusters(&maxClusters, fused_kernel, &cfg) != cudaSuccess) maxClusters = 0;
  }
  pp.b0 = -NEXTRA;
  if (maxClusters >= (NCTA + NEXTRA) / 2) {
    cfg.gridDim = dim3(NCTA + NEXTRA);
  } else {
    cfg.gridDim = dim3(NEXTRA);
    cudaLaunchKernelEx(&cfg, fused_kernel, pp, maps);
    cfg.gridDim = dim3(NCTA); pp.b0 = 0;
  }
  cudaLaunchKernelEx(&cfg, fused_kernel, pp, maps);
}
```

```cpp
#include <cuda_runtime.h>
#include <cuda_bf16.h>
#include <cuda.h>
#include <stdint.h>

#define DEVINL __device__ __forceinline__

namespace fk {

constexpr int S_ = 2048, D_ = 1024, F_ = 3584;
constexpr int NCTA = 128;
constexpr int NEXTRA = 4;
constexpr int NMOE = 112;
constexpr int SLOT = 16384;
constexpr int STAGE = 3 * SLOT;
constexpr int SPARE = 4 * STAGE;
constexpr int MISC = SPARE + 32768;
constexpr int SMEM_BYTES = MISC + 3072;
constexpr int BAR_OFF = MISC;
constexpr int CST_OFF = MISC + 480;
constexpr int SEL_OFF = MISC + 496;
constexpr int T1_OFF = MISC + 512;
constexpr int RS_OFF = T1_OFF + 2048;
constexpr int GA_OFF = T1_OFF;
constexpr int W_OFF = GA_OFF + 512;
constexpr int TOP_OFF = GA_OFF + 1792;
constexpr int XST_OFF = 3 * STAGE + SLOT;
constexpr int PART_REL = 0;
constexpr int SCR_REL = 4096;
constexpr int RST_REL = 6144;
enum { B_FULL = 0, B_EMPTY = 4, B_EMPTYH = 8, B_PRDY = 12  , B_PL = 16  , B_WM = 20  , B_LAND = 24  ,
       B_WB = 28  , B_DN = 32  , B_RECV = 36  , B_STAG = 40, B_T1 = 41, B_MODOK = 42, B_PEER = 43  , B_X = 45, B_T2 = 46,
       B_GU = 47, B_XDONE = 48, B_SEL = 49, B_NUM = 50 };

__host__ __device__ constexpr int bar_count(int i) {
  return (i >= B_EMPTY && i < B_EMPTYH) || (i >= B_PRDY && i < B_PL) || i == B_X || i == B_XDONE ? 4
         : (i < B_EMPTY || i == B_T1 || i == B_GU || i == B_MODOK) ? 2 : 1;
}

#define FK_XDEPTH 2
#define FK_G0 8
#define FK_ROW1DLY 700
#define FK_ROW2DLY 1300
#define FK_HINT 0
#define FK_A1EARLY 0
#define FK_XDLY 600
#define FK_ROW4DLY 2600
#define FK_WS0DLY 500
#define FK_WS1DLY 1600
#define FK_ADLY 1800
#define FK_L1 2
#define FK_L2 3
#define FK_PF0 19
#define FK_E1DLY 150
#define FK_E2DLY 300
#define FK_E4DLY 650
#define FK_MAP 3
#define FK_PPACE 620
#define FK_PACE0 1000
#define FK_WMPF 0
#define FK_TG 28
#define FK_TU 31
#define FK_BSLEEP 250
#define FK_PFSKIP 0
#define FK_DNWIN 1
#define FK_OPACE 330
#define FK_OSPLIT 6
#define FK_WGATE -1
#define FK_RSLEEP 1000
#define FK_PGAP 150
#define FK_GX 10
#define FK_ROW8DLY 3600
#define FK_GSTART 7000
#define FK_OPACE2 330
#define FK_E2GAP -1
#define FK_TABEARLY 1
#define FK_PUSHALL 0
#define FK_E3WEAK 1
#define FK_PK 8
#define FK_NQ 4
#define FK_NL 2
#define FK_W2 0
#define FK_PACE 2000
constexpr int SPIN_LIMIT = 1 << 22;
constexpr uint32_t SENT = 0xFFFFFFFFu;

struct Maps {
  CUtensorMap ws[2];
  CUtensorMap n;
  CUtensorMap p;
  CUtensorMap ps;
  CUtensorMap wd[2];
  CUtensorMap x;
  CUtensorMap wg, wu;
  CUtensorMap wdn;
  CUtensorMap wm;
};
template <int V> struct IntC { static constexpr int value = V; };
struct Mail;
struct Ptrs { const char* x; char* n; unsigned* cnt; int b0; uint32_t zero; Mail* mail; uint32_t* mod; const char *c, *ws_re, *ws_im, *wd_re, *wd_im, *wr, *wg, *wu, *wdn, *wm; char* out; unsigned long long* trace; };

__device__ __align__(1024) __nv_bfloat16 g_n[S_ * D_];
__device__ __align__(1024) __nv_bfloat16 g_P[2 * S_ * D_];
__device__ __align__(128) uint32_t g_mod[3 * D_];
__device__ __align__(128) unsigned g_cnt[19 * 32];
struct Mail {
  uint4 stats[32 * 4 * 64];
  uint2 cand[32];
  uint4 rowh[64 * 128];
  uint4 rowx[64 * 128];
  uint4 part[128 * NMOE * 2];
  uint2 rs[2 * 16 * 128];
};
static_assert(FK_L2 == 3, "the receive layout assumes a stagger of three k-blocks");
__device__ __align__(1024) Mail g_mail;

#define SPIN_FAIL(what) __trap()
DEVINL uint32_t smem_u32(const void* p) { return (uint32_t)__cvta_generic_to_shared(p); }
DEVINL void mbar_init(uint32_t bar, uint32_t cnt) { asm volatile("mbarrier.init.shared::cta.b64 [%0], %1;" ::"r"(bar), "r"(cnt) : "memory"); }
DEVINL void mbar_expect_tx(uint32_t bar, uint32_t bytes) { asm volatile("mbarrier.arrive.expect_tx.shared::cta.b64 _, [%0], %1;" ::"r"(bar), "r"(bytes) : "memory"); }
DEVINL void mbar_arrive(uint32_t bar) { asm volatile("mbarrier.arrive.shared::cta.b64 _, [%0];" ::"r"(bar) : "memory"); }
DEVINL void mbar_arrive_cluster(uint32_t bar) { asm volatile("mbarrier.arrive.shared::cluster.b64 _, [%0];" ::"r"(bar) : "memory"); }
DEVINL uint32_t mapa(uint32_t a, uint32_t cta) { uint32_t r; asm("mapa.shared::cluster.u32 %0, %1, %2;" : "=r"(r) : "r"(a), "r"(cta)); return r; }
DEVINL void mbar_wait(uint32_t bar, uint32_t parity) {
  asm volatile("{\n.reg .pred p;\n.reg .u32 c;\nmov.u32 c, 0;\n"
               "LW:\nmbarrier.try_wait.parity.shared::cta.b64 p, [%0], %1;\n@p bra LD;\n"
               "add.u32 c, c, 1;\nsetp.lt.u32 p, c, 4194304;\n@p bra LW;\ntrap;\nLD:\n}" ::"r"(bar), "r"(parity) : "memory");
}
DEVINL void fence_async_smem() { asm volatile("fence.proxy.async.shared::cta;" ::: "memory"); }
DEVINL void fence_async_global() { asm volatile("fence.proxy.async.global;" ::: "memory"); }
DEVINL void fence_gpu() { asm volatile("fence.acq_rel.gpu;" ::: "memory"); }
template <int ID, int N> DEVINL void named_bar() { asm volatile("bar.sync %0, %1;" ::"n"(ID), "n"(N) : "memory"); }
template <int ID, int N> DEVINL void named_arrive() { asm volatile("bar.arrive %0, %1;" ::"n"(ID), "n"(N) : "memory"); }

DEVINL void tma_2d(uint32_t dst, const CUtensorMap* m, int x, int y, uint32_t bar) {
  asm volatile("cp.async.bulk.tensor.2d.shared::cluster.global.mbarrier::complete_tx::bytes [%0], [%1, {%3, %4}], [%2];"
               ::"r"(dst), "l"(m), "r"(bar), "r"(x), "r"(y) : "memory");
}
DEVINL void tma_2d_hint(uint32_t dst, const CUtensorMap* m, int x, int y, uint32_t bar, uint64_t pol) {
  asm volatile("cp.async.bulk.tensor.2d.shared::cluster.global.mbarrier::complete_tx::bytes.L2::cache_hint [%0], [%1, {%3, %4}], [%2], %5;"
               ::"r"(dst), "l"(m), "r"(bar), "r"(x), "r"(y), "l"(pol) : "memory");
}
DEVINL void tma_3d(uint32_t dst, const CUtensorMap* m, int x, int y, int z, uint32_t bar) {
  asm volatile("cp.async.bulk.tensor.3d.shared::cluster.global.mbarrier::complete_tx::bytes [%0], [%1, {%3, %4, %5}], [%2];"
               ::"r"(dst), "l"(m), "r"(bar), "r"(x), "r"(y), "r"(z) : "memory");
}
DEVINL void tma_store_2d(const CUtensorMap* m, uint32_t src, int x, int y) {
  asm volatile("cp.async.bulk.tensor.2d.global.shared::cta.bulk_group [%0, {%2, %3}], [%1];" ::"l"(m), "r"(src), "r"(x), "r"(y) : "memory");
}
DEVINL void bulk_load(uint32_t dst, const void* src, uint32_t bytes, uint32_t bar) {
  asm volatile("cp.async.bulk.shared::cluster.global.mbarrier::complete_tx::bytes [%0], [%1], %2, [%3];" ::"r"(dst), "l"(src), "r"(bytes), "r"(bar) : "memory");
}
DEVINL void bulk_store(void* dst, uint32_t src, uint32_t bytes) {
  asm volatile("cp.async.bulk.global.shared::cta.bulk_group [%0], [%1], %2;" ::"l"(dst), "r"(src), "r"(bytes) : "memory");
}
DEVINL void pf_bulk(const void* p, uint32_t bytes) { asm volatile("cp.async.bulk.prefetch.L2.global [%0], %1;" ::"l"(p), "r"(bytes) : "memory"); }
DEVINL void pf_bulk_hint(const void* p, uint32_t bytes, uint64_t pol) {
  asm volatile("cp.async.bulk.prefetch.L2.global.L2::cache_hint [%0], %1, %2;" ::"l"(p), "r"(bytes), "l"(pol) : "memory");
}
DEVINL void pf_2d(const CUtensorMap* m, int x, int y) {
  asm volatile("cp.async.bulk.prefetch.tensor.2d.L2.global [%0, {%1, %2}];" ::"l"(m), "r"(x), "r"(y) : "memory");
}
DEVINL void bulk_commit() { asm volatile("cp.async.bulk.commit_group;" ::: "memory"); }
template <int N> DEVINL void bulk_wait() { asm volatile("cp.async.bulk.wait_group %0;" ::"n"(N) : "memory"); }
template <int N> DEVINL void bulk_wait_read() { asm volatile("cp.async.bulk.wait_group.read %0;" ::"n"(N) : "memory"); }
DEVINL void prefetch_tmap(const CUtensorMap* m) { asm volatile("prefetch.tensormap [%0];" ::"l"(m) : "memory"); }

DEVINL void wg_fence() { asm volatile("wgmma.fence.sync.aligned;" ::: "memory"); }
DEVINL void wg_commit() { asm volatile("wgmma.commit_group.sync.aligned;" ::: "memory"); }
template <int N> DEVINL void wg_wait() { asm volatile("wgmma.wait_group.sync.aligned %0;" ::"n"(N) : "memory"); }

DEVINL uint64_t make_desc(uint32_t addr, uint32_t lbo, uint32_t sbo) {
  return (uint64_t)((addr & 0x3FFFF) >> 4) | ((uint64_t)(lbo >> 4) << 16) | ((uint64_t)(sbo >> 4) << 32) | ((uint64_t)1 << 62);
}

#define R8(a, o) "+f"(a[o]), "+f"(a[o + 1]), "+f"(a[o + 2]), "+f"(a[o + 3]), "+f"(a[o + 4]), "+f"(a[o + 5]), "+f"(a[o + 6]), "+f"(a[o + 7])
#define R128(a) R8(a, 0), R8(a, 8), R8(a, 16), R8(a, 24), R8(a, 32), R8(a, 40), R8(a, 48), R8(a, 56), \
                R8(a, 64), R8(a, 72), R8(a, 80), R8(a, 88), R8(a, 96), R8(a, 104), R8(a, 112), R8(a, 120)
template <int TB>
DEVINL void wgmma_n256(float (&d)[128], uint64_t da, uint64_t db, int scale_d) {
  asm volatile(
      "{\n.reg .pred p;\nsetp.ne.b32 p, %130, 0;\n"
      "wgmma.mma_async.sync.aligned.m64n256k16.f32.bf16.bf16 "
      "{%0, %1, %2, %3, %4, %5, %6, %7, %8, %9, %10, %11, %12, %13, %14, %15, "
      "%16, %17, %18, %19, %20, %21, %22, %23, %24, %25, %26, %27, %28, %29, %30, %31, "
      "%32, %33, %34, %35, %36, %37, %38, %39, %40, %41, %42, %43, %44, %45, %46, %47, "
      "%48, %49, %50, %51, %52, %53, %54, %55, %56, %57, %58, %59, %60, %61, %62, %63, "
      "%64, %65, %66, %67, %68, %69, %70, %71, %72, %73, %74, %75, %76, %77, %78, %79, "
      "%80, %81, %82, %83, %84, %85, %86, %87, %88, %89, %90, %91, %92, %93, %94, %95, "
      "%96, %97, %98, %99, %100, %101, %102, %103, %104, %105, %106, %107, %108, %109, %110, %111, "
      "%112, %113, %114, %115, %116, %117, %118, %119, %120, %121, %122, %123, %124, %125, %126, %127}, "
      "%128, %129, p, 1, 1, 0, %131;\n}\n"
      : R128(d)
      : "l"(da), "l"(db), "r"(scale_d), "n"(TB));
}
DEVINL void reg_fence128(float (&a)[128]) {
#pragma unroll
  for (int i = 0; i < 128; i++) asm volatile("" : "+f"(a[i])::"memory");
}

DEVINL uint32_t pack_bf16(float lo, float hi) {
  uint32_t r;
  asm("cvt.rn.bf16x2.f32 %0, %1, %2;" : "=r"(r) : "f"(hi), "f"(lo));
  return r;
}
DEVINL uint32_t fma_bf2(uint32_t a, uint32_t b, uint32_t c) { uint32_t r; asm("fma.rn.bf16x2 %0, %1, %2, %3;" : "=r"(r) : "r"(a), "r"(b), "r"(c)); return r; }
DEVINL uint32_t mul_bf2(uint32_t a, uint32_t b) { uint32_t r; asm("mul.rn.bf16x2 %0, %1, %2;" : "=r"(r) : "r"(a), "r"(b)); return r; }
DEVINL uint32_t add_bf2(uint32_t a, uint32_t b) { uint32_t r; asm("add.rn.bf16x2 %0, %1, %2;" : "=r"(r) : "r"(a), "r"(b)); return r; }
DEVINL uint32_t add1_bf2(uint32_t a) { return fma_bf2(a, 0x3F803F80u, 0x3F803F80u); }
DEVINL float bf_lo(uint32_t w) { return __uint_as_float(w << 16); }
DEVINL float bf_hi(uint32_t w) { return __uint_as_float(w & 0xFFFF0000u); }
DEVINL float round_bf16(float v) { return __bfloat162float(__float2bfloat16_rn(v)); }
DEVINL float sigmoid_f(float v) { float r; asm("rcp.approx.ftz.f32 %0, %1;" : "=f"(r) : "f"(1.f + __expf(-v))); return r; }
DEVINL float silu_f(float v) { return v * sigmoid_f(v); }
DEVINL void stsm_x4(uint32_t addr, uint32_t r0, uint32_t r1, uint32_t r2, uint32_t r3) {
  asm volatile("stmatrix.sync.aligned.m8n8.x4.shared.b16 [%0], {%1, %2, %3, %4};" ::"r"(addr), "r"(r0), "r"(r1), "r"(r2), "r"(r3) : "memory");
}
DEVINL void ldsm_x4(uint32_t addr, uint32_t& r0, uint32_t& r1, uint32_t& r2, uint32_t& r3) {
  asm volatile("ldmatrix.sync.aligned.m8n8.x4.shared.b16 {%0, %1, %2, %3}, [%4];" : "=r"(r0), "=r"(r1), "=r"(r2), "=r"(r3) : "r"(addr) : "memory");
}
DEVINL void ldsm_x4_t(uint32_t addr, uint32_t& r0, uint32_t& r1, uint32_t& r2, uint32_t& r3) {
  asm volatile("ldmatrix.sync.aligned.m8n8.x4.trans.shared.b16 {%0, %1, %2, %3}, [%4];" : "=r"(r0), "=r"(r1), "=r"(r2), "=r"(r3) : "r"(addr) : "memory");
}
DEVINL void mma_16816(float (&c)[4], uint32_t a0, uint32_t a1, uint32_t a2, uint32_t a3, uint32_t b0, uint32_t b1) {
  asm("mma.sync.aligned.m16n8k16.row.col.f32.bf16.bf16.f32 {%0, %1, %2, %3}, {%4, %5, %6, %7}, {%8, %9}, {%0, %1, %2, %3};"
      : "+f"(c[0]), "+f"(c[1]), "+f"(c[2]), "+f"(c[3]) : "r"(a0), "r"(a1), "r"(a2), "r"(a3), "r"(b0), "r"(b1));
}
DEVINL void mma_1688(float (&c)[4], uint32_t a0, uint32_t a1, uint32_t b0) {
  asm("mma.sync.aligned.m16n8k8.row.col.f32.bf16.bf16.f32 {%0, %1, %2, %3}, {%4, %5}, {%6}, {%0, %1, %2, %3};"
      : "+f"(c[0]), "+f"(c[1]), "+f"(c[2]), "+f"(c[3]) : "r"(a0), "r"(a1), "r"(b0));
}
DEVINL float4 lds128(uint32_t a) { float4 v; asm volatile("ld.shared.v4.f32 {%0, %1, %2, %3}, [%4];" : "=f"(v.x), "=f"(v.y), "=f"(v.z), "=f"(v.w) : "r"(a)); return v; }
DEVINL uint4 lds128u(uint32_t a) { uint4 v; asm volatile("ld.shared.v4.u32 {%0, %1, %2, %3}, [%4];" : "=r"(v.x), "=r"(v.y), "=r"(v.z), "=r"(v.w) : "r"(a)); return v; }
DEVINL float2 lds64(uint32_t a) { float2 v; asm volatile("ld.shared.v2.f32 {%0, %1}, [%2];" : "=f"(v.x), "=f"(v.y) : "r"(a)); return v; }
DEVINL uint2 lds64u(uint32_t a) { uint2 v; asm volatile("ld.shared.v2.u32 {%0, %1}, [%2];" : "=r"(v.x), "=r"(v.y) : "r"(a)); return v; }
DEVINL float lds32(uint32_t a) { float v; asm volatile("ld.shared.f32 %0, [%1];" : "=f"(v) : "r"(a)); return v; }
DEVINL float lds16f(uint32_t a) { uint32_t v; asm volatile("ld.shared.u16 %0, [%1];" : "=r"(v) : "r"(a)); return __uint_as_float(v << 16); }
DEVINL uint32_t lds32u(uint32_t a) { uint32_t v; asm volatile("ld.shared.u32 %0, [%1];" : "=r"(v) : "r"(a)); return v; }
DEVINL void sts128(uint32_t a, float x, float y, float z, float w) { asm volatile("st.shared.v4.f32 [%0], {%1, %2, %3, %4};" ::"r"(a), "f"(x), "f"(y), "f"(z), "f"(w) : "memory"); }
DEVINL void sts128u(uint32_t a, uint32_t x, uint32_t y, uint32_t z, uint32_t w) { asm volatile("st.shared.v4.u32 [%0], {%1, %2, %3, %4};" ::"r"(a), "r"(x), "r"(y), "r"(z), "r"(w) : "memory"); }
DEVINL void sts64(uint32_t a, float x, float y) { asm volatile("st.shared.v2.f32 [%0], {%1, %2};" ::"r"(a), "f"(x), "f"(y) : "memory"); }
DEVINL void sts64u(uint32_t a, uint32_t x, uint32_t y) { asm volatile("st.shared.v2.u32 [%0], {%1, %2};" ::"r"(a), "r"(x), "r"(y) : "memory"); }
DEVINL void sts32(uint32_t a, float v) { asm volatile("st.shared.f32 [%0], %1;" ::"r"(a), "f"(v) : "memory"); }
DEVINL void sts32u(uint32_t a, uint32_t v) { asm volatile("st.shared.u32 [%0], %1;" ::"r"(a), "r"(v) : "memory"); }

DEVINL uint4 ld_msg(const uint4* p) {
  unsigned long long a, b;
  asm volatile("{\n.reg .b128 r;\nld.relaxed.gpu.global.b128 r, [%2];\nmov.b128 {%0, %1}, r;\n}" : "=l"(a), "=l"(b) : "l"(p) : "memory");
  return make_uint4((uint32_t)a, (uint32_t)(a >> 32), (uint32_t)b, (uint32_t)(b >> 32));
}
DEVINL void st_msg(uint4* p, uint32_t x, uint32_t y, uint32_t z, uint32_t w) {
  unsigned long long a = (unsigned long long)x | ((unsigned long long)y << 32), b = (unsigned long long)z | ((unsigned long long)w << 32);
  asm volatile("{\n.reg .b128 r;\nmov.b128 r, {%1, %2};\nst.relaxed.gpu.global.b128 [%0], r;\n}" ::"l"(p), "l"(a), "l"(b) : "memory");
}
DEVINL uint2 ld_msg8(const void* p) {
  unsigned long long a;
  asm volatile("ld.relaxed.gpu.global.b64 %0, [%1];" : "=l"(a) : "l"(p) : "memory");
  return make_uint2((uint32_t)a, (uint32_t)(a >> 32));
}
DEVINL void st_msg8(uint2* p, uint32_t x, uint32_t y) {
  asm volatile("st.relaxed.gpu.global.b64 [%0], %1;" ::"l"(p), "l"((unsigned long long)x | ((unsigned long long)y << 32)) : "memory");
}
DEVINL unsigned ld_rlx(const void* p) { unsigned v; asm volatile("ld.relaxed.gpu.global.u32 %0, [%1];" : "=r"(v) : "l"(p) : "memory"); return v; }
DEVINL void st_rlx(unsigned* p, unsigned v) { asm volatile("st.relaxed.gpu.global.u32 [%0], %1;" ::"l"(p), "r"(v) : "memory"); }
DEVINL void red_add(unsigned* p, unsigned v) { asm volatile("red.relaxed.gpu.global.add.u32 [%0], %1;" ::"l"(p), "r"(v) : "memory"); }
DEVINL void red_max8(uint2* p, uint32_t lo, uint32_t hi) {
  asm volatile("red.relaxed.gpu.global.max.u64 [%0], %1;" ::"l"(p), "l"((unsigned long long)lo | ((unsigned long long)hi << 32)) : "memory");
}
DEVINL void red_add_release(unsigned* p, unsigned v) { asm volatile("red.release.gpu.global.add.u32 [%0], %1;" ::"l"(p), "r"(v) : "memory"); }
DEVINL uint4 ldg_nc(const void* p) {
  uint4 v;
  asm volatile("ld.global.nc.L1::no_allocate.v4.u32 {%0, %1, %2, %3}, [%4];" : "=r"(v.x), "=r"(v.y), "=r"(v.z), "=r"(v.w) : "l"(p));
  return v;
}
DEVINL uint4 ldg128(const void* p) {
  uint4 v;
  asm volatile("ld.global.v4.u32 {%0, %1, %2, %3}, [%4];" : "=r"(v.x), "=r"(v.y), "=r"(v.z), "=r"(v.w) : "l"(p) : "memory");
  return v;
}
DEVINL void stg128(void* p, uint4 v) { asm volatile("st.global.v4.u32 [%0], {%1, %2, %3, %4};" ::"l"(p), "r"(v.x), "r"(v.y), "r"(v.z), "r"(v.w) : "memory"); }
DEVINL uint32_t landed(uint32_t readback, uint32_t zero) { return __reduce_or_sync(~0u, readback & zero); }
DEVINL uint32_t clk() { uint32_t c; asm volatile("mov.u32 %0, %%clock;" : "=r"(c)); return c; }
DEVINL void delay_until(uint32_t c0, uint32_t cycles) { while (clk() - c0 < cycles) {} }

#define TRACE(id)
#define TRACE_CLK(id)

DEVINL const char* piece_addr(const Ptrs& pp, int b, int i) {
  if (i >= 20) return pp.wdn + (size_t)b * 57344 + (i - 20) * 8192;
  if ((i >> 2) == 2) return (b < 64 ? pp.wd_re : pp.wd_im) + (size_t)(b & 63) * 32768 + (i & 3) * 8192;
  return (i < 4 || (i >> 2) == 3 ? pp.wg : pp.wu) + (size_t)((i < 8 ? ((i & 3) ^ 2) * 128 : 512 + (i & 3) * 128) + b) * (2 * F_);
}

DEVINL uint32_t dn_box(int i) { return i == 0 ? STAGE + 2 * SLOT : i == 3 ? SPARE : 2 * STAGE + i * SLOT; }
DEVINL int sibling(int m4, int r) {
  return r < 2 ? m4 ^ r : ((m4 & 2) ^ 2) + r - 2;
}

DEVINL uint32_t fkey(float v, int row) {
  const uint32_t u = __float_as_uint(v);
  return (((u & 0x80000000u) ? ~u : (u | 0x80000000u)) & ~2047u) | (uint32_t)(2047 - row);
}
DEVINL int key_row(uint32_t k) { return 2047 - (int)(k & 2047u); }
DEVINL float key_val(uint32_t k) { k = (k & ~2047u) | 1024u; return __uint_as_float((k & 0x80000000u) ? (k & 0x7FFFFFFFu) : ~k); }
DEVINL uint32_t redux_max(uint32_t v) { uint32_t r; asm volatile("redux.sync.max.u32 %0, %1, 0xffffffff;" : "=r"(r) : "r"(v)); return r; }
DEVINL void warp_top2(uint32_t ka, uint32_t kb, uint32_t& k1, uint32_t& k2) {
  k1 = redux_max(ka);
  k2 = redux_max(ka == k1 ? kb : ka);
}
DEVINL int sel_slot(uint2 sel, int n) {
  const int bA = key_row(sel.x) >> 6, bB = key_row(sel.y) >> 6;
  return n ? bB * 2 + (bA == bB ? 1 : 0) : bA * 2;
}

DEVINL void ln_stats(const uint4 (&w)[4], float (&v)[32], float& rstd, float& nmr) {
#pragma unroll
  for (int i = 0; i < 4; i++) {
    v[8 * i + 0] = bf_lo(w[i].x); v[8 * i + 1] = bf_hi(w[i].x); v[8 * i + 2] = bf_lo(w[i].y); v[8 * i + 3] = bf_hi(w[i].y);
    v[8 * i + 4] = bf_lo(w[i].z); v[8 * i + 5] = bf_hi(w[i].z); v[8 * i + 6] = bf_lo(w[i].w); v[8 * i + 7] = bf_hi(w[i].w);
  }
  float s[4] = {0.f, 0.f, 0.f, 0.f}, q[4] = {0.f, 0.f, 0.f, 0.f};
#pragma unroll
  for (int i = 0; i < 32; i++) { s[i & 3] += v[i]; q[i & 3] = fmaf(v[i], v[i], q[i & 3]); }
  rstd = (s[0] + s[1]) + (s[2] + s[3]); nmr = (q[0] + q[1]) + (q[2] + q[3]);
}
DEVINL void ln_apply(uint4 (&w)[4], const float (&v)[32], float sum, float sq) {
#pragma unroll
  for (int o = 16; o; o >>= 1) { sum += __shfl_xor_sync(~0u, sum, o); sq += __shfl_xor_sync(~0u, sq, o); }
  const float mean = sum * (1.f / D_);
  const float rstd = rsqrtf(fmaxf(fmaf(-mean, mean, sq * (1.f / D_)), 0.f) + 1e-5f), nmr = -mean * rstd;
#pragma unroll
  for (int i = 0; i < 4; i++) {
    w[i].x = pack_bf16(fmaf(v[8 * i], rstd, nmr), fmaf(v[8 * i + 1], rstd, nmr)); w[i].y = pack_bf16(fmaf(v[8 * i + 2], rstd, nmr), fmaf(v[8 * i + 3], rstd, nmr));
    w[i].z = pack_bf16(fmaf(v[8 * i + 4], rstd, nmr), fmaf(v[8 * i + 5], rstd, nmr)); w[i].w = pack_bf16(fmaf(v[8 * i + 6], rstd, nmr), fmaf(v[8 * i + 7], rstd, nmr));
  }
}
DEVINL void ln_row(uint4 (&w)[4]) { float v[32], s, q; ln_stats(w, v, s, q); ln_apply(w, v, s, q); }
DEVINL float sum8(uint4 u) { return ((bf_lo(u.x) + bf_hi(u.x)) + (bf_lo(u.y) + bf_hi(u.y))) + ((bf_lo(u.z) + bf_hi(u.z)) + (bf_lo(u.w) + bf_hi(u.w))); }

template <int R> DEVINL void take_box(uint32_t (&wf)[128], uint32_t box, int lane) {
  const int kr = (lane & 7) + (lane >> 4) * 8;
  const uint32_t base = box + kr * 64, sw = (uint32_t)((kr >> 1) & 3), hb = (uint32_t)((lane >> 3) & 1);
#pragma unroll
  for (int mt = 0; mt < 2; mt++) {
    const uint32_t ad = base + (((mt * 2 + hb) ^ sw) << 4);
#pragma unroll
    for (int ks = 0; ks < 8; ks++) {
      const int o = (ks * 4 + R * 2 + mt) * 4;
      ldsm_x4_t(ad + ks * 1024, wf[o], wf[o + 1], wf[o + 2], wf[o + 3]);
    }
  }
}
DEVINL void gate_up(const Ptrs& pp, uint32_t (&wf)[128], uint32_t sb, uint32_t scr, int ksl, int lane) {
  const uint2 sel = lds64u(sb + SEL_OFF);
  const int gq = lane >> 2, q4 = lane & 3;
  const uint4* src = &pp.mail->rowh[sel_slot(sel, gq & 1) * 128 + ksl * 16 + q4];
  uint4 bf[4];
  int it = 0;
#pragma unroll
  for (int u = 0; u < 4; u++) bf[u] = FK_E3WEAK ? ldg128(src + u * 4) : ld_msg(src + u * 4);
  while (!__all_sync(~0u, bf[0].x != SENT && bf[1].x != SENT && bf[2].x != SENT && bf[3].x != SENT)) {
#pragma unroll
    for (int u = 0; u < 4; u++) bf[u] = ld_msg(src + u * 4);
    if (++it > SPIN_LIMIT) SPIN_FAIL(0x207);
  }
  if (lane == 0 && ksl == 4) TRACE(20);
  float acc[8][4];
#pragma unroll
  for (int i = 0; i < 8; i++) { acc[i][0] = acc[i][1] = acc[i][2] = acc[i][3] = 0.f; }
#pragma unroll
  for (int u = 0; u < 4; u++)
#pragma unroll
    for (int mt = 0; mt < 4; mt++) {
      const int o = (2 * u * 4 + mt) * 4;
      mma_16816(acc[mt], wf[o], wf[o + 1], wf[o + 2], wf[o + 3], bf[u].x, bf[u].y);
      mma_16816(acc[4 + mt], wf[o + 16], wf[o + 17], wf[o + 18], wf[o + 19], bf[u].z, bf[u].w);
    }
  if (q4 == 0) {
    const uint32_t pb = scr + PART_REL + ksl * 512 + gq * 8;
#pragma unroll
    for (int mt = 0; mt < 4; mt++) {
      sts64(pb + mt * 128, acc[mt][0] + acc[4 + mt][0], acc[mt][1] + acc[4 + mt][1]);
      sts64(pb + mt * 128 + 64, acc[mt][2] + acc[4 + mt][2], acc[mt][3] + acc[4 + mt][3]);
    }
  }
  named_arrive<4, 384>();
}

struct OutTab { float G[8], H[8]; };
DEVINL void out_tab(OutTab& tb, uint4 cb, uint4 sv, uint4 gb) {
  const uint32_t c4[4] = {cb.x, cb.y, cb.z, cb.w}, s4[4] = {sv.x, sv.y, sv.z, sv.w}, g4[4] = {gb.x, gb.y, gb.z, gb.w};
#pragma unroll
  for (int u = 0; u < 4; u++) {
    const uint32_t A = add1_bf2(c4[u]);
    tb.G[2 * u] = bf_lo(g4[u]) * bf_lo(A); tb.G[2 * u + 1] = bf_hi(g4[u]) * bf_hi(A);
    tb.H[2 * u] = bf_lo(g4[u]) * bf_lo(s4[u]); tb.H[2 * u + 1] = bf_hi(g4[u]) * bf_hi(s4[u]);
  }
}
DEVINL void out_rows(const OutTab& tb, uint32_t sb, uint32_t scr, int r, uint32_t mask, int lane, char* dst) {
  const float4 st = lds128(scr + RST_REL + r * 8);
  uint4 v[2];
#pragma unroll
  for (int k = 0; k < 2; k++) v[k] = lds128u(sb + XST_OFF + (r + k) * 512 + ((lane ^ ((r + k) & 7)) << 4));
#pragma unroll
  for (int k = 0; k < 2; k++) {
    const float rs = k ? st.z : st.x, nm = k ? st.w : st.y;
    const uint32_t x4[4] = {v[k].x, v[k].y, v[k].z, v[k].w};
    uint32_t o[4];
#pragma unroll
    for (int u = 0; u < 4; u++)
      o[u] = pack_bf16(fmaf(fmaf(bf_lo(x4[u]), rs, nm), tb.G[2 * u], bf_lo(x4[u]) + tb.H[2 * u]),
                       fmaf(fmaf(bf_hi(x4[u]), rs, nm), tb.G[2 * u + 1], bf_hi(x4[u]) + tb.H[2 * u + 1]));
    if ((mask >> k) & 1) stg128(dst + (size_t)(r + k) * (2 * D_), make_uint4(o[0], o[1], o[2], o[3]));
  }
}
DEVINL void out_group(const OutTab& tb, uint32_t sb, uint32_t scr, int r0, uint32_t mask, int lane, char* dst, uint32_t pace) {
#pragma unroll 1
  for (int r = r0; mask; r += 2, mask >>= 2) {
    if (!(mask & 3)) continue;
    const uint32_t cn = clk();
    out_rows(tb, sb, scr, r, mask, lane, dst);
    if (mask >> 2) delay_until(cn, pace);
  }
}
DEVINL uint32_t row_bit(uint32_t key, int g0) { const unsigned r = (unsigned)(key_row(key) - g0); return r < 16 ? 1u << r : 0u; }

template <int TB, int G0, int G1>
DEVINL void gemm_phase(const Ptrs& pp, float (&acc)[128], uint32_t sb, int cw, bool lag, bool elect, uint32_t rel) {
  const uint32_t bars = sb + BAR_OFF;
#pragma unroll 1
  for (int g = G0; g < G1; g++) {
    const int s = g & 3;
    mbar_wait(bars + (B_FULL + s) * 8, (g >> 2) & 1);
    const bool hold = lag && g == G1 - (TB ? FK_L1 : FK_L2);
    if (hold) {
      wg_wait<0>();
      if (rel) mbar_arrive_cluster(rel + ((g - 1) & 3) * 8);
      mbar_wait(bars + B_STAG * 8, TB ? 0 : 1);
    }
    const uint32_t sa = sb + s * STAGE;
    const uint64_t da = make_desc(sa + cw * 8192, 16, 1024), db = make_desc(sa + SLOT, TB ? 8192 : 16, 1024);
    constexpr int KB = TB ? 128 : 2;
    wg_fence();
    wgmma_n256<TB>(acc, da, db, g > G0);
    wgmma_n256<TB>(acc, da + 2, db + KB, 1);
    wg_commit();
    wg_wait<1>();
    if (rel && g > G0 && !hold) mbar_arrive_cluster(rel + ((g - 1) & 3) * 8);
    if (!TB && g == G1 - 1 && !lag && elect) mbar_arrive_cluster(mapa(bars + B_PEER * 8, cw));
    wg_fence();
    wgmma_n256<TB>(acc, da + 4, db + 2 * KB, 1);
    wgmma_n256<TB>(acc, da + 6, db + 3 * KB, 1);
    wg_commit();
  }
  if (!lag) {
    wg_wait<1>();
    if (elect) mbar_arrive(bars + B_STAG * 8);
  }
}
DEVINL void gemm_finish(float (&acc)[128], uint32_t rel) {
  wg_wait<0>();
  reg_fence128(acc);
  if (rel) mbar_arrive_cluster(rel + 24);
}

__global__ void __launch_bounds__(384, 1)
fused_kernel(const Ptrs pp, const __grid_constant__ Maps maps) {
  extern __shared__ __align__(1024) uint8_t smem_raw[];
  const uint32_t c0 = clk();
  if (threadIdx.x == 0 && blockIdx.x >= NEXTRA) TRACE(0);
  const uint32_t sb = smem_u32(smem_raw);
  const int tid = threadIdx.x, lane = tid & 31;
  const int warp = __shfl_sync(~0u, tid >> 5, 0);
  const int rb = (int)blockIdx.x + pp.b0;
  const uint32_t bars = sb + BAR_OFF;
  auto BAR = [&](int i) { return bars + i * 8; };

  if (rb < 0) {
    const uint32_t ring = sb + warp * 16384, rbar = sb + MISC + warp * 64;
    const int row0 = FK_GX * 128 + ((rb + NEXTRA) * 12 + warp) * 2;
    if (lane == 0) {
#pragma unroll 1
      for (int i = 0; i < 4; i++) mbar_init(rbar + i * 8, 1);
      asm volatile("fence.mbarrier_init.release.cluster;" ::: "memory");
      delay_until(c0, FK_XDLY);
#pragma unroll 1
      for (int i = 0; i < FK_XDEPTH; i++) { mbar_expect_tx(rbar + i * 8, 4096); bulk_load(ring + i * 4096, pp.x + (size_t)(row0 + 96 * i) * (2 * D_), 4096, rbar + i * 8); }
    }
    __syncwarp();
    int row = row0;
#pragma unroll 1
    for (int it = 0; row < S_; it++, row += 96) {
      const uint32_t st = ring + (it & 3) * 4096;
      mbar_wait(rbar + (it & 3) * 8, (it >> 2) & 1);
      uint4 w[4], w2[4];
#pragma unroll
      for (int i = 0; i < 4; i++) { w[i] = lds128u(st + lane * 16 + i * 512); w2[i] = lds128u(st + 2048 + lane * 16 + i * 512); }
      ln_row(w);
      uint32_t rbk = 0;
      if (it) {
        if (lane == 0) bulk_wait<0>();
        __syncwarp();
        rbk = ld_rlx(pp.n + (size_t)(row - 96) * (2 * D_) + lane * 128);
      }
      ln_row(w2);
#pragma unroll
      for (int i = 0; i < 4; i++) { sts128u(st + lane * 16 + i * 512, w[i].x, w[i].y, w[i].z, w[i].w); sts128u(st + 2048 + lane * 16 + i * 512, w2[i].x, w2[i].y, w2[i].z, w2[i].w); }
      fence_async_smem();
      const uint32_t z = landed(rbk, pp.zero);
      if (lane == 0) {
        if (it) red_add(&pp.cnt[((row - 96) >> 7) * 32], 2 + z);
        bulk_store(pp.n + (size_t)row * (2 * D_), st, 4096); bulk_commit();
        if (row + 96 * FK_XDEPTH < S_) {
          const int sn = (it + FK_XDEPTH) & 3;
          mbar_expect_tx(rbar + sn * 8, 4096); bulk_load(ring + sn * 4096, pp.x + (size_t)(row + 96 * FK_XDEPTH) * (2 * D_), 4096, rbar + sn * 8);
        }
      }
      __syncwarp();
    }
    if (lane == 0) bulk_wait<0>();
    __syncwarp();
    const uint32_t z = landed(ld_rlx(pp.n + (size_t)(row - 96) * (2 * D_) + lane * 128), pp.zero);
    if (lane == 0) red_add(&pp.cnt[((row - 96) >> 7) * 32], 2 + z);
    return;
  }
  if (warp > 4) asm volatile("barrier.cluster.arrive.relaxed.aligned;" ::: "memory");
  if ((unsigned)(warp - 4) < FK_G0) {
    const int row = (warp - 4) * 128 + rb;
    uint4 w[4];
    if (warp > 4) delay_until(c0, warp == 5 ? FK_ROW1DLY : warp < 8 ? FK_ROW2DLY : FK_ROW4DLY);
#pragma unroll
    for (int i = 0; i < 4; i++) w[i] = ldg_nc(pp.x + (size_t)row * (2 * D_) + lane * 16 + i * 512);
    if (warp == 4) asm volatile("barrier.cluster.arrive.relaxed.aligned;" ::: "memory");
    const bool first = warp < 6;
    uint32_t pm = 0, par = 0;
    if (first) {
      par = ld_rlx(&pp.cnt[17 * 32]) + 1;
      pm = (lane & 7) ? 0u : 1u;
      const uint32_t z = landed(w[0].x | w[1].x | w[2].x | w[3].x | par, pp.zero);
      if (lane == 0) { red_add(&pp.cnt[(warp - 4) * 32], 1 + z); if (warp == 4) TRACE(1); }
    }
    ln_row(w);
    char* dst = pp.n + (size_t)row * (2 * D_);
#pragma unroll
    for (int i = 0; i < 4; i++) { w[i].x = (w[i].x & ~pm) | (par & pm); stg128(dst + lane * 16 + i * 512, w[i]); }
    if (tid == 128) TRACE(31);
    if (lane == 0 && warp == 3 + FK_G0) TRACE(55);
    if (!first) { if (warp < 8) named_arrive<8, 96>(); else named_arrive<9, 32 * (FK_G0 - 3)>(); }
  }
  int m4, t;
  {
    const int c = (rb >> 1) - 2;
    int g = 8, i = c + 2;
    if (c >= 32) { i = ((c - 32) * 37) >> 8; g = c - 32 - 7 * i; g += g >= 2; i += 4; }
    else if (c >= 0) { g = c & 7; i = c >> 3; }
    if (g == 8) { g = 2; i += 6; } else if (i == 8) { i = 4 + g; g = 2; }
    m4 = (g >> 2) * 2 + (i & 1); t = (g & 3) * 4 + (i >> 1);
  }
  const int j = rb & 1, b = t * 8 + m4 * 2 + j;
  const int blk = t * 2 + j;
  const uint32_t scr = sb + 2 * STAGE + j * 8192;
  if (warp < 4) {
    uint32_t tag = ld_rlx(&pp.cnt[17 * 32]);
    auto ws_touch = [&](int o) {
      uint32_t v;
      asm volatile("ld.global.nc.L1::no_allocate.L2::128B.u32 %0, [%1];" : "=r"(v)
                   : "l"((j ? pp.ws_im : pp.ws_re) + (size_t)(t * 128 + m4 * 32 + lane) * (2 * S_) + o));
      return v;
    };
    uint32_t early = 0;
    if (warp == 1) { delay_until(c0, FK_WS0DLY); early = ws_touch(0); if (lane == 0) TRACE(126); }
    if (warp == 0) early = ld_rlx(&pp.cnt[(lane & 1) * 32]);
    if (lane == 0) {
      if (warp < 2) {
        if (warp == 0) {
          prefetch_tmap(&maps.ws[j]); prefetch_tmap(&maps.n);
          if (sb & 1023) __trap();
#pragma unroll
          for (int i = 0; i < 8; i++) mbar_init(BAR(i), bar_count(i));
        } else {
#pragma unroll
          for (int i = 8; i < 22; i++) mbar_init(BAR(i), bar_count(i));
        }
      } else if (warp == 2) {
#pragma unroll
        for (int i = 22; i < 36; i++) mbar_init(BAR(i), bar_count(i));
      } else {
#pragma unroll
        for (int i = 36; i < B_NUM; i++) mbar_init(BAR(i), bar_count(i));
#pragma unroll
        for (int i = 0; i < 4; i++) mbar_expect_tx(BAR(B_RECV + i), 8192);
      }
      asm volatile("fence.mbarrier_init.release.cluster;" ::: "memory");
    }
    named_bar<6, 128>();
    named_arrive<0, 256>(); named_arrive<3, 256>();
    asm volatile("barrier.cluster.arrive.relaxed.aligned;" ::: "memory");
    uint64_t pol_first;
    asm volatile("createpolicy.fractional.L2::evict_first.b64 %0, 1.0;" : "=l"(pol_first));
    const bool moe = b < NMOE;
    uint32_t wf[128];
    auto take = [&](auto R) {
      constexpr int r = decltype(R)::value;
      const uint32_t box = sb + SPARE + warp * 8192;
      if (moe || r == 0) mbar_wait(BAR(B_WB + warp), r);
      if (moe) take_box<r>(wf, box, lane);
      fence_async_smem();
      __syncwarp();
      if (lane == 0) {
        if (r) { mbar_expect_tx(BAR(B_X), 8192); tma_2d(box, &maps.x, m4 * 256 + warp * 64, t * 128 + j * 64, BAR(B_X)); }
        else if (moe) { mbar_expect_tx(BAR(B_WB + warp), 8192); tma_2d_hint(box, &maps.wu, b * 32, warp * 128, BAR(B_WB + warp), pol_first); }
      }
      __syncwarp();
    };

    if (warp == 0) {
      auto loadA = [&](int g) {
        mbar_expect_tx(BAR(B_FULL + (g & 3)), SLOT);
        tma_2d_hint(sb + (g & 3) * STAGE, &maps.ws[j], g * 64, t * 128, BAR(B_FULL + (g & 3)), pol_first);
      };
      auto loadB = [&](int g, int bar) { mbar_expect_tx(BAR(bar + (g & 3)), 2 * SLOT); tma_3d(sb + (g & 3) * STAGE + SLOT, &maps.n, 0, g * 64, m4 * 4, BAR(bar + (g & 3))); };
      delay_until(c0, FK_ADLY);
      if (lane == 0) { loadA(0); if (FK_A1EARLY) loadA(1); TRACE(63); }
      asm volatile("add.u32 %0, %0, 1;" : "+r"(tag)::"memory");
#pragma unroll 1
      for (int gi = 0; gi < 2; gi++) {
        int it = 0;
        const unsigned* cp = &pp.cnt[(lane & 1) * 32];
        while (true) {
          delay_until(clk(), FK_PGAP);
          const uint32_t e2 = ld_rlx(cp);
          if ((__ballot_sync(~0u, (int)(early - tag * 128u) >= 0) >> gi) & 1) break;
          delay_until(clk(), FK_PGAP);
          early = ld_rlx(cp);
          if ((__ballot_sync(~0u, (int)(e2 - tag * 128u) >= 0) >> gi) & 1) break;
          if (++it > SPIN_LIMIT) SPIN_FAIL(0x201);
        }
        if (lane == 0) {
          if (gi == 0) TRACE(2);
          loadB(2 * gi, B_LAND);
          if (gi) loadA(2);
          if (gi || !FK_A1EARLY) loadA(2 * gi + 1);
          loadB(2 * gi + 1, B_LAND);
        }
        __syncwarp();
      }
      if (lane == 0) { prefetch_tmap(&maps.p); prefetch_tmap(&maps.wd[j]); }
      const unsigned tgt = tag * 128u;
      unsigned pend = ld_rlx(&pp.cnt[2 * 32]);
      const char* pfa = piece_addr(pp, b, lane);
      const uint32_t pfn = (lane >> 2) == 2 || lane >= 20 ? 8192 : 7168;
      auto produce1 = [&](int g0, int g1) {
#pragma unroll 1
        for (int g = g0; g < g1; g++) {
          mbar_wait(BAR(B_EMPTYH + (g & 3)), ((g >> 2) - 1) & 1);
          mbar_wait(BAR(B_EMPTY + (g & 3)), ((g >> 2) - 1) & 1);
          if (!(g & 1)) {
            if ((int)(pend - tgt) < 0) {
              int it = 0;
              while ((int)(ld_rlx(&pp.cnt[(g >> 1) * 32]) - tgt) < 0) { if (++it > SPIN_LIMIT) SPIN_FAIL(0x20c); }
            }
            fence_async_global();
            pend = ld_rlx(&pp.cnt[((g >> 1) + 1) * 32]);
          }
          if (lane == 0) {
            loadA(g); loadB(g, B_FULL);
          }
          if (lane == g - FK_PF0 && lane >= FK_PFSKIP) pf_bulk(pfa, pfn);
          __syncwarp();
        }
      };
      produce1(4, FK_TG);
      take(IntC<0>{});
      produce1(FK_TG, FK_TU);
      take(IntC<1>{});
      produce1(FK_TU, 32);
      int sib = 0, pc = 0;
      auto produce2 = [&](int q0, int q1) {
#pragma unroll 1
        for (int q = q0; q < q1; q++) {
          const int s = q & 3, k0 = sibling(m4, sib) * 256 + pc * 64;
          const uint32_t sa = sb + s * STAGE;
          mbar_wait(BAR(B_EMPTY + s), ((q >> 2) + 1) & 1);
          if (lane == 0) {
            mbar_expect_tx(BAR(B_FULL + s), 2 * SLOT);
            tma_2d(sa + SLOT, &maps.wd[j], k0, m4 * 256, BAR(B_FULL + s));
            if (q < 4) mbar_arrive(BAR(B_FULL + s));
          }
          __syncwarp();
          if (q >= 4) {
            mbar_wait(BAR(B_PL + s), 0);
            if (lane == 0) { mbar_expect_tx(BAR(B_LAND + s), SLOT); tma_2d(sa, &maps.p, k0, j * S_ + t * 128, BAR(B_LAND + s)); }
            if (++sib == 4) { sib = 1; pc++; }
          } else if (++pc == 4) { pc = 0; sib = 1; }
          if (lane == 32 + q - FK_PF0 && lane < 27) pf_bulk(pfa, pfn);
          __syncwarp();
        }
      };
      produce2(0, 16);
      if (moe) {
        mbar_wait(BAR(B_EMPTY + 0), 1);
        if (lane == 0) {
          mbar_expect_tx(BAR(B_GU), 49152);
#pragma unroll 1
          for (int i = 0; i < 3; i++) {
            tma_2d(sb + i * SLOT, &maps.wg, b * 32, 512 + i * 128, BAR(B_GU));
            tma_2d(sb + i * SLOT + 8192, &maps.wu, b * 32, 512 + i * 128, BAR(B_GU));
          }
        }
        mbar_wait(BAR(B_EMPTY + 1), 1);
        if (FK_WGATE >= 0) mbar_wait(BAR(B_RECV + FK_WGATE), 0);
        if (lane == 0) {
          mbar_expect_tx(BAR(B_GU), 16384);
          tma_2d(sb + STAGE + SLOT, &maps.wg, b * 32, 896, BAR(B_GU));
          tma_2d(sb + STAGE + SLOT + 8192, &maps.wu, b * 32, 896, BAR(B_GU));
        }
#pragma unroll 1
        for (int i = 0; i < 4; i++) {
          if (i == 1) mbar_wait(BAR(B_EMPTY + 2), 1);
          if (i == 3) mbar_wait(BAR(B_XDONE), 0);
          if (i >= FK_DNWIN) mbar_wait(BAR(B_DN + i - FK_DNWIN), 0);
          if (lane == 0) {
            mbar_expect_tx(BAR(B_DN + i), 16384);
            tma_3d(sb + dn_box(i), &maps.wdn, 0, b * 32, i * 4, BAR(B_DN + i));
          }
        }
      }
      __syncwarp();
    } else if (warp == 1) {
      asm volatile("add.u32 %0, %0, 1;" : "+r"(tag)::"memory");
      if (lane == 0) prefetch_tmap(&maps.ps);
      delay_until(c0, FK_WS1DLY);
      float a0 = __uint_as_float(early & pp.zero), a1 = __uint_as_float(ws_touch(128) & pp.zero);
      auto rowsum = [&](int g0, int g1) {
        const uint32_t rb = sb + (m4 * 32 + lane) * 128 + ((lane & 7) << 4);
#pragma unroll 1
        for (int g = g0; g < g1; g++) {
          const int s = g & 3;
          mbar_wait(BAR(B_FULL + s), (g >> 2) & 1);
          uint4 u[8];
#pragma unroll
          for (int c = 0; c < 8; c++) u[c] = lds128u((rb ^ (uint32_t)(c << 4)) + s * STAGE);
#pragma unroll
          for (int c = 0; c < 8; c += 2) { a0 += sum8(u[c]); a1 += sum8(u[c + 1]); }
          if (lane == 0) mbar_arrive(BAR(B_EMPTYH + s) + ((__float_as_uint(a0) | __float_as_uint(a1)) & pp.zero));
        }
      };
      rowsum(0, FK_TG - 2);
      take(IntC<0>{});
      rowsum(FK_TG - 2, 28);
      mbar_wait(BAR(B_MODOK), 0);
      a0 += lds32(sb + RS_OFF + 256 + lane * 4);
      __syncwarp();
      uint2* rsp = &pp.mail->rs[(j * 16 + t) * 128 + lane];
      st_msg8(rsp + m4 * 32, __float_as_uint(a0 + a1), tag);
      {
        uint2 m[4]; int it = 0;
        while (true) {
#pragma unroll
          for (int i = 0; i < 4; i++) m[i] = ld_msg8(rsp + 32 * i);
          if (__all_sync(~0u, m[0].y == tag && m[1].y == tag && m[2].y == tag && m[3].y == tag)) break;
          if (++it > SPIN_LIMIT) SPIN_FAIL(0x208);
        }
#pragma unroll
        for (int i = 0; i < 4; i++) sts32u(sb + RS_OFF + (lane + 32 * i) * 4, pack_bf16(__uint_as_float(m[i].x), __uint_as_float(m[i].x)));
      }
      __syncwarp();
      if (lane == 0) { mbar_arrive(BAR(B_T1)); TRACE(11); }
      take(IntC<1>{});
      {
        uint32_t cn = 0;
#pragma unroll 1
        for (int i = 0; i < 8; i++) {
          const int q = i >> 1, half = (i & 1) ? j : 1 - j;
          if (i < 4) mbar_wait(BAR(B_PRDY + (i & 1) * 2 + q), 0);
          if (i) delay_until(cn, FK_PPACE);
          cn = clk();
          if (lane == 0) {
            tma_store_2d(&maps.ps, sb + q * STAGE + half * 8192, m4 * 256 + q * 64, j * S_ + t * 128 + half * 64);
            bulk_commit();
            if (i && !(i & 1)) { bulk_wait_read<1>(); mbar_arrive(BAR(B_PL + q - 1)); }
          }
          __syncwarp();
        }
        if (lane == 0) { bulk_wait_read<0>(); mbar_arrive(BAR(B_PL + 3)); }
        if (lane == 0) TRACE(8);
      }
      named_bar<7, 64>();
      delay_until(clk(), FK_E2DLY);
      const uint2* cp = &pp.mail->cand[lane];
      auto select = [&](uint2 m) {
        if (!__all_sync(~0u, m.y != 0)) return false;
        uint32_t k1, k2;
        warp_top2(m.y, m.x, k1, k2);
        if (lane == 0) { sts64u(sb + SEL_OFF, k1, k2); mbar_arrive(BAR(B_SEL)); TRACE(19); }
        return true;
      };
      int it = 0;
      while (!select(ld_msg8(cp))) { delay_until(clk(), -(FK_E2GAP)); if (++it > SPIN_LIMIT) SPIN_FAIL(0x206); }
    } else {
      const int kh = warp - 2;
      const uint32_t reg = sb + SPARE + kh * 16384;
      const uint4 cw0 = ldg_nc(pp.c + (kh * 64 + lane) * 16), cw1 = ldg_nc(pp.c + (kh * 64 + lane + 32) * 16);
#pragma unroll 1
      for (int i = 0; i < 2; i++) {
        const uint4 cw4 = i ? cw1 : cw0;
        const uint32_t ad = reg + 12288 + (lane + 32 * i) * 32;
        sts128(ad, round_bf16(silu_f(bf_lo(cw4.x))), round_bf16(silu_f(bf_hi(cw4.x))), round_bf16(silu_f(bf_lo(cw4.y))), round_bf16(silu_f(bf_hi(cw4.y))));
        sts128(ad + 16, round_bf16(silu_f(bf_lo(cw4.z))), round_bf16(silu_f(bf_hi(cw4.z))), round_bf16(silu_f(bf_lo(cw4.w))), round_bf16(silu_f(bf_hi(cw4.w))));
      }
      asm volatile("add.u32 %0, %0, 1;" : "+r"(tag)::"memory");
      if (lane == 0) prefetch_tmap(&maps.wm);
      unsigned ph = 0;
      if (kh == 0) {
#pragma unroll 1
        for (int s = 0; s < 4; s++) {
          const uint32_t ra = sb + s * STAGE + SLOT + lane * 128 + ((lane & 7) << 4);
          int it = 0;
          while (true) {
            mbar_wait(BAR(B_LAND + s), (ph >> s) & 1);
            ph ^= 1u << s;
            if (lane == 0 && it == 0) TRACE(120 + s);
            uint32_t bad = 0;
#pragma unroll
            for (int u = 0; u < 8; u++) bad |= lds32u(ra + u * 4096) ^ tag;
            if (!__any_sync(~0u, bad & 1)) break;
            if (lane == 0) { mbar_expect_tx(BAR(B_LAND + s), 2 * SLOT); tma_3d(sb + s * STAGE + SLOT, &maps.n, 0, s * 64, m4 * 4, BAR(B_LAND + s)); TRACE(92 + s); }
            if (++it > (1 << 16)) SPIN_FAIL(0x203);
          }
          if (lane == 0) mbar_arrive(BAR(B_FULL + s));
        }
      } else {
        named_bar<8, 96>();
        uint32_t rbk = ld_rlx(pp.n + (size_t)((2 + (lane >> 4)) * 128 + rb) * (2 * D_) + (lane & 15) * 128);
        uint4 w[FK_GX - FK_G0][4];
        delay_until(c0, FK_ROW8DLY);
#pragma unroll
        for (int k = 0; k < FK_GX - FK_G0; k++)
#pragma unroll
          for (int i = 0; i < 4; i++) w[k][i] = ldg_nc(pp.x + (size_t)((FK_G0 + k) * 128 + rb) * (2 * D_) + lane * 16 + i * 512);
        uint32_t z = landed(rbk, pp.zero);
        if (lane < 2) red_add(&pp.cnt[(2 + lane) * 32], 1 + z);
        named_bar<9, 32 * (FK_G0 - 3)>();
        rbk = 0;
#pragma unroll
        for (int g = 4; g < FK_G0; g += 2) rbk |= ld_rlx(pp.n + (size_t)(min(g + (lane >> 4), FK_G0 - 1) * 128 + rb) * (2 * D_) + (lane & 15) * 128);
        z = landed(rbk, pp.zero);
        if (lane >= 4 && lane < FK_G0) red_add(&pp.cnt[lane * 32], 1 + z);
#pragma unroll
        for (int k = 0; k < FK_GX - FK_G0; k++) {
          ln_row(w[k]);
#pragma unroll
          for (int i = 0; i < 4; i++) stg128(pp.n + (size_t)((FK_G0 + k) * 128 + rb) * (2 * D_) + lane * 16 + i * 512, w[k][i]);
        }
        z = landed(ld_rlx(pp.n + (size_t)(min(FK_G0 + (lane >> 4), FK_GX - 1) * 128 + rb) * (2 * D_) + (lane & 15) * 128), pp.zero);
        if (lane >= FK_G0 && lane < FK_GX) red_add(&pp.cnt[lane * 32], 1 + z);
        if (lane == 0) TRACE(56);
      }
      {
        float acc[3][8];
        uint32_t sad[3];
#pragma unroll
        for (int a = 0; a < 3; a++) {
          sad[a] = reg + 12288 + ((32 * a + lane) / 6) * 4;
#pragma unroll
          for (int i = 0; i < 8; i++) acc[a][i] = 0.f;
        }
        const char* wpf = pp.wm + (size_t)kh * (512 * 12 * D_) + b * 6144;
        const char* wsrc = (j ? pp.ws_im : pp.ws_re) + (size_t)(t * 128 + m4 * 32 + kh * 16 - 16) * (2 * S_) + 28 * 128 + lane * 16;
        if (FK_WMPF && lane == 0) pf_bulk(wpf, 6144);
        uint32_t cn = c0 + FK_GSTART + kh * (FK_PACE / 2);
        auto request = [&](int c) {
          mbar_expect_tx(BAR(B_WM + kh * 2 + (c & 1)), 6144 + ((__float_as_uint(acc[0][0]) | __float_as_uint(acc[1][0]) | __float_as_uint(acc[2][0])) & pp.zero));
          tma_2d_hint(reg + (c & 1) * 6144, &maps.wm, b * 48, kh * 512 + c * 64, BAR(B_WM + kh * 2 + (c & 1)), pol_first);
        };
        uint4 e[4];
#pragma unroll 1
        for (int c = -2; c < 8; c++) {
          while ((int)(clk() - cn) < 0) __nanosleep(40);
          cn += c < 0 ? FK_PACE0 : FK_PACE;
          if (lane == 0) {
            if (FK_WMPF && c < 5) pf_bulk(wpf + (size_t)(c + 3) * (64 * 12 * D_), 6144);
          }
          __syncwarp();
          if (c < 0) {
            if (lane == 0) request(c + 2);
            __syncwarp();
            continue;
          }
          if (c >= 4) {
            const float v0 = sum8(e[0]), v1 = sum8(e[1]), v2 = sum8(e[2]), v3 = sum8(e[3]);
            const bool u4 = lane & 16, u3 = lane & 8;
            const float w0 = (u4 ? v2 : v0) + __shfl_xor_sync(~0u, u4 ? v0 : v2, 16), w1 = (u4 ? v3 : v1) + __shfl_xor_sync(~0u, u4 ? v1 : v3, 16);
            float v = (u3 ? w1 : w0) + __shfl_xor_sync(~0u, u3 ? w0 : w1, 8);
            v += __shfl_xor_sync(~0u, v, 4); v += __shfl_xor_sync(~0u, v, 2); v += __shfl_xor_sync(~0u, v, 1);
            if (!(lane & 7)) sts32(sb + RS_OFF + 256 + (kh * 16 + c * 4 - 16 + (lane >> 3)) * 4, v);
          }
          if (c >= 3 && c < 7) {
#pragma unroll
            for (int i = 0; i < 4; i++) e[i] = ldg_nc(wsrc + (size_t)(c * 4 + 4 + i) * (2 * S_));
          }
          mbar_wait(BAR(B_WM + kh * 2 + (c & 1)), (c >> 1) & 1);
#pragma unroll
          for (int u = 0; u < 12; u++) {
            const uint4 v = lds128u(reg + (c & 1) * 6144 + lane * 16 + u * 512);
            const float sc = lds32(sad[u % 3] + (u / 3) * 64);
            float (&ac)[8] = acc[u % 3];
            ac[0] = fmaf(sc, bf_lo(v.x), ac[0]); ac[1] = fmaf(sc, bf_hi(v.x), ac[1]);
            ac[2] = fmaf(sc, bf_lo(v.y), ac[2]); ac[3] = fmaf(sc, bf_hi(v.y), ac[3]);
            ac[4] = fmaf(sc, bf_lo(v.z), ac[4]); ac[5] = fmaf(sc, bf_hi(v.z), ac[5]);
            ac[6] = fmaf(sc, bf_lo(v.w), ac[6]); ac[7] = fmaf(sc, bf_hi(v.w), ac[7]);
          }
#pragma unroll
          for (int a = 0; a < 3; a++) sad[a] += 256;
          __syncwarp();
          if (lane == 0 && c < 6) request(c + 2);
        }
        __syncwarp();
#pragma unroll
        for (int a = 0; a < 3; a++) {
          sts128(reg + (32 * a + lane) * 32, acc[a][0], acc[a][1], acc[a][2], acc[a][3]);
          sts128(reg + (32 * a + lane) * 32 + 16, acc[a][4], acc[a][5], acc[a][6], acc[a][7]);
        }
        __syncwarp();
        float s0 = 0.f, s1 = 0.f;
#pragma unroll 8
        for (int m = 0; m < 16; m++) { const float2 v = lds64(reg + (lane < 24 ? lane * 8 : 0) + m * 192); s0 += v.x; s1 += v.y; }
        if (kh == 0) sts64(sb + RS_OFF + lane * 8, s0, s1);
        if (lane == 0) TRACE(80 + kh);
        named_bar<5, 64>();
        if (kh == 1) {
          const float2 p = lds64(sb + RS_OFF + lane * 8);
          unsigned* dst = pp.mod + b * 24 + (lane < 24 ? lane : 0);
          if (lane < 24) st_rlx(dst, pack_bf16(s0 + p.x, s1 + p.y));
          uint32_t rbk = ld_rlx(dst);
          if (b == 0) { st_msg8(&pp.mail->cand[lane], 0, 0); rbk |= ld_rlx(&pp.mail->cand[lane]); }
          const uint32_t z = landed(rbk, pp.zero);
          if (lane == 0) { red_add(&pp.cnt[16 * 32], 1 + z); mbar_arrive(BAR(B_MODOK)); TRACE(9); }
          __syncwarp();
        }
      }
      if (kh == 0) {
        if (lane == 0) { mbar_arrive(BAR(B_MODOK)); TRACE(57); }
#pragma unroll 1
        for (int i = 0; i < 4; i++) {
          const int w = i ^ 2;
          if (lane == 0) {
            if (moe) { mbar_expect_tx(BAR(B_WB + w), 8192); tma_2d_hint(sb + SPARE + w * 8192, &maps.wg, b * 32, w * 128, BAR(B_WB + w), pol_first); }
            else mbar_arrive(BAR(B_WB + w));
          }
          __nanosleep(FK_BSLEEP);
        }
        take(IntC<0>{});
        take(IntC<1>{});
        if (lane == 0) TRACE(98);
        int sib = 1, pc = 0;
#pragma unroll 1
        for (int q = 4; q < 16; q++) {
          const int s = q & 3;
          const uint32_t ra = sb + s * STAGE + lane * 128 + ((lane & 7) << 4);
          int it = 0;
          while (true) {
            mbar_wait(BAR(B_LAND + s), (ph >> s) & 1);
            ph ^= 1u << s;
            const uint32_t bad = ((lds32u(ra) ^ tag) | (lds32u(ra + 4096) ^ tag) | (lds32u(ra + 8192) ^ tag) | (lds32u(ra + 12288) ^ tag)) & 1;
            if (!__any_sync(~0u, bad)) break;
            if (lane == 0) {
              mbar_expect_tx(BAR(B_LAND + s), SLOT);
              tma_2d(sb + s * STAGE, &maps.p, sibling(m4, sib) * 256 + pc * 64, j * S_ + t * 128, BAR(B_LAND + s));
            }
            if (++it > (1 << 16)) SPIN_FAIL(0x202);
          }
          if (lane == 0) mbar_arrive(BAR(B_FULL + s));
          if (++sib == 4) { sib = 1; pc++; }
        }
        if (lane == 0) TRACE(99);
      } else {
        take(IntC<0>{});
        {
          const unsigned tgt = tag * 128u; int it = 0;
          while ((int)(ld_rlx(&pp.cnt[16 * 32]) - tgt) < 0) { __nanosleep(100); if (++it > SPIN_LIMIT) SPIN_FAIL(0x204); }
        }
        if (lane == 0) TRACE(10);
        {
          const uint32_t sgn = j ? 0x80008000u : 0u;
          uint32_t sa[4], ca[4]; uint4 sv[4], cv[4], wr[4];
#pragma unroll
          for (int i = 0; i < 4; i++) {
            const int p = lane + 32 * i;
            sa[i] = ld_rlx(pp.mod + m4 * 128 + p); ca[i] = ld_rlx(pp.mod + 512 + m4 * 128 + p);
            sv[i] = ld_msg(reinterpret_cast<const uint4*>(pp.mod + 1536) + p); cv[i] = ld_msg(reinterpret_cast<const uint4*>(pp.mod + 2048) + p);
            wr[i] = ldg_nc(pp.wr + p * 16);
          }
          float c1 = 0.f, c2 = 0.f;
#pragma unroll
          for (int i = 0; i < 4; i++) {
            const int p = lane + 32 * i;
            sts64(sb + T1_OFF + ((p >> 3) * 4 + (p & 3)) * 16 + ((p >> 2) & 1) * 8, __uint_as_float(add1_bf2(ca[i]) ^ sgn), __uint_as_float(sa[i] ^ sgn));
            const uint32_t s4[4] = {sv[i].x, sv[i].y, sv[i].z, sv[i].w}, c4[4] = {cv[i].x, cv[i].y, cv[i].z, cv[i].w}, w4[4] = {wr[i].x, wr[i].y, wr[i].z, wr[i].w};
#pragma unroll
            for (int u = 0; u < 4; u++) {
              const uint32_t A = add1_bf2(c4[u]);
              c1 = fmaf(bf_lo(A), bf_lo(w4[u]), c1); c1 = fmaf(bf_hi(A), bf_hi(w4[u]), c1);
              c2 = fmaf(bf_lo(s4[u]), bf_lo(w4[u]), c2); c2 = fmaf(bf_hi(s4[u]), bf_hi(w4[u]), c2);
            }
          }
#pragma unroll
          for (int o = 16; o; o >>= 1) { c1 += __shfl_xor_sync(~0u, c1, o); c2 += __shfl_xor_sync(~0u, c2, o); }
          __syncwarp();
          if (lane == 0) { sts128(sb + CST_OFF, c1, c2, __uint_as_float(tag), 0.f); mbar_arrive(BAR(B_T1)); TRACE(30); }
        }
        take(IntC<1>{});
        const int G = lane >> 2, q = lane & 3, p0 = m4 * 128 + G * 16 + q;
        mbar_wait(BAR(B_PRDY + 1), 0);
        mbar_wait(BAR(B_PRDY + 3), 0);
        uint32_t ga[4], hi[4], lo[4];
#pragma unroll
        for (int u = 0; u < 4; u++) {
          ga[u] = ld_rlx(pp.mod + 1024 + p0 + 4 * u);
          const uint32_t cb = ld_rlx(pp.mod + 2048 + p0 + 4 * u), wr = __ldg(reinterpret_cast<const uint32_t*>(pp.wr) + p0 + 4 * u);
          const float w0 = bf_lo(add1_bf2(cb)) * bf_lo(wr), w1 = bf_hi(add1_bf2(cb)) * bf_hi(wr);
          hi[u] = pack_bf16(w0, w1);
          lo[u] = pack_bf16(w0 - bf_lo(hi[u]), w1 - bf_hi(hi[u]));
        }
        sts128u(sb + GA_OFF + lane * 16, ga[0], ga[1], ga[2], ga[3]);
        sts128u(sb + W_OFF + G * 144 + q * 16, hi[0], hi[1], hi[2], hi[3]);
        sts128u(sb + W_OFF + G * 144 + 64 + q * 16, lo[0], lo[1], lo[2], lo[3]);
        sts32u(sb + W_OFF + G * 144 + 128 + q * 4, 0x3F803F80u);
        mbar_wait(BAR(B_PL + 3), 0);
        __nanosleep(FK_RSLEEP);
        const uint4 sv = make_uint4(SENT, SENT, SENT, SENT);
#pragma unroll 1
        for (int i = 0; i < 7; i++) stg128(&pp.mail->part[(size_t)b * (NMOE * 2) + lane + 32 * i], sv);
#pragma unroll 1
        for (int i = 0; i < 2; i++) {
          stg128(&pp.mail->stats[(blk * 4 + m4) * 64 + lane + 32 * i], sv);
          stg128(&pp.mail->rowh[(blk * 2 + i) * 128 + m4 * 32 + lane], sv);
          stg128(&pp.mail->rowx[(blk * 2 + i) * 128 + m4 * 32 + lane], sv);
        }
        if (lane == 0) { red_max8(&pp.mail->cand[blk], 1, 0); red_add(&pp.cnt[18 * 32], 1); }
        __syncwarp();
        if (lane == 0) { fence_gpu(); mbar_arrive(BAR(B_T2)); TRACE(97); }
      }
    }
    mbar_wait(BAR(B_SEL), 0);
    if (moe) gate_up(pp, wf, sb, scr, warp, lane);
    if (warp == 1) {
      const uint2 sel = lds64u(sb + SEL_OFF);
      const int n = (lane >> 3) & 1;
      const int col = (b >> 4) * 128 + (lane & 1) * 64 + ((b >> 2) & 3) * 16 + (b & 3) * 2 + ((lane >> 1) & 1) + (lane >> 4) * 8;
      const int slot = sel_slot(sel, n) * 512, wofs = slot + ((col >> 5) * 4 + ((col >> 1) & 3)) * 4 + ((col >> 3) & 3);
      const uint32_t gbp = ld_rlx(pp.mod + 2560 + (col >> 1));
      uint32_t hp, xp; int it = 0;
      while (true) {
        hp = ld_rlx(reinterpret_cast<const uint32_t*>(pp.mail->rowh) + wofs); xp = ld_rlx(reinterpret_cast<const uint32_t*>(pp.mail->rowx) + slot + (col >> 1));
        if (__all_sync(~0u, hp != SENT && xp != SENT)) break;
        if (++it > SPIN_LIMIT) SPIN_FAIL(0x2ff);
      }
      const float sg = round_bf16(sigmoid_f(round_bf16(key_val(n ? sel.y : sel.x))));
      const int gq = lane >> 2;
      const uint32_t one = (lane & 1) == (gq >> 2) ? ((gq & 1) ? 0x3F800000u : 0x00003F80u) : 0u;
      const uint32_t s0 = (gq & 2) ? 0u : one, s1 = (gq & 2) ? one : 0u;
      const uint4* src = &pp.mail->part[(size_t)b * (NMOE * 2) + lane];
      uint4 m[7];
      it = 0;
      while ((int)(ld_rlx(&pp.cnt[18 * 32]) - tag * (NCTA + NMOE)) < 0) { if (++it > SPIN_LIMIT) SPIN_FAIL(0x20d); }
      delay_until(clk(), FK_E4DLY);
      it = 0;
      while (true) {
        bool ok = true;
#pragma unroll
        for (int i = 0; i < 7; i++) m[i] = ld_msg(src + 32 * i);
#pragma unroll
        for (int i = 0; i < 7; i++) ok &= m[i].x != SENT;
        if (__all_sync(~0u, ok)) break;
        if (++it > SPIN_LIMIT) SPIN_FAIL(0x20b);
      }
      if (lane == 0) TRACE(23);
      float c[3][4];
#pragma unroll
      for (int i = 0; i < 3; i++) { c[i][0] = c[i][1] = c[i][2] = c[i][3] = 0.f; }
#pragma unroll
      for (int i = 0; i < 7; i++) mma_16816(c[i % 3], m[i].x, m[i].y, m[i].z, m[i].w, s0, s1);
#pragma unroll
      for (int i = 0; i < 4; i++) c[0][i] += c[1][i] + c[2][i];
      const bool u4 = lane & 16, u3 = lane & 8;
      const float a0 = (u4 ? c[0][2] : c[0][0]) + __shfl_xor_sync(~0u, u4 ? c[0][0] : c[0][2], 16), a1 = (u4 ? c[0][3] : c[0][1]) + __shfl_xor_sync(~0u, u4 ? c[0][1] : c[0][3], 16);
      float y = (u3 ? a1 : a0) + __shfl_xor_sync(~0u, u3 ? a0 : a1, 8);
      y += __shfl_xor_sync(~0u, y, 4);
      const bool odd = col & 1;
      const float upd = round_bf16(round_bf16(y) * sg);
      const float o = fmaf(odd ? bf_hi(gbp) : bf_lo(gbp), (odd ? bf_hi(hp) : bf_lo(hp)) + upd, odd ? bf_hi(xp) : bf_lo(xp));
      if (!(lane & 4)) reinterpret_cast<__nv_bfloat16*>(pp.out)[(size_t)key_row(n ? sel.y : sel.x) * D_ + col] = __float2bfloat16_rn(o);
      if (lane == 0) { TRACE(24); TRACE_CLK(54); if (b == 0) pp.cnt[17 * 32] = tag; }
    }
  } else {
    const int cw = (warp - 4) >> 2;
    const int wq = warp & 3;
    const int wtid = tid & 127;
    const int gq = lane >> 2, q4 = lane & 3;
    const bool lag = cw == j;
    const bool elect = wtid == 0;
    const uint32_t rel = wtid < 2 ? mapa(BAR(B_EMPTY), wtid) : 0;

    if (cw) named_bar<3, 256>(); else named_bar<0, 256>();
    if (tid == 128) TRACE(124);
    asm volatile("barrier.cluster.wait.acquire.aligned;" ::: "memory");
    if (tid == 128) TRACE(125);

    const int mrow = wq * 16 + (lane & 7) + ((lane >> 3) & 1) * 8;
    {
      float acc[128];
      gemm_phase<1, 0, 32>(pp, acc, sb, cw, lag, elect, rel);
      mbar_wait(BAR(B_T1), 0);
      const uint32_t tad = sb + T1_OFF + q4 * 16;
      uint4 tb[16];
#pragma unroll
      for (int c = 0; c < 4; c++) tb[c] = lds128u(tad + c * 64);
      const uint32_t rs0 = lds32u(sb + RS_OFF + (cw * 64 + wq * 16 + gq) * 4), rs1 = lds32u(sb + RS_OFF + (cw * 64 + wq * 16 + gq + 8) * 4);
      const uint32_t dst = sb + cw * 8192 + mrow * 128, pb = BAR(B_PRDY + (lag ? 2 : 0));
      const uint32_t pmask = q4 ? 0u : 1u, par = lds32u(sb + CST_OFF + 8);
      gemm_finish(acc, rel);
      if (elect) { TRACE(lag ? 5 : 4); if (lag) TRACE_CLK(51); }
#pragma unroll
      for (int i = 0; i < 16; i++) {
        uint32_t r[4];
        const int o = 8 * i;
        r[0] = fma_bf2(pack_bf16(acc[o], acc[o + 1]), tb[i].x, mul_bf2(rs0, tb[i].y));
        r[1] = fma_bf2(pack_bf16(acc[o + 2], acc[o + 3]), tb[i].x, mul_bf2(rs1, tb[i].y));
        r[2] = fma_bf2(pack_bf16(acc[o + 4], acc[o + 5]), tb[i].z, mul_bf2(rs0, tb[i].w));
        r[3] = fma_bf2(pack_bf16(acc[o + 6], acc[o + 7]), tb[i].z, mul_bf2(rs1, tb[i].w));
        if (!(i & 3)) { r[0] = (r[0] & ~pmask) | (par & pmask); r[1] = (r[1] & ~pmask) | (par & pmask); }
        if (i < 12) tb[i + 4] = lds128u(tad + (i + 4) * 64);
        stsm_x4(dst + (i >> 2) * STAGE + (uint32_t)(((((2 * i) & 7) + (lane >> 4)) ^ (lane & 7)) << 4), r[0], r[1], r[2], r[3]);
        if (i == 3 || i == 15) {
          fence_async_smem();
          __syncwarp();
          if (lane == 0) mbar_arrive(pb + (i >> 3) * 8);
        }
      }
      mbar_wait(pb + 8, 0);
    }
    if (elect) TRACE(lag ? 7 : 6);
    float acc[128];
    gemm_phase<0, 32, 48>(pp, acc, sb, cw, lag, elect, rel);

    if (!lag) {
      const uint32_t rdst = mapa(sb + STAGE + j * 8192 + wtid * 16, j ^ 1), rbar = mapa(BAR(B_RECV), j ^ 1);
      mbar_wait(BAR(B_PEER), 0);
      gemm_finish(acc, rel);
      if (elect) { mbar_arrive_cluster(rbar + (B_PEER + 1 - B_RECV) * 8); TRACE(12); }
#pragma unroll
      for (int i = 0; i < 16; i++) {
        const int o = 8 * i;
        if (i == 8) mbar_wait(BAR(B_PEER + 1), 0);
        if (i == 12) mbar_wait(BAR(B_EMPTY + 1), 1);
        asm volatile("st.async.weak.shared::cluster.mbarrier::complete_tx::bytes.v4.b32 [%0], {%1, %2, %3, %4}, [%5];"
                     ::"r"(i < 12 ? rdst + (i >> 2) * STAGE + (i & 3) * 2048 : rdst + (1 - 2 * j) * 8192 + (i & 3) * 2048),
                       "r"(pack_bf16(acc[o], acc[o + 1])), "r"(pack_bf16(acc[o + 2], acc[o + 3])), "r"(pack_bf16(acc[o + 4], acc[o + 5])),
                       "r"(pack_bf16(acc[o + 6], acc[o + 7])), "r"(rbar + (i >> 2) * 8) : "memory");
      }
      if (elect) TRACE(13);
      if (b < NMOE) {
        uint32_t wf[128];
        named_bar<1, 256>();
        mbar_wait(BAR(B_GU), 0);
        const uint32_t box = sb + (wq < 3 ? wq : 4) * SLOT;
        take_box<0>(wf, box, lane);
        take_box<1>(wf, box + 8192, lane);
        if (elect) TRACE(26);
        mbar_wait(BAR(B_SEL), 0);
        gate_up(pp, wf, sb, scr, 4 + wq, lane);
      }
      OutTab tb;
      {
        const uint4* mp = reinterpret_cast<const uint4*>(pp.mod) + m4 * 32 + lane;
        out_tab(tb, ldg128(mp + 512), ldg128(mp + 384), ldg128(mp + 640));
      }
      mbar_wait(BAR(B_SEL), 0);
      const uint2 sel = lds64u(sb + SEL_OFF), cnd = lds64u(sb + TOP_OFF + 32);
      char* odst = pp.out + (size_t)blk * (64 * 2 * D_) + m4 * 512 + lane * 16;
      const int g0 = blk * 64 + wq * 16;
      out_group(tb, sb, scr, wq * 16, ((0xFFFFu & (0xFFFFu << FK_OSPLIT)) | row_bit(cnd.x, g0) | row_bit(cnd.y, g0)) & ~(row_bit(sel.x, g0) | row_bit(sel.y, g0)),
                lane, odst, FK_OPACE2);
      if (elect) TRACE(28);
    } else {
      mbar_wait(BAR(B_T2), 0);
      uint32_t xa[64];
      float dl[2][4], dq[4][4];
#pragma unroll
      for (int i = 0; i < 4; i++) { dl[0][i] = dl[1][i] = dq[0][i] = dq[1][i] = dq[2][i] = dq[3][i] = 0.f; }
      {
        uint32_t wad = sb + W_OFF + ((gq & 2) ? 128 : (gq & 1) * 64 + q4 * 16), gad = sb + GA_OFF + q4 * 16;
        uint32_t rsrc = sb + STAGE + (1 - j) * 8192 + wtid * 16, xad = sb + SPARE + mrow * 128 + (uint32_t)(((lane >> 4) ^ (lane & 7)) << 4);
        asm volatile("" : "+r"(wad), "+r"(gad), "+r"(rsrc), "+r"(xad));
        uint4 rv[16], wb[8], ga[8];
        uint32_t xf[16][4];
        auto loadx = [&](int i) { ldsm_x4((xad ^ (uint32_t)((i & 3) << 5)) + (i >> 2) * 8192, xf[i][0], xf[i][1], xf[i][2], xf[i][3]); };
        auto loadr = [&](int i) { rv[i] = lds128u(i < 12 ? rsrc + (i >> 2) * STAGE + (i & 3) * 2048 : rsrc + (2 * j - 1) * 8192 + (i & 3) * 2048); };
        auto loadt = [&](int h) { loadx(2 * h); loadx(2 * h + 1); ga[h] = lds128u(gad + h * 64); wb[h] = lds128u(wad + h * 144); };
        mbar_wait(BAR(B_X), 0);
        mbar_wait(BAR(B_RECV), 0);
        loadx(0); loadr(0); ga[0] = lds128u(gad);
        mbar_wait(BAR(B_RECV + 1), 0);
        gemm_finish(acc, rel);
        if (elect) { TRACE(14); TRACE_CLK(53); }
#pragma unroll
        for (int u = 0; u < 8 * FK_PK; u++) {
          xa[u] = pack_bf16(acc[2 * u], acc[2 * u + 1]);
          if (u == 15) { loadx(1); loadr(1); wb[0] = lds128u(wad); }
        }
#pragma unroll
        for (int h = 0; h < 8; h++) {
          if (h == FK_W2 || h == 6) mbar_wait(BAR(B_RECV + (h == 6 ? 3 : 2)), 0);
          if (h == 6) { loadr(12); loadr(13); }
          if (h < 7) loadt(h + 1);
          if (h < 7 && h != 5) { loadr(2 * h + 2); loadr(2 * h + 3); }
          if (h + FK_PK < 8) {
#pragma unroll
            for (int u = 8 * (h + FK_PK); u < 8 * (h + FK_PK) + 8; u++) xa[u] = pack_bf16(acc[2 * u], acc[2 * u + 1]);
          }
#pragma unroll
          for (int i = 2 * h; i < 2 * h + 2; i++) {
            const uint32_t g0 = (i & 1) ? ga[h].z : ga[h].x, g1 = (i & 1) ? ga[h].w : ga[h].y;
            const uint32_t a0 = fma_bf2(g0, add_bf2(xa[4 * i], rv[i].x), xf[i][0]), a1 = fma_bf2(g0, add_bf2(xa[4 * i + 1], rv[i].y), xf[i][1]);
            const uint32_t a2 = fma_bf2(g1, add_bf2(xa[4 * i + 2], rv[i].z), xf[i][2]), a3 = fma_bf2(g1, add_bf2(xa[4 * i + 3], rv[i].w), xf[i][3]);
            xa[4 * i] = a0; xa[4 * i + 1] = a1; xa[4 * i + 2] = a2; xa[4 * i + 3] = a3;
            mma_1688(dq[0], a0, a1, a0); mma_1688(dq[1], a0, a1, a1);
            mma_1688(dq[2 % FK_NQ], a2, a3, a2); mma_1688(dq[3 % FK_NQ], a2, a3, a3);
            mma_16816(dl[i & (FK_NL - 1)], a0, a1, a2, a3, (i & 1) ? wb[h].z : wb[h].x, (i & 1) ? wb[h].w : wb[h].y);
          }
        }
      }
      const float4 cst = lds128(sb + CST_OFF);
      const uint32_t tag = __float_as_uint(cst.z);
      uint4 own;
      {
        const bool odd = q4 & 1;
        const float l0 = dl[0][0] + dl[1][0], l1 = dl[0][1] + dl[1][1], l2 = dl[0][2] + dl[1][2], l3 = dl[0][3] + dl[1][3];
        const float mine = odd ? l2 : l0 + l1;
        const float other = __shfl_xor_sync(~0u, odd ? l0 : l2 + l3, 1);
        const int dsrc = (lane & ~3) | (gq >> 1);
        const float qa = __shfl_sync(~0u, (gq & 1) ? dq[0][1] + dq[2][1] : dq[0][0] + dq[2][0], dsrc);
        const float qb = __shfl_sync(~0u, (gq & 1) ? dq[1][3] + dq[3][3] : dq[1][2] + dq[3][2], dsrc);
        own = make_uint4(__float_as_uint(odd ? mine : other), __float_as_uint(odd ? qb : qa), __float_as_uint(odd ? other : mine), tag);
        if (q4 < 2) st_msg(&pp.mail->stats[(blk * 4 + m4) * 64 + wq * 16 + gq + 8 * q4], own.x, own.y, own.z, tag);
      }
      if (lane == 0) mbar_arrive(BAR(B_XDONE));
      if (elect) TRACE(15);
      const int srow = wq * 16 + gq + 8 * (q4 & 1);
      const uint4* src0 = &pp.mail->stats[(blk * 4 + (m4 ^ (q4 | 1))) * 64 + srow];
      const uint4* src1 = &pp.mail->stats[(blk * 4 + (m4 ^ 2)) * 64 + srow];
      if (FK_E1DLY) delay_until(clk(), FK_E1DLY);
      uint4 m0 = ld_msg(src0), m1 = own;
      if (q4 >= 2) m1 = ld_msg(src1);
      mbar_wait(BAR(B_EMPTY + 3), 1);
#pragma unroll
      for (int i = 0; i < 16; i++)
        stsm_x4(sb + XST_OFF + mrow * 512 + (i >> 2) * 128 + (uint32_t)(((((2 * i) & 7) + (lane >> 4)) ^ (lane & 7)) << 4), xa[4 * i], xa[4 * i + 1], xa[4 * i + 2], xa[4 * i + 3]);
      uint4 cbv, sbv, gbv;
      const uint4* mp = reinterpret_cast<const uint4*>(pp.mod) + m4 * 32 + lane;
      cbv = ldg128(mp + 512); sbv = ldg128(mp + 384); gbv = ldg128(mp + 640);
      uint32_t k1, k2;
      {
        int it = 0;
        while (!__all_sync(~0u, m0.w == tag && m1.w == tag)) {
          m0 = ld_msg(src0);
          if (q4 >= 2) m1 = ld_msg(src1);
          if (++it > SPIN_LIMIT) SPIN_FAIL(0x209);
        }
        if (elect) TRACE(16);
        float sa = __uint_as_float(m0.x) + __uint_as_float(m1.x), qa = __uint_as_float(m0.y) + __uint_as_float(m1.y), da = __uint_as_float(m0.z) + __uint_as_float(m1.z);
        sa += __shfl_xor_sync(~0u, sa, 2); qa += __shfl_xor_sync(~0u, qa, 2); da += __shfl_xor_sync(~0u, da, 2);
        const float mean = sa * (1.f / D_);
        const float rstd = rsqrtf(fmaxf(fmaf(-mean, mean, qa * (1.f / D_)), 0.f) + 1e-5f);
        const float rme = fmaf(rstd, fmaf(-mean, cst.x, da), cst.y);
        warp_top2(fkey(rme, blk * 64 + srow), 0u, k1, k2);
        if (lane == 0) sts64u(sb + TOP_OFF + wq * 8, k1, k2);
        if (q4 < 2) sts64(scr + RST_REL + srow * 8, rstd, -mean * rstd);
        named_bar<2, 128>();
        const uint2 c = lds64u(sb + TOP_OFF + (lane & 3) * 8);
        warp_top2(c.x, c.y, k1, k2);
        if (wq == 0) {
          if (lane == 0 && (FK_PUSHALL || m4 == (t & 3))) red_max8(&pp.mail->cand[blk], k2, k1);
          if (lane == 0) sts64u(sb + TOP_OFF + 32, k1, k2);
          named_arrive<7, 64>();
        }
      }
      if (b < NMOE) named_arrive<1, 256>();
      if (elect) TRACE(17);
      const int c1 = key_row(k1) - blk * 64, c2 = key_row(k2) - blk * 64;
      if (wq >= 2) {
        const int r = wq == 2 ? c1 : c2;
        const uint4 v = lds128u(sb + XST_OFF + r * 512 + ((lane ^ (r & 7)) << 4));
        const float2 st = lds64(scr + RST_REL + r * 8);
        auto h2 = [&](uint32_t xv, uint32_t cv, uint32_t sv) {
          const uint32_t av = add1_bf2(cv);
          return pack_bf16(fmaf(fmaf(bf_lo(xv), st.x, st.y), bf_lo(av), bf_lo(sv)), fmaf(fmaf(bf_hi(xv), st.x, st.y), bf_hi(av), bf_hi(sv)));
        };
        const uint32_t sc = scr + SCR_REL + wq * 512;
        sts128u(sc + lane * 16, h2(v.x, cbv.x, sbv.x), h2(v.y, cbv.y, sbv.y), h2(v.z, cbv.z, sbv.z), h2(v.w, cbv.w, sbv.w));
        __syncwarp();
        const uint32_t fa = sc + gq * 64 + q4 * 4;
        const int o = (blk * 2 + wq - 2) * 128 + m4 * 32 + lane;
        st_msg(&pp.mail->rowh[o], lds32u(fa), lds32u(fa + 16), lds32u(fa + 32), lds32u(fa + 48));
        st_msg(&pp.mail->rowx[o], v.x, v.y, v.z, v.w);
        if (lane == 0 && wq == 3) TRACE(18);
      }
      {
        OutTab tb;
        out_tab(tb, cbv, sbv, gbv);
        char* odst = pp.out + (size_t)blk * (64 * 2 * D_) + m4 * 512 + lane * 16;
        const int g0 = blk * 64 + wq * 16;
        out_group(tb, sb, scr, wq * 16, ((1u << FK_OSPLIT) - 1) & ~(row_bit(k1, g0) | row_bit(k2, g0)), lane, odst, FK_OPACE);
      }
      if (elect) TRACE(25);
      if (b < NMOE) {
        uint32_t wd[128];
        mbar_wait(BAR(B_DN + wq), 0);
        {
          const int fr = (lane & 7) + (lane >> 4) * 8;
          const uint32_t base = sb + dn_box(wq) + fr * 128;
#pragma unroll
          for (int c = 0; c < 4; c++) {
            const uint32_t ad = base + (((uint32_t)(c * 2 + ((lane >> 3) & 1)) ^ (uint32_t)(lane & 7)) << 4);
#pragma unroll
            for (int gI = 0; gI < 4; gI++)
#pragma unroll
              for (int ks = 0; ks < 2; ks++) {
                const int o = ((gI * 4 + c) * 2 + ks) * 4;
                ldsm_x4_t(ad + gI * 4096 + ks * 2048, wd[o], wd[o + 1], wd[o + 2], wd[o + 3]);
              }
          }
        }
        uint4* dst = &pp.mail->part[((size_t)(wq * 32 + q4 * 4 + (gq >> 1)) * NMOE + b) * 2 + (gq & 1)];
        if (lane == 0 && wq == 3) TRACE(27);
        named_bar<4, 384>();
        if (wtid == 96) red_add(&pp.cnt[18 * 32], 1);
        if (elect) TRACE(21);
        float g0 = 0.f, g1 = 0.f, u0 = 0.f, u1 = 0.f;
#pragma unroll
        for (int w = 0; w < 8; w++) {
          const float2 gv = lds64(scr + PART_REL + w * 512 + lane * 8), uv = lds64(scr + PART_REL + w * 512 + 256 + lane * 8);
          g0 += gv.x; g1 += gv.y; u0 += uv.x; u1 += uv.y;
        }
        const uint32_t act = pack_bf16(round_bf16(silu_f(round_bf16(g0))) * round_bf16(u0), round_bf16(silu_f(round_bf16(g1))) * round_bf16(u1));
        uint32_t ab[4];
#pragma unroll
        for (int u = 0; u < 4; u++) {
          const uint32_t v0 = __shfl_sync(~0u, act, 8 * u + 2 * q4), v1 = __shfl_sync(~0u, act, 8 * u + 2 * q4 + 1);
          ab[u] = __byte_perm(v0, v1, (gq & 1) ? 0x7632 : 0x5410);
        }
        float c[4][4];
#pragma unroll
        for (int v = 0; v < 4; v++) { c[v][0] = c[v][1] = c[v][2] = c[v][3] = 0.f; }
#pragma unroll
        for (int q = 0; q < 4; q++) {
          const uint32_t mk = (gq >> 1) == q ? ~0u : 0u;
          const uint32_t b0 = ab[0] & mk, b1 = ab[1] & mk, b2 = ab[2] & mk, b3 = ab[3] & mk;
#pragma unroll
          for (int v = 0; v < 4; v++) { const int o = (4 * v + q) * 8; mma_16816(c[v], wd[o], wd[o + 1], wd[o + 2], wd[o + 3], b0, b1); }
#pragma unroll
          for (int v = 0; v < 4; v++) { const int o = (4 * v + q) * 8 + 4; mma_16816(c[v], wd[o], wd[o + 1], wd[o + 2], wd[o + 3], b2, b3); }
        }
#pragma unroll
        for (int u = 0; u < 2; u++)
          st_msg(dst + u * (16 * NMOE * 2), pack_bf16(c[2 * u][0], c[2 * u][1]), pack_bf16(c[2 * u][2], c[2 * u][3]),
                 pack_bf16(c[2 * u + 1][0], c[2 * u + 1][1]), pack_bf16(c[2 * u + 1][2], c[2 * u + 1][3]));
        if (elect) TRACE(22);
      }
    }
  }
}

typedef CUresult (*PFN_encodeTiled)(CUtensorMap*, CUtensorMapDataType, cuuint32_t, void*, const cuuint64_t*, const cuuint64_t*,
                                    const cuuint32_t*, const cuuint32_t*, CUtensorMapInterleave, CUtensorMapSwizzle,
                                    CUtensorMapL2promotion, CUtensorMapFloatOOBfill);

static void map2d(PFN_encodeTiled enc, CUtensorMap* m, const void* p, uint64_t rows, uint64_t cols, uint32_t brows, uint32_t bcols, CUtensorMapSwizzle sw,
                  CUtensorMapL2promotion pr = CU_TENSOR_MAP_L2_PROMOTION_L2_128B) {
  cuuint64_t dims[2] = {cols, rows}; cuuint64_t str[1] = {cols * 2}; cuuint32_t box[2] = {bcols, brows}; cuuint32_t es[2] = {1, 1};
  enc(m, CU_TENSOR_MAP_DATA_TYPE_BFLOAT16, 2, (void*)p, dims, str, box, es, CU_TENSOR_MAP_INTERLEAVE_NONE, sw, pr,
      CU_TENSOR_MAP_FLOAT_OOB_FILL_NONE);
}
static void map3d(PFN_encodeTiled enc, CUtensorMap* m, const void* p, uint64_t rows, uint64_t cols, uint32_t brows, uint32_t bgroups) {
  cuuint64_t dims[3] = {64, rows, cols / 64}; cuuint64_t str[2] = {cols * 2, 128}; cuuint32_t box[3] = {64, brows, bgroups}; cuuint32_t es[3] = {1, 1, 1};
  enc(m, CU_TENSOR_MAP_DATA_TYPE_BFLOAT16, 3, (void*)p, dims, str, box, es, CU_TENSOR_MAP_INTERLEAVE_NONE, CU_TENSOR_MAP_SWIZZLE_128B,
      CU_TENSOR_MAP_L2_PROMOTION_L2_128B, CU_TENSOR_MAP_FLOAT_OOB_FILL_NONE);
}

}

extern "C" void kernel_launch(void* const* d_in, const int* in_sizes, int n_in, void* d_out, int out_size) {
  using namespace fk;
  (void)in_sizes; (void)n_in; (void)out_size;
  static PFN_encodeTiled enc = nullptr;
  static int maxClusters = -1;
  static void *pn = nullptr, *pP = nullptr, *pc = nullptr, *pm = nullptr, *pmod = nullptr;
  if (!enc) {
    void* fn = nullptr; cudaDriverEntryPointQueryResult qr;
    cudaGetDriverEntryPoint("cuTensorMapEncodeTiled", &fn, cudaEnableDefault, &qr);
    enc = (PFN_encodeTiled)fn;
    cudaGetSymbolAddress(&pn, g_n);
    cudaGetSymbolAddress(&pP, g_P);
    cudaGetSymbolAddress(&pc, g_cnt);
    cudaGetSymbolAddress(&pm, g_mail);
    cudaGetSymbolAddress(&pmod, g_mod);
    cudaFuncSetAttribute(fused_kernel, cudaFuncAttributeMaxDynamicSharedMemorySize, SMEM_BYTES);
  }
  Maps maps;
  map2d(enc, &maps.ws[0], d_in[1], S_, S_, 128, 64, CU_TENSOR_MAP_SWIZZLE_128B);
  map2d(enc, &maps.ws[1], d_in[2], S_, S_, 128, 64, CU_TENSOR_MAP_SWIZZLE_128B);
  map3d(enc, &maps.n, pn, S_, D_, 64, 4);
  map2d(enc, &maps.p, pP, 2 * S_, D_, 128, 64, CU_TENSOR_MAP_SWIZZLE_128B);
  map2d(enc, &maps.ps, pP, 2 * S_, D_, 64, 64, CU_TENSOR_MAP_SWIZZLE_128B);
  map2d(enc, &maps.wd[0], d_in[3], D_, D_, 256, 64, CU_TENSOR_MAP_SWIZZLE_128B);
  map2d(enc, &maps.wd[1], d_in[4], D_, D_, 256, 64, CU_TENSOR_MAP_SWIZZLE_128B);
  map2d(enc, &maps.x, d_in[0], S_, D_, 64, 64, CU_TENSOR_MAP_SWIZZLE_128B);
  map2d(enc, &maps.wg, d_in[7], D_, F_, 128, 32, CU_TENSOR_MAP_SWIZZLE_64B);
  map2d(enc, &maps.wu, d_in[8], D_, F_, 128, 32, CU_TENSOR_MAP_SWIZZLE_64B);
  map3d(enc, &maps.wdn, d_in[9], F_, D_, 32, 4);
  map2d(enc, &maps.wm, d_in[11], D_, 6 * D_, 64, 48, CU_TENSOR_MAP_SWIZZLE_NONE);

  cudaLaunchConfig_t cfg = {};
  cfg.gridDim = dim3(NCTA); cfg.blockDim = dim3(384); cfg.dynamicSmemBytes = SMEM_BYTES; cfg.stream = cudaStreamPerThread;
  cudaLaunchAttribute at[1];
  at[0].id = cudaLaunchAttributeClusterDimension; at[0].val.clusterDim.x = 2; at[0].val.clusterDim.y = 1; at[0].val.clusterDim.z = 1;
  cfg.attrs = at; cfg.numAttrs = 1;
  Ptrs pp{(const char*)d_in[0], (char*)pn, (unsigned*)pc, 0, 0, (Mail*)pm, (uint32_t*)pmod, (const char*)d_in[10], (const char*)d_in[1], (const char*)d_in[2],
          (const char*)d_in[3], (const char*)d_in[4], (const char*)d_in[6], (const char*)d_in[7], (const char*)d_in[8], (const char*)d_in[9], (const char*)d_in[11], (char*)d_out, nullptr};
  if (maxClusters < 0) {
    cfg.gridDim = dim3(NCTA + NEXTRA);
    if (cudaOccupancyMaxActiveClusters(&maxClusters, fused_kernel, &cfg) != cudaSuccess) maxClusters = 0;
  }
  pp.b0 = -NEXTRA;
  if (maxClusters >= (NCTA + NEXTRA) / 2) {
    cfg.gridDim = dim3(NCTA + NEXTRA);
  } else {
    cfg.gridDim = dim3(NEXTRA);
    cudaLaunchKernelEx(&cfg, fused_kernel, pp, maps);
    cfg.gridDim = dim3(NCTA); pp.b0 = 0;
  }
  cudaLaunchKernelEx(&cfg, fused_kernel, pp, maps);
}
```

```cpp
#include <cuda_runtime.h>
#include <cuda_bf16.h>
#include <cuda.h>
#include <stdint.h>

#define DEVINL __device__ __forceinline__

namespace fk {

constexpr int S_ = 2048, D_ = 1024, F_ = 3584;
constexpr int NCTA = 128;
constexpr int NEXTRA = 4;
constexpr int NMOE = 112;
constexpr int SLOT = 16384;
constexpr int STAGE = 3 * SLOT;
constexpr int SPARE = 4 * STAGE;
constexpr int MISC = SPARE + 32768;
constexpr int SMEM_BYTES = MISC + 3072;
constexpr int BAR_OFF = MISC;
constexpr int CST_OFF = MISC + 480;
constexpr int SEL_OFF = MISC + 496;
constexpr int T1_OFF = MISC + 512;
constexpr int RS_OFF = T1_OFF + 2048;
constexpr int GA_OFF = T1_OFF;
constexpr int W_OFF = GA_OFF + 512;
constexpr int TOP_OFF = GA_OFF + 1792;
constexpr int XST_OFF = 3 * STAGE + SLOT;
constexpr int PART_REL = 0;
constexpr int SCR_REL = 4096;
constexpr int RST_REL = 6144;
enum { B_FULL = 0, B_EMPTY = 4, B_EMPTYH = 8, B_PRDY = 12  , B_PL = 16  , B_WM = 20  , B_LAND = 24  ,
       B_WB = 28  , B_DN = 32  , B_RECV = 36  , B_STAG = 40, B_T1 = 41, B_MODOK = 42, B_PEER = 43  , B_X = 45, B_T2 = 46,
       B_GU = 47, B_XDONE = 48, B_SEL = 49, B_XF = 50, B_OUT = 51, B_NUM = 52 };

__host__ __device__ constexpr int bar_count(int i) {
  return (i >= B_EMPTY && i < B_EMPTYH) || (i >= B_PRDY && i < B_PL) || i == B_X || i == B_XDONE || i == B_XF || i == B_OUT ? 4
         : (i < B_EMPTY || i == B_T1 || i == B_GU || i == B_MODOK) ? 2 : 1;
}

#define FK_XDEPTH 2
#define FK_G0 8
#define FK_ROW1DLY 700
#define FK_ROW2DLY 1300
#define FK_A1EARLY 0
#define FK_XDLY 2500
#define FK_ROW4DLY 2600
#define FK_WS0DLY 500
#define FK_WS1DLY 1600
#define FK_ADLY 1200
#define FK_L1 2
#define FK_L2 3
#define FK_PF0 19
#define FK_E1DLY 150
#define FK_E2DLY 300
#define FK_E4DLY 550
#define FK_MAP 3
#define FK_PPACE 720
#define FK_PACE0 1000
#define FK_WMPF 0
#define FK_TG 28
#define FK_TU 31
#define FK_BSLEEP 250
#define FK_PFSKIP 0
#define FK_DNWIN 1
#define FK_OPACE 240
#define FK_WGATE -1
#define FK_RSLEEP 1000
#define FK_POLL0 2100
#define FK_GX 10
#define FK_ROW8DLY 3600
#define FK_GSTART 7000
#define FK_OPACE2 170
#define FK_E2GAP -1
#define FK_TABEARLY 1
#define FK_PUSHALL 0
#define FK_E3WEAK 1
#define FK_PK 8
#define FK_NQ 4
#define FK_NL 2
#define FK_W2 0
#define FK_XQ 0
#define FK_XS 1
#define FK_H1 0
#define FK_LF 1
#define FK_WB 1
#define FK_NOHINT 0
#define FK_QUIET 1
#define FK_OEXTRA 0
#define FK_PACE 2000
constexpr int SPIN_LIMIT = 1 << 22;
constexpr uint32_t SENT = 0xFFFFFFFFu;

struct Maps {
  CUtensorMap ws[2];
  CUtensorMap n;
  CUtensorMap p;
  CUtensorMap ps;
  CUtensorMap wd[2];
  CUtensorMap x;
  CUtensorMap wg, wu;
  CUtensorMap wdn;
  CUtensorMap wm;
};
template <int V> struct IntC { static constexpr int value = V; };
struct Mail;
struct Ptrs { const char* x; char* n; unsigned* cnt; int b0; uint32_t zero; Mail* mail; uint32_t* mod; const char *c, *ws_re, *ws_im, *wd_re, *wd_im, *wr, *wg, *wu, *wdn, *wm; char* out; unsigned long long* trace; };

__device__ __align__(1024) __nv_bfloat16 g_n[S_ * D_];
__device__ __align__(1024) __nv_bfloat16 g_P[2 * S_ * D_];
__device__ __align__(128) uint32_t g_mod[3 * D_];
__device__ __align__(128) unsigned g_cnt[19 * 32];
struct Mail {
  uint4 stats[32 * 4 * 64];
  uint2 cand[32];
  uint4 rowh[64 * 128];
  uint4 rowx[64 * 128];
  uint4 part[128 * NMOE * 2];
  uint2 rs[2 * 16 * 128];
};
static_assert(FK_L2 == 3, "the receive layout assumes a stagger of three k-blocks");
__device__ __align__(1024) Mail g_mail;

#define SPIN_FAIL(what) __trap()
DEVINL uint32_t smem_u32(const void* p) { return (uint32_t)__cvta_generic_to_shared(p); }
DEVINL void mbar_init(uint32_t bar, uint32_t cnt) { asm volatile("mbarrier.init.shared::cta.b64 [%0], %1;" ::"r"(bar), "r"(cnt) : "memory"); }
DEVINL void mbar_expect_tx(uint32_t bar, uint32_t bytes) { asm volatile("mbarrier.arrive.expect_tx.shared::cta.b64 _, [%0], %1;" ::"r"(bar), "r"(bytes) : "memory"); }
DEVINL void mbar_arrive(uint32_t bar) { asm volatile("mbarrier.arrive.shared::cta.b64 _, [%0];" ::"r"(bar) : "memory"); }
DEVINL void mbar_arrive_cluster(uint32_t bar) { asm volatile("mbarrier.arrive.shared::cluster.b64 _, [%0];" ::"r"(bar) : "memory"); }
DEVINL uint32_t mapa(uint32_t a, uint32_t cta) { uint32_t r; asm("mapa.shared::cluster.u32 %0, %1, %2;" : "=r"(r) : "r"(a), "r"(cta)); return r; }
DEVINL bool mbar_test(uint32_t bar, uint32_t parity) {
  uint32_t ok;
  asm volatile("{\n.reg .pred p;\nmbarrier.test_wait.parity.shared::cta.b64 p, [%1], %2;\nselp.u32 %0, 1, 0, p;\n}" : "=r"(ok) : "r"(bar), "r"(parity) : "memory");
  return ok;
}
DEVINL void mbar_wait(uint32_t bar, uint32_t parity) {
  asm volatile("{\n.reg .pred p;\n.reg .u32 c;\nmov.u32 c, 0;\n"
               "LW:\nmbarrier.try_wait.parity.shared::cta.b64 p, [%0], %1;\n@p bra LD;\n"
               "add.u32 c, c, 1;\nsetp.lt.u32 p, c, 4194304;\n@p bra LW;\ntrap;\nLD:\n}" ::"r"(bar), "r"(parity) : "memory");
}
DEVINL void fence_async_smem() { asm volatile("fence.proxy.async.shared::cta;" ::: "memory"); }
DEVINL void fence_async_global() { asm volatile("fence.proxy.async.global;" ::: "memory"); }
DEVINL void fence_gpu() { asm volatile("fence.acq_rel.gpu;" ::: "memory"); }
template <int ID, int N> DEVINL void named_bar() { asm volatile("bar.sync %0, %1;" ::"n"(ID), "n"(N) : "memory"); }
template <int ID, int N> DEVINL void named_arrive() { asm volatile("bar.arrive %0, %1;" ::"n"(ID), "n"(N) : "memory"); }

DEVINL void tma_2d(uint32_t dst, const CUtensorMap* m, int x, int y, uint32_t bar) {
  asm volatile("cp.async.bulk.tensor.2d.shared::cluster.global.mbarrier::complete_tx::bytes [%0], [%1, {%3, %4}], [%2];"
               ::"r"(dst), "l"(m), "r"(bar), "r"(x), "r"(y) : "memory");
}
DEVINL void tma_2d_hint(uint32_t dst, const CUtensorMap* m, int x, int y, uint32_t bar, uint64_t pol) {
  asm volatile("cp.async.bulk.tensor.2d.shared::cluster.global.mbarrier::complete_tx::bytes.L2::cache_hint [%0], [%1, {%3, %4}], [%2], %5;"
               ::"r"(dst), "l"(m), "r"(bar), "r"(x), "r"(y), "l"(pol) : "memory");
}
DEVINL void tma_3d(uint32_t dst, const CUtensorMap* m, int x, int y, int z, uint32_t bar) {
  asm volatile("cp.async.bulk.tensor.3d.shared::cluster.global.mbarrier::complete_tx::bytes [%0], [%1, {%3, %4, %5}], [%2];"
               ::"r"(dst), "l"(m), "r"(bar), "r"(x), "r"(y), "r"(z) : "memory");
}
DEVINL void tma_store_2d(const CUtensorMap* m, uint32_t src, int x, int y) {
  asm volatile("cp.async.bulk.tensor.2d.global.shared::cta.bulk_group [%0, {%2, %3}], [%1];" ::"l"(m), "r"(src), "r"(x), "r"(y) : "memory");
}
DEVINL void bulk_load(uint32_t dst, const void* src, uint32_t bytes, uint32_t bar) {
  asm volatile("cp.async.bulk.shared::cluster.global.mbarrier::complete_tx::bytes [%0], [%1], %2, [%3];" ::"r"(dst), "l"(src), "r"(bytes), "r"(bar) : "memory");
}
DEVINL void bulk_store(void* dst, uint32_t src, uint32_t bytes) {
  asm volatile("cp.async.bulk.global.shared::cta.bulk_group [%0], [%1], %2;" ::"l"(dst), "r"(src), "r"(bytes) : "memory");
}
DEVINL void pf_bulk(const void* p, uint32_t bytes) { asm volatile("cp.async.bulk.prefetch.L2.global [%0], %1;" ::"l"(p), "r"(bytes) : "memory"); }
DEVINL void pf_bulk_hint(const void* p, uint32_t bytes, uint64_t pol) {
  asm volatile("cp.async.bulk.prefetch.L2.global.L2::cache_hint [%0], %1, %2;" ::"l"(p), "r"(bytes), "l"(pol) : "memory");
}
DEVINL void pf_2d(const CUtensorMap* m, int x, int y) {
  asm volatile("cp.async.bulk.prefetch.tensor.2d.L2.global [%0, {%1, %2}];" ::"l"(m), "r"(x), "r"(y) : "memory");
}
DEVINL void bulk_commit() { asm volatile("cp.async.bulk.commit_group;" ::: "memory"); }
template <int N> DEVINL void bulk_wait() { asm volatile("cp.async.bulk.wait_group %0;" ::"n"(N) : "memory"); }
template <int N> DEVINL void bulk_wait_read() { asm volatile("cp.async.bulk.wait_group.read %0;" ::"n"(N) : "memory"); }
DEVINL void prefetch_tmap(const CUtensorMap* m) { asm volatile("prefetch.tensormap [%0];" ::"l"(m) : "memory"); }

DEVINL void wg_fence() { asm volatile("wgmma.fence.sync.aligned;" ::: "memory"); }
DEVINL void wg_commit() { asm volatile("wgmma.commit_group.sync.aligned;" ::: "memory"); }
template <int N> DEVINL void wg_wait() { asm volatile("wgmma.wait_group.sync.aligned %0;" ::"n"(N) : "memory"); }

DEVINL uint64_t make_desc(uint32_t addr, uint32_t lbo, uint32_t sbo) {
  return (uint64_t)((addr & 0x3FFFF) >> 4) | ((uint64_t)(lbo >> 4) << 16) | ((uint64_t)(sbo >> 4) << 32) | ((uint64_t)1 << 62);
}

#define R8(a, o) "+f"(a[o]), "+f"(a[o + 1]), "+f"(a[o + 2]), "+f"(a[o + 3]), "+f"(a[o + 4]), "+f"(a[o + 5]), "+f"(a[o + 6]), "+f"(a[o + 7])
#define R128(a) R8(a, 0), R8(a, 8), R8(a, 16), R8(a, 24), R8(a, 32), R8(a, 40), R8(a, 48), R8(a, 56), \
                R8(a, 64), R8(a, 72), R8(a, 80), R8(a, 88), R8(a, 96), R8(a, 104), R8(a, 112), R8(a, 120)
template <int TB>
DEVINL void wgmma_n256(float (&d)[128], uint64_t da, uint64_t db, int scale_d) {
  asm volatile(
      "{\n.reg .pred p;\nsetp.ne.b32 p, %130, 0;\n"
      "wgmma.mma_async.sync.aligned.m64n256k16.f32.bf16.bf16 "
      "{%0, %1, %2, %3, %4, %5, %6, %7, %8, %9, %10, %11, %12, %13, %14, %15, "
      "%16, %17, %18, %19, %20, %21, %22, %23, %24, %25, %26, %27, %28, %29, %30, %31, "
      "%32, %33, %34, %35, %36, %37, %38, %39, %40, %41, %42, %43, %44, %45, %46, %47, "
      "%48, %49, %50, %51, %52, %53, %54, %55, %56, %57, %58, %59, %60, %61, %62, %63, "
      "%64, %65, %66, %67, %68, %69, %70, %71, %72, %73, %74, %75, %76, %77, %78, %79, "
      "%80, %81, %82, %83, %84, %85, %86, %87, %88, %89, %90, %91, %92, %93, %94, %95, "
      "%96, %97, %98, %99, %100, %101, %102, %103, %104, %105, %106, %107, %108, %109, %110, %111, "
      "%112, %113, %114, %115, %116, %117, %118, %119, %120, %121, %122, %123, %124, %125, %126, %127}, "
      "%128, %129, p, 1, 1, 0, %131;\n}\n"
      : R128(d)
      : "l"(da), "l"(db), "r"(scale_d), "n"(TB));
}
DEVINL void reg_fence128(float (&a)[128]) {
#pragma unroll
  for (int i = 0; i < 128; i++) asm volatile("" : "+f"(a[i])::"memory");
}

DEVINL uint32_t pack_bf16(float lo, float hi) {
  uint32_t r;
  asm("cvt.rn.bf16x2.f32 %0, %1, %2;" : "=r"(r) : "f"(hi), "f"(lo));
  return r;
}
DEVINL uint32_t fma_bf2(uint32_t a, uint32_t b, uint32_t c) { uint32_t r; asm("fma.rn.bf16x2 %0, %1, %2, %3;" : "=r"(r) : "r"(a), "r"(b), "r"(c)); return r; }
DEVINL uint32_t mul_bf2(uint32_t a, uint32_t b) { uint32_t r; asm("mul.rn.bf16x2 %0, %1, %2;" : "=r"(r) : "r"(a), "r"(b)); return r; }
DEVINL uint32_t add_bf2(uint32_t a, uint32_t b) { uint32_t r; asm("add.rn.bf16x2 %0, %1, %2;" : "=r"(r) : "r"(a), "r"(b)); return r; }
DEVINL uint32_t add1_bf2(uint32_t a) { return fma_bf2(a, 0x3F803F80u, 0x3F803F80u); }
DEVINL float bf_lo(uint32_t w) { return __uint_as_float(w << 16); }
DEVINL float bf_hi(uint32_t w) { return __uint_as_float(w & 0xFFFF0000u); }
DEVINL float round_bf16(float v) { return bf_lo(pack_bf16(v, v)); }
DEVINL float sigmoid_f(float v) {
  float e, r;
  asm("ex2.approx.ftz.f32 %0, %1;" : "=f"(e) : "f"(v * -1.4426950408889634f));
  asm("rcp.approx.ftz.f32 %0, %1;" : "=f"(r) : "f"(1.f + e));
  return r;
}
DEVINL float rsqrt_f(float v) { float r; asm("rsqrt.approx.ftz.f32 %0, %1;" : "=f"(r) : "f"(v)); return r; }
DEVINL float silu_f(float v) { return v * sigmoid_f(v); }
DEVINL void stsm_x4(uint32_t addr, uint32_t r0, uint32_t r1, uint32_t r2, uint32_t r3) {
  asm volatile("stmatrix.sync.aligned.m8n8.x4.shared.b16 [%0], {%1, %2, %3, %4};" ::"r"(addr), "r"(r0), "r"(r1), "r"(r2), "r"(r3) : "memory");
}
DEVINL void ldsm_x4(uint32_t addr, uint32_t& r0, uint32_t& r1, uint32_t& r2, uint32_t& r3) {
  asm volatile("ldmatrix.sync.aligned.m8n8.x4.shared.b16 {%0, %1, %2, %3}, [%4];" : "=r"(r0), "=r"(r1), "=r"(r2), "=r"(r3) : "r"(addr) : "memory");
}
DEVINL void ldsm_x4_t(uint32_t addr, uint32_t& r0, uint32_t& r1, uint32_t& r2, uint32_t& r3) {
  asm volatile("ldmatrix.sync.aligned.m8n8.x4.trans.shared.b16 {%0, %1, %2, %3}, [%4];" : "=r"(r0), "=r"(r1), "=r"(r2), "=r"(r3) : "r"(addr) : "memory");
}
DEVINL void mma_16816(float (&c)[4], uint32_t a0, uint32_t a1, uint32_t a2, uint32_t a3, uint32_t b0, uint32_t b1) {
  asm("mma.sync.aligned.m16n8k16.row.col.f32.bf16.bf16.f32 {%0, %1, %2, %3}, {%4, %5, %6, %7}, {%8, %9}, {%0, %1, %2, %3};"
      : "+f"(c[0]), "+f"(c[1]), "+f"(c[2]), "+f"(c[3]) : "r"(a0), "r"(a1), "r"(a2), "r"(a3), "r"(b0), "r"(b1));
}
DEVINL void mma_1688(float (&c)[4], uint32_t a0, uint32_t a1, uint32_t b0) {
  asm("mma.sync.aligned.m16n8k8.row.col.f32.bf16.bf16.f32 {%0, %1, %2, %3}, {%4, %5}, {%6}, {%0, %1, %2, %3};"
      : "+f"(c[0]), "+f"(c[1]), "+f"(c[2]), "+f"(c[3]) : "r"(a0), "r"(a1), "r"(b0));
}
DEVINL float4 lds128(uint32_t a) { float4 v; asm volatile("ld.shared.v4.f32 {%0, %1, %2, %3}, [%4];" : "=f"(v.x), "=f"(v.y), "=f"(v.z), "=f"(v.w) : "r"(a)); return v; }
DEVINL uint4 lds128u(uint32_t a) { uint4 v; asm volatile("ld.shared.v4.u32 {%0, %1, %2, %3}, [%4];" : "=r"(v.x), "=r"(v.y), "=r"(v.z), "=r"(v.w) : "r"(a)); return v; }
DEVINL float2 lds64(uint32_t a) { float2 v; asm volatile("ld.shared.v2.f32 {%0, %1}, [%2];" : "=f"(v.x), "=f"(v.y) : "r"(a)); return v; }
DEVINL uint2 lds64u(uint32_t a) { uint2 v; asm volatile("ld.shared.v2.u32 {%0, %1}, [%2];" : "=r"(v.x), "=r"(v.y) : "r"(a)); return v; }
DEVINL float lds32(uint32_t a) { float v; asm volatile("ld.shared.f32 %0, [%1];" : "=f"(v) : "r"(a)); return v; }
DEVINL float lds16f(uint32_t a) { uint32_t v; asm volatile("ld.shared.u16 %0, [%1];" : "=r"(v) : "r"(a)); return __uint_as_float(v << 16); }
DEVINL uint32_t lds32u(uint32_t a) { uint32_t v; asm volatile("ld.shared.u32 %0, [%1];" : "=r"(v) : "r"(a)); return v; }
DEVINL void sts128(uint32_t a, float x, float y, float z, float w) { asm volatile("st.shared.v4.f32 [%0], {%1, %2, %3, %4};" ::"r"(a), "f"(x), "f"(y), "f"(z), "f"(w) : "memory"); }
DEVINL void sts128u(uint32_t a, uint32_t x, uint32_t y, uint32_t z, uint32_t w) { asm volatile("st.shared.v4.u32 [%0], {%1, %2, %3, %4};" ::"r"(a), "r"(x), "r"(y), "r"(z), "r"(w) : "memory"); }
DEVINL void sts64(uint32_t a, float x, float y) { asm volatile("st.shared.v2.f32 [%0], {%1, %2};" ::"r"(a), "f"(x), "f"(y) : "memory"); }
DEVINL void sts64u(uint32_t a, uint32_t x, uint32_t y) { asm volatile("st.shared.v2.u32 [%0], {%1, %2};" ::"r"(a), "r"(x), "r"(y) : "memory"); }
DEVINL void sts32(uint32_t a, float v) { asm volatile("st.shared.f32 [%0], %1;" ::"r"(a), "f"(v) : "memory"); }
DEVINL void sts32u(uint32_t a, uint32_t v) { asm volatile("st.shared.u32 [%0], %1;" ::"r"(a), "r"(v) : "memory"); }

DEVINL uint4 ld_msg(const uint4* p) {
  unsigned long long a, b;
  asm volatile("{\n.reg .b128 r;\nld.relaxed.gpu.global.b128 r, [%2];\nmov.b128 {%0, %1}, r;\n}" : "=l"(a), "=l"(b) : "l"(p) : "memory");
  return make_uint4((uint32_t)a, (uint32_t)(a >> 32), (uint32_t)b, (uint32_t)(b >> 32));
}
DEVINL void st_msg(uint4* p, uint32_t x, uint32_t y, uint32_t z, uint32_t w) {
  unsigned long long a = (unsigned long long)x | ((unsigned long long)y << 32), b = (unsigned long long)z | ((unsigned long long)w << 32);
  asm volatile("{\n.reg .b128 r;\nmov.b128 r, {%1, %2};\nst.relaxed.gpu.global.b128 [%0], r;\n}" ::"l"(p), "l"(a), "l"(b) : "memory");
}
DEVINL uint2 ld_msg8(const void* p) {
  unsigned long long a;
  asm volatile("ld.relaxed.gpu.global.b64 %0, [%1];" : "=l"(a) : "l"(p) : "memory");
  return make_uint2((uint32_t)a, (uint32_t)(a >> 32));
}
DEVINL void st_msg8(uint2* p, uint32_t x, uint32_t y) {
  asm volatile("st.relaxed.gpu.global.b64 [%0], %1;" ::"l"(p), "l"((unsigned long long)x | ((unsigned long long)y << 32)) : "memory");
}
DEVINL unsigned ld_rlx(const void* p) { unsigned v; asm volatile("ld.relaxed.gpu.global.u32 %0, [%1];" : "=r"(v) : "l"(p) : "memory"); return v; }
DEVINL void st_rlx(unsigned* p, unsigned v) { asm volatile("st.relaxed.gpu.global.u32 [%0], %1;" ::"l"(p), "r"(v) : "memory"); }
DEVINL void red_add(unsigned* p, unsigned v) { asm volatile("red.relaxed.gpu.global.add.u32 [%0], %1;" ::"l"(p), "r"(v) : "memory"); }
DEVINL void red_max8(uint2* p, uint32_t lo, uint32_t hi) {
  asm volatile("red.relaxed.gpu.global.max.u64 [%0], %1;" ::"l"(p), "l"((unsigned long long)lo | ((unsigned long long)hi << 32)) : "memory");
}
DEVINL void red_add_release(unsigned* p, unsigned v) { asm volatile("red.release.gpu.global.add.u32 [%0], %1;" ::"l"(p), "r"(v) : "memory"); }
DEVINL uint4 ldg_nc(const void* p) {
  uint4 v;
  asm volatile("ld.global.nc.L1::no_allocate.v4.u32 {%0, %1, %2, %3}, [%4];" : "=r"(v.x), "=r"(v.y), "=r"(v.z), "=r"(v.w) : "l"(p));
  return v;
}
DEVINL uint4 ldg128(const void* p) {
  uint4 v;
  asm volatile("ld.global.v4.u32 {%0, %1, %2, %3}, [%4];" : "=r"(v.x), "=r"(v.y), "=r"(v.z), "=r"(v.w) : "l"(p) : "memory");
  return v;
}
DEVINL void stg128(void* p, uint4 v) { asm volatile("st.global.v4.u32 [%0], {%1, %2, %3, %4};" ::"l"(p), "r"(v.x), "r"(v.y), "r"(v.z), "r"(v.w) : "memory"); }
DEVINL uint32_t landed(uint32_t readback, uint32_t zero) { return __reduce_or_sync(~0u, readback & zero); }
DEVINL uint32_t clk() { uint32_t c; asm volatile("mov.u32 %0, %%clock;" : "=r"(c)); return c; }
DEVINL void delay_until(uint32_t c0, uint32_t cycles) { while (clk() - c0 < cycles) {} }

#define TRACE(id)
#define TRACE_CLK(id)
#define FK_TTMASK 0x1111C1110101ull

DEVINL const char* piece_addr(const Ptrs& pp, int b, int i) {
  if (i >= 20) return pp.wdn + (size_t)b * 57344 + (i - 20) * 8192;
  if ((i >> 2) == 2) return (b < 64 ? pp.wd_re : pp.wd_im) + (size_t)(b & 63) * 32768 + (i & 3) * 8192;
  return (i < 4 || (i >> 2) == 3 ? pp.wg : pp.wu) + (size_t)((i < 8 ? ((i & 3) ^ 2) * 128 : 512 + (i & 3) * 128) + b) * (2 * F_);
}

DEVINL uint32_t dn_box(int i) { return i == 0 ? STAGE + 2 * SLOT : i == 3 ? SPARE : 2 * STAGE + i * SLOT; }
DEVINL int sibling(int m4, int r) {
  return r < 2 ? m4 ^ r : ((m4 & 2) ^ 2) + r - 2;
}

DEVINL uint32_t fkey(float v, int row) {
  const uint32_t u = __float_as_uint(v);
  return (((u & 0x80000000u) ? ~u : (u | 0x80000000u)) & ~2047u) | (uint32_t)(2047 - row);
}
DEVINL int key_row(uint32_t k) { return 2047 - (int)(k & 2047u); }
DEVINL float key_val(uint32_t k) { k = (k & ~2047u) | 1024u; return __uint_as_float((k & 0x80000000u) ? (k & 0x7FFFFFFFu) : ~k); }
DEVINL uint32_t redux_max(uint32_t v) { uint32_t r; asm volatile("redux.sync.max.u32 %0, %1, 0xffffffff;" : "=r"(r) : "r"(v)); return r; }
DEVINL void warp_top2(uint32_t ka, uint32_t kb, uint32_t& k1, uint32_t& k2) {
  k1 = redux_max(ka);
  k2 = redux_max(ka == k1 ? kb : ka);
}
DEVINL int sel_slot(uint2 sel, int n) {
  const int bA = key_row(sel.x) >> 6, bB = key_row(sel.y) >> 6;
  return n ? bB * 2 + (bA == bB ? 1 : 0) : bA * 2;
}

DEVINL void ln_stats(const uint4 (&w)[4], float (&v)[32], float& rstd, float& nmr) {
#pragma unroll
  for (int i = 0; i < 4; i++) {
    v[8 * i + 0] = bf_lo(w[i].x); v[8 * i + 1] = bf_hi(w[i].x); v[8 * i + 2] = bf_lo(w[i].y); v[8 * i + 3] = bf_hi(w[i].y);
    v[8 * i + 4] = bf_lo(w[i].z); v[8 * i + 5] = bf_hi(w[i].z); v[8 * i + 6] = bf_lo(w[i].w); v[8 * i + 7] = bf_hi(w[i].w);
  }
  float s[4] = {0.f, 0.f, 0.f, 0.f}, q[4] = {0.f, 0.f, 0.f, 0.f};
#pragma unroll
  for (int i = 0; i < 32; i++) { s[i & 3] += v[i]; q[i & 3] = fmaf(v[i], v[i], q[i & 3]); }
  rstd = (s[0] + s[1]) + (s[2] + s[3]); nmr = (q[0] + q[1]) + (q[2] + q[3]);
}
DEVINL void ln_apply(uint4 (&w)[4], const float (&v)[32], float sum, float sq) {
#pragma unroll
  for (int o = 16; o; o >>= 1) { sum += __shfl_xor_sync(~0u, sum, o); sq += __shfl_xor_sync(~0u, sq, o); }
  const float mean = sum * (1.f / D_);
  const float rstd = rsqrt_f(fmaxf(fmaf(-mean, mean, sq * (1.f / D_)), 0.f) + 1e-5f), nmr = -mean * rstd;
#pragma unroll
  for (int i = 0; i < 4; i++) {
    w[i].x = pack_bf16(fmaf(v[8 * i], rstd, nmr), fmaf(v[8 * i + 1], rstd, nmr)); w[i].y = pack_bf16(fmaf(v[8 * i + 2], rstd, nmr), fmaf(v[8 * i + 3], rstd, nmr));
    w[i].z = pack_bf16(fmaf(v[8 * i + 4], rstd, nmr), fmaf(v[8 * i + 5], rstd, nmr)); w[i].w = pack_bf16(fmaf(v[8 * i + 6], rstd, nmr), fmaf(v[8 * i + 7], rstd, nmr));
  }
}
DEVINL void ln_row(uint4 (&w)[4]) { float v[32], s, q; ln_stats(w, v, s, q); ln_apply(w, v, s, q); }
DEVINL float sum8(uint4 u) { return ((bf_lo(u.x) + bf_hi(u.x)) + (bf_lo(u.y) + bf_hi(u.y))) + ((bf_lo(u.z) + bf_hi(u.z)) + (bf_lo(u.w) + bf_hi(u.w))); }

template <int R> DEVINL void take_box(uint32_t (&wf)[128], uint32_t box, int lane) {
  const int kr = (lane & 7) + (lane >> 4) * 8;
  const uint32_t base = box + kr * 64, sw = (uint32_t)((kr >> 1) & 3), hb = (uint32_t)((lane >> 3) & 1);
#pragma unroll
  for (int mt = 0; mt < 2; mt++) {
    const uint32_t ad = base + (((mt * 2 + hb) ^ sw) << 4);
#pragma unroll
    for (int ks = 0; ks < 8; ks++) {
      const int o = (ks * 4 + R * 2 + mt) * 4;
      ldsm_x4_t(ad + ks * 1024, wf[o], wf[o + 1], wf[o + 2], wf[o + 3]);
    }
  }
}
DEVINL void gate_up(const Ptrs& pp, uint32_t (&wf)[128], uint32_t sb, uint32_t scr, int ksl, int lane) {
  const uint2 sel = lds64u(sb + SEL_OFF);
  const int gq = lane >> 2, q4 = lane & 3;
  const uint4* src = &pp.mail->rowh[sel_slot(sel, gq & 1) * 128 + ksl * 16 + q4];
  uint4 bf[4];
  int it = 0;
#pragma unroll
  for (int u = 0; u < 4; u++) bf[u] = FK_E3WEAK ? ldg128(src + u * 4) : ld_msg(src + u * 4);
  while (!__all_sync(~0u, bf[0].x != SENT && bf[1].x != SENT && bf[2].x != SENT && bf[3].x != SENT)) {
#pragma unroll
    for (int u = 0; u < 4; u++) bf[u] = ld_msg(src + u * 4);
    if (++it > SPIN_LIMIT) SPIN_FAIL(0x207);
  }
  if (lane == 0 && ksl == 4) TRACE(20);
  float acc[8][4];
#pragma unroll
  for (int i = 0; i < 8; i++) { acc[i][0] = acc[i][1] = acc[i][2] = acc[i][3] = 0.f; }
#pragma unroll
  for (int u = 0; u < 4; u++)
#pragma unroll
    for (int mt = 0; mt < 4; mt++) {
      const int o = (2 * u * 4 + mt) * 4;
      mma_16816(acc[mt], wf[o], wf[o + 1], wf[o + 2], wf[o + 3], bf[u].x, bf[u].y);
      mma_16816(acc[4 + mt], wf[o + 16], wf[o + 17], wf[o + 18], wf[o + 19], bf[u].z, bf[u].w);
    }
  {
    const bool h = q4 & 1, m = q4 & 2;
    float v[4][2];
#pragma unroll
    for (int mt = 0; mt < 4; mt++) {
      v[mt][0] = h ? acc[mt][2] + acc[4 + mt][2] : acc[mt][0] + acc[4 + mt][0];
      v[mt][1] = h ? acc[mt][3] + acc[4 + mt][3] : acc[mt][1] + acc[4 + mt][1];
    }
    sts128(scr + PART_REL + ksl * 512 + (q4 * 8 + gq) * 16, m ? v[1][0] : v[0][0], m ? v[1][1] : v[0][1], m ? v[3][0] : v[2][0], m ? v[3][1] : v[2][1]);
  }
  named_arrive<4, 384>();
}

struct OutTab { uint32_t A[4], S[4], G[4]; };
DEVINL void out_tab(OutTab& tb, uint4 cb, uint4 sv, uint4 gb) {
  tb.A[0] = add1_bf2(cb.x); tb.A[1] = add1_bf2(cb.y); tb.A[2] = add1_bf2(cb.z); tb.A[3] = add1_bf2(cb.w);
  tb.S[0] = sv.x; tb.S[1] = sv.y; tb.S[2] = sv.z; tb.S[3] = sv.w;
  tb.G[0] = gb.x; tb.G[1] = gb.y; tb.G[2] = gb.z; tb.G[3] = gb.w;
}
DEVINL void out_rows(const OutTab& tb, uint32_t sb, uint32_t scr, int r, uint32_t mask, int lane, char* dst) {
  const float4 st = lds128(scr + RST_REL + r * 8);
  uint4 v[2];
#pragma unroll
  for (int k = 0; k < 2; k++) v[k] = lds128u(sb + XST_OFF + (r + k) * 512 + ((lane ^ ((r + k) & 7)) << 4));
#pragma unroll
  for (int k = 0; k < 2; k++) {
    const float rs = k ? st.z : st.x, nm = k ? st.w : st.y;
    const uint32_t x4[4] = {v[k].x, v[k].y, v[k].z, v[k].w};
    uint32_t o[4];
#pragma unroll
    for (int u = 0; u < 4; u++)
      o[u] = fma_bf2(tb.G[u], fma_bf2(pack_bf16(fmaf(bf_lo(x4[u]), rs, nm), fmaf(bf_hi(x4[u]), rs, nm)), tb.A[u], tb.S[u]), x4[u]);
    if ((mask >> k) & 1) stg128(dst + (size_t)(r + k) * (2 * D_), make_uint4(o[0], o[1], o[2], o[3]));
  }
}
DEVINL int out_group(const OutTab& tb, uint32_t sb, uint32_t scr, int r0, uint32_t mask, int lane, char* dst, uint32_t pace, uint32_t stop) {
  int r = 0;
#pragma unroll 1
  for (; mask; r += 2, mask >>= 2) {
    if (!(mask & 3)) continue;
    const bool last = stop && mbar_test(stop, 0);
    if (last && !FK_OEXTRA) return r;
    const uint32_t cn = clk();
    out_rows(tb, sb, scr, r0 + r, mask, lane, dst);
    if (last) return r + 2;
    if (mask >> 2) delay_until(cn, pace);
  }
  return 16;
}
DEVINL uint32_t row_bit(uint32_t key, int g0) { const unsigned r = (unsigned)(key_row(key) - g0); return r < 16 ? 1u << r : 0u; }

template <int TB, int G0, int G1>
DEVINL void gemm_phase(const Ptrs& pp, float (&acc)[128], uint32_t sb, int cw, bool lag, bool elect, uint32_t rel) {
  const uint32_t bars = sb + BAR_OFF;
#pragma unroll 1
  for (int g = G0; g < G1; g++) {
    const int s = g & 3;
    mbar_wait(bars + (B_FULL + s) * 8, (g >> 2) & 1);
    const bool hold = lag && g == G1 - (TB ? FK_L1 : FK_L2) && !(TB && FK_H1);
    if (hold) {
      wg_wait<0>();
      if (rel) mbar_arrive_cluster(rel + ((g - 1) & 3) * 8);
      mbar_wait(bars + B_STAG * 8, TB ? 0 : 1);
    }
    const uint32_t sa = sb + s * STAGE;
    const uint64_t da = make_desc(sa + cw * 8192, 16, 1024), db = make_desc(sa + SLOT, TB ? 8192 : 16, 1024);
    constexpr int KB = TB ? 128 : 2;
    wg_fence();
    wgmma_n256<TB>(acc, da, db, g > G0);
    wgmma_n256<TB>(acc, da + 2, db + KB, 1);
    wg_commit();
    wg_wait<1>();
    if (rel && g > G0 && !hold) mbar_arrive_cluster(rel + ((g - 1) & 3) * 8);
    if (!TB && g == G1 - 1 && !lag && elect) mbar_arrive_cluster(mapa(bars + B_PEER * 8, cw));
    if (TB && FK_H1 && lag && g == G1 - FK_L1 - 1) mbar_wait(bars + B_STAG * 8, 0);
    wg_fence();
    wgmma_n256<TB>(acc, da + 4, db + 2 * KB, 1);
    wgmma_n256<TB>(acc, da + 6, db + 3 * KB, 1);
    wg_commit();
  }
  if (!lag) {
    wg_wait<1>();
    if (elect) mbar_arrive(bars + B_STAG * 8);
  }
}
DEVINL void gemm_finish(float (&acc)[128], uint32_t rel) {
  wg_wait<0>();
  reg_fence128(acc);
  if (rel) mbar_arrive_cluster(rel + 24);
}

__global__ void __launch_bounds__(384, 1)
fused_kernel(const Ptrs pp, const __grid_constant__ Maps maps) {
  extern __shared__ __align__(1024) uint8_t smem_raw[];
  const uint32_t c0 = clk();
  if (threadIdx.x == 0 && blockIdx.x >= NEXTRA) TRACE(0);
  const uint32_t sb = smem_u32(smem_raw);
  const int tid = threadIdx.x, lane = tid & 31;
  const int warp = __shfl_sync(~0u, tid >> 5, 0);
  const int rb = (int)blockIdx.x + pp.b0;
  const uint32_t bars = sb + BAR_OFF;
  auto BAR = [&](int i) { return bars + i * 8; };

  if (rb < 0) {
    const uint32_t ring = sb + warp * 16384, rbar = sb + MISC + warp * 64;
    const int row0 = FK_GX * 128 + ((rb + NEXTRA) * 12 + warp) * 2;
    if (lane == 0) {
#pragma unroll 1
      for (int i = 0; i < 4; i++) mbar_init(rbar + i * 8, 1);
      asm volatile("fence.mbarrier_init.release.cluster;" ::: "memory");
      delay_until(c0, FK_XDLY);
#pragma unroll 1
      for (int i = 0; i < FK_XDEPTH; i++) { mbar_expect_tx(rbar + i * 8, 4096); bulk_load(ring + i * 4096, pp.x + (size_t)(row0 + 96 * i) * (2 * D_), 4096, rbar + i * 8); }
    }
    __syncwarp();
    int row = row0;
#pragma unroll 1
    for (int it = 0; row < S_; it++, row += 96) {
      const uint32_t st = ring + (it & 3) * 4096;
      mbar_wait(rbar + (it & 3) * 8, (it >> 2) & 1);
      uint4 w[4], w2[4];
#pragma unroll
      for (int i = 0; i < 4; i++) { w[i] = lds128u(st + lane * 16 + i * 512); w2[i] = lds128u(st + 2048 + lane * 16 + i * 512); }
      ln_row(w);
      uint32_t rbk = 0;
      if (it) {
        if (lane == 0) bulk_wait<0>();
        __syncwarp();
        rbk = ld_rlx(pp.n + (size_t)(row - 96) * (2 * D_) + lane * 128);
      }
      ln_row(w2);
#pragma unroll
      for (int i = 0; i < 4; i++) { sts128u(st + lane * 16 + i * 512, w[i].x, w[i].y, w[i].z, w[i].w); sts128u(st + 2048 + lane * 16 + i * 512, w2[i].x, w2[i].y, w2[i].z, w2[i].w); }
      fence_async_smem();
      const uint32_t z = landed(rbk, pp.zero);
      if (lane == 0) {
        if (it) red_add(&pp.cnt[((row - 96) >> 7) * 32], 2 + z);
        bulk_store(pp.n + (size_t)row * (2 * D_), st, 4096); bulk_commit();
        if (row + 96 * FK_XDEPTH < S_) {
          const int sn = (it + FK_XDEPTH) & 3;
          mbar_expect_tx(rbar + sn * 8, 4096); bulk_load(ring + sn * 4096, pp.x + (size_t)(row + 96 * FK_XDEPTH) * (2 * D_), 4096, rbar + sn * 8);
        }
      }
      __syncwarp();
    }
    if (lane == 0) bulk_wait<0>();
    __syncwarp();
    const uint32_t z = landed(ld_rlx(pp.n + (size_t)(row - 96) * (2 * D_) + lane * 128), pp.zero);
    if (lane == 0) red_add(&pp.cnt[((row - 96) >> 7) * 32], 2 + z);
    return;
  }
  if (warp > 4) asm volatile("barrier.cluster.arrive.relaxed.aligned;" ::: "memory");
  if ((unsigned)(warp - 4) < FK_G0) {
    const int row = (warp - 4) * 128 + rb;
    uint4 w[4];
    const bool first = warp < 6;
    {
      uint32_t pm = 0, par = 0;
      if (warp > 4) delay_until(c0, warp == 5 ? FK_ROW1DLY : warp < 8 ? FK_ROW2DLY : FK_ROW4DLY);
#pragma unroll
      for (int i = 0; i < 4; i++) w[i] = ldg_nc(pp.x + (size_t)row * (2 * D_) + lane * 16 + i * 512);
      if (warp == 4) asm volatile("barrier.cluster.arrive.relaxed.aligned;" ::: "memory");
      if (first) {
        par = ld_rlx(&pp.cnt[17 * 32]) + 1;
        pm = (lane & 7) ? 0u : 1u;
        const uint32_t z = landed(w[0].x | w[1].x | w[2].x | w[3].x | par, pp.zero);
        if (lane == 0) red_add(&pp.cnt[(warp - 4) * 32], 1 + z);
        if (tid == 128) TRACE(1);
      }
      ln_row(w);
      char* dst = pp.n + (size_t)row * (2 * D_);
#pragma unroll
      for (int i = 0; i < 4; i++) { w[i].x = (w[i].x & ~pm) | (par & pm); stg128(dst + lane * 16 + i * 512, w[i]); }
    }
    if (tid == 128) TRACE(31);
    if (lane == 0 && warp == 3 + FK_G0) TRACE(55);
    if (!first) { if (warp < 8) named_arrive<8, 96>(); else named_arrive<9, 32 * (FK_G0 - 3)>(); }
  }
  int m4, t;
  {
    const int c = (rb >> 1) - 2;
    int g = 8, i = c + 2;
    if (c >= 32) { i = ((c - 32) * 37) >> 8; g = c - 32 - 7 * i; g += g >= 2; i += 4; }
    else if (c >= 0) { g = c & 7; i = c >> 3; }
    if (g == 8) { g = 2; i += 6; } else if (i == 8) { i = 4 + g; g = 2; }
    m4 = (g >> 2) * 2 + (i & 1); t = (g & 3) * 4 + (i >> 1);
  }
  const int j = rb & 1, b = t * 8 + m4 * 2 + j;
  const int blk = t * 2 + j;
  const uint32_t scr = sb + 2 * STAGE + j * 8192;
  if (warp < 4) {
    uint32_t tag = ld_rlx(&pp.cnt[17 * 32]);
    auto ws_touch = [&](int o) {
      uint32_t v;
      asm volatile("ld.global.nc.L1::no_allocate.L2::128B.u32 %0, [%1];" : "=r"(v)
                   : "l"((j ? pp.ws_im : pp.ws_re) + (size_t)(t * 128 + m4 * 32 + lane) * (2 * S_) + o));
      return v;
    };
    uint32_t early = 0;
    if (warp == 1) { delay_until(c0, FK_WS0DLY); early = ws_touch(0); if (lane == 0) TRACE(126); }
    if (warp == 0) early = ld_rlx(&pp.cnt[(lane & 1) * 32]);
    if (lane == 0) {
      if (warp < 2) {
        if (warp == 0) {
          prefetch_tmap(&maps.ws[j]); prefetch_tmap(&maps.n);
          if (sb & 1023) __trap();
#pragma unroll
          for (int i = 0; i < 8; i++) mbar_init(BAR(i), bar_count(i));
        } else {
#pragma unroll
          for (int i = 8; i < 22; i++) mbar_init(BAR(i), bar_count(i));
        }
      } else if (warp == 2) {
#pragma unroll
        for (int i = 22; i < 36; i++) mbar_init(BAR(i), bar_count(i));
      } else {
#pragma unroll
        for (int i = 36; i < B_NUM; i++) mbar_init(BAR(i), bar_count(i));
#pragma unroll
        for (int i = 0; i < 4; i++) mbar_expect_tx(BAR(B_RECV + i), 8192);
      }
      asm volatile("fence.mbarrier_init.release.cluster;" ::: "memory");
    }
    named_bar<6, 128>();
    named_arrive<0, 256>(); named_arrive<3, 256>();
    asm volatile("barrier.cluster.arrive.relaxed.aligned;" ::: "memory");
    uint64_t pol_first;
    asm volatile("createpolicy.fractional.L2::evict_first.b64 %0, 1.0;" : "=l"(pol_first));
    const bool moe = b < NMOE;
    uint32_t wf[128];
    auto take = [&](auto R) {
      constexpr int r = decltype(R)::value;
      const uint32_t box = sb + SPARE + warp * 8192;
      if (moe || r == 0) mbar_wait(BAR(B_WB + warp), r);
      if (moe) take_box<r>(wf, box, lane);
      fence_async_smem();
      __syncwarp();
      if (lane == 0) {
        if (r) {
          mbar_arrive(BAR(B_XF));
        }
        else if (moe) { mbar_expect_tx(BAR(B_WB + warp), 8192); tma_2d_hint(box, &maps.wu, b * 32, warp * 128, BAR(B_WB + warp), pol_first); }
      }
      __syncwarp();
    };

    if (warp == 0) {
      auto loadA = [&](int g) {
        mbar_expect_tx(BAR(B_FULL + (g & 3)), SLOT);
        tma_2d_hint(sb + (g & 3) * STAGE, &maps.ws[j], g * 64, t * 128, BAR(B_FULL + (g & 3)), pol_first);
      };
      auto loadB = [&](int g, int bar) { mbar_expect_tx(BAR(bar + (g & 3)), 2 * SLOT); tma_3d(sb + (g & 3) * STAGE + SLOT, &maps.n, 0, g * 64, m4 * 4, BAR(bar + (g & 3))); };
      delay_until(c0, FK_ADLY);
      if (lane == 0) { loadA(0); if (FK_A1EARLY) loadA(1); TRACE(63); }
      asm volatile("add.u32 %0, %0, 1;" : "+r"(tag)::"memory");
      delay_until(c0, FK_POLL0 + (early & pp.zero));
#pragma unroll 1
      for (int gi = 0; gi < 2; gi++) {
        int it = 0;
        const unsigned* cp = &pp.cnt[gi * 32];
        if (gi >= FK_NOHINT) while ((int)(ld_rlx(cp) - tag * 128u) < 0) { if (++it > SPIN_LIMIT) SPIN_FAIL(0x201); }
        if (gi && FK_NOHINT == 2) delay_until(c0, FK_POLL0 + 600);
        if (lane == 0) {
          if (gi == 0) TRACE(2);
          loadB(2 * gi, B_LAND);
          if (gi) loadA(2);
          if (gi || !FK_A1EARLY) loadA(2 * gi + 1);
          loadB(2 * gi + 1, B_LAND);
        }
        __syncwarp();
      }
      if (lane == 0) { prefetch_tmap(&maps.p); prefetch_tmap(&maps.wd[j]); }
      const unsigned tgt = tag * 128u;
      unsigned pend = ld_rlx(&pp.cnt[2 * 32]);
      const char* pfa = piece_addr(pp, b, lane);
      const uint32_t pfn = (lane >> 2) == 2 || lane >= 20 ? 8192 : 7168;
      auto produce1 = [&](int g0, int g1) {
#pragma unroll 1
        for (int g = g0; g < g1; g++) {
          mbar_wait(BAR(B_EMPTYH + (g & 3)), ((g >> 2) - 1) & 1);
          mbar_wait(BAR(B_EMPTY + (g & 3)), ((g >> 2) - 1) & 1);
          if (!(g & 1)) {
            if ((int)(pend - tgt) < 0) {
              int it = 0;
              while ((int)(ld_rlx(&pp.cnt[(g >> 1) * 32]) - tgt) < 0) { if (++it > SPIN_LIMIT) SPIN_FAIL(0x20c); }
            }
            fence_async_global();
            pend = ld_rlx(&pp.cnt[((g >> 1) + 1) * 32]);
          }
          if (lane == 0) {
            loadA(g); loadB(g, B_FULL);
          }
          if (lane == g - FK_PF0 && lane >= FK_PFSKIP) pf_bulk(pfa, pfn);
          __syncwarp();
        }
      };
      produce1(4, FK_TG);
      take(IntC<0>{});
      produce1(FK_TG, FK_TU);
      take(IntC<1>{});
      produce1(FK_TU, 32);
      int sib = 0, pc = 0;
      auto produce2 = [&](int q0, int q1) {
#pragma unroll 1
        for (int q = q0; q < q1; q++) {
          const int s = q & 3, k0 = sibling(m4, sib) * 256 + pc * 64;
          const uint32_t sa = sb + s * STAGE;
          mbar_wait(BAR(B_EMPTY + s), ((q >> 2) + 1) & 1);
          if (lane == 0) {
            mbar_expect_tx(BAR(B_FULL + s), 2 * SLOT);
            tma_2d(sa + SLOT, &maps.wd[j], k0, m4 * 256, BAR(B_FULL + s));
            if (q < 4) mbar_arrive(BAR(B_FULL + s));
          }
          __syncwarp();
          if (q >= 4) {
            mbar_wait(BAR(B_PL + s), 0);
            if (lane == 0) { mbar_expect_tx(BAR(B_LAND + s), SLOT); tma_2d(sa, &maps.p, k0, j * S_ + t * 128, BAR(B_LAND + s)); }
            if (++sib == 4) { sib = 1; pc++; }
          } else if (++pc == 4) { pc = 0; sib = 1; }
          if (lane == 32 + q - FK_PF0 && lane < 27) pf_bulk(pfa, pfn);
          if (q >= FK_XQ && q < FK_XQ + 4 * FK_XS && (q - FK_XQ) % FK_XS == 0) {
            const int w = (q - FK_XQ) / FK_XS;
            mbar_wait(BAR(B_XF), 0);
            if (lane == 0) { mbar_expect_tx(BAR(B_X), 8192); tma_2d(sb + SPARE + w * 8192, &maps.x, m4 * 256 + w * 64, t * 128 + j * 64, BAR(B_X)); }
          }
          __syncwarp();
        }
      };
      produce2(0, 16);
      if (moe) {
        mbar_wait(BAR(B_EMPTY + 0), 1);
        if (lane == 0) {
          mbar_expect_tx(BAR(B_GU), 49152);
#pragma unroll 1
          for (int i = 0; i < 3; i++) {
            tma_2d(sb + i * SLOT, &maps.wg, b * 32, 512 + i * 128, BAR(B_GU));
            tma_2d(sb + i * SLOT + 8192, &maps.wu, b * 32, 512 + i * 128, BAR(B_GU));
          }
        }
        mbar_wait(BAR(B_EMPTY + 1), 1);
        if (FK_WGATE >= 0) mbar_wait(BAR(B_RECV + FK_WGATE), 0);
        if (lane == 0) {
          mbar_expect_tx(BAR(B_GU), 16384);
          tma_2d(sb + STAGE + SLOT, &maps.wg, b * 32, 896, BAR(B_GU));
          tma_2d(sb + STAGE + SLOT + 8192, &maps.wu, b * 32, 896, BAR(B_GU));
        }
#pragma unroll 1
        for (int i = 0; i < 4; i++) {
          if (i == 1) mbar_wait(BAR(B_EMPTY + 2), 1);
          if (i == 3) mbar_wait(BAR(B_XDONE), 0);
          if (i >= FK_DNWIN) mbar_wait(BAR(B_DN + i - FK_DNWIN), 0);
          if (lane == 0) {
            mbar_expect_tx(BAR(B_DN + i), 16384);
            tma_3d(sb + dn_box(i), &maps.wdn, 0, b * 32, i * 4, BAR(B_DN + i));
          }
        }
      }
      __syncwarp();
    } else if (warp == 1) {
      asm volatile("add.u32 %0, %0, 1;" : "+r"(tag)::"memory");
      if (lane == 0) prefetch_tmap(&maps.ps);
      delay_until(c0, FK_WS1DLY);
      float a0 = __uint_as_float(early & pp.zero), a1 = __uint_as_float(ws_touch(128) & pp.zero);
      auto rowsum = [&](int g0, int g1) {
        const uint32_t rb = sb + (m4 * 32 + lane) * 128 + ((lane & 7) << 4);
#pragma unroll 1
        for (int g = g0; g < g1; g++) {
          const int s = g & 3;
          mbar_wait(BAR(B_FULL + s), (g >> 2) & 1);
          uint4 u[8];
#pragma unroll
          for (int c = 0; c < 8; c++) u[c] = lds128u((rb ^ (uint32_t)(c << 4)) + s * STAGE);
#pragma unroll
          for (int c = 0; c < 8; c += 2) { a0 += sum8(u[c]); a1 += sum8(u[c + 1]); }
          if (lane == 0) mbar_arrive(BAR(B_EMPTYH + s) + ((__float_as_uint(a0) | __float_as_uint(a1)) & pp.zero));
        }
      };
      rowsum(0, FK_TG - 2);
      take(IntC<0>{});
      rowsum(FK_TG - 2, 28);
      mbar_wait(BAR(B_MODOK), 0);
      a0 += lds32(sb + RS_OFF + 256 + lane * 4);
      __syncwarp();
      uint2* rsp = &pp.mail->rs[(j * 16 + t) * 128 + lane];
      st_msg8(rsp + m4 * 32, __float_as_uint(a0 + a1), tag);
      {
        uint2 m[4]; int it = 0;
        while (true) {
#pragma unroll
          for (int i = 0; i < 4; i++) m[i] = ld_msg8(rsp + 32 * i);
          if (__all_sync(~0u, m[0].y == tag && m[1].y == tag && m[2].y == tag && m[3].y == tag)) break;
          if (++it > SPIN_LIMIT) SPIN_FAIL(0x208);
        }
#pragma unroll
        for (int i = 0; i < 4; i++) sts32u(sb + RS_OFF + (lane + 32 * i) * 4, pack_bf16(__uint_as_float(m[i].x), __uint_as_float(m[i].x)));
      }
      __syncwarp();
      if (lane == 0) { mbar_arrive(BAR(B_T1)); TRACE(11); }
      take(IntC<1>{});
      {
        uint32_t cn = 0;
#pragma unroll 1
        for (int i = 0; i < 8; i++) {
          const int q = i >> 1, half = (i & 1) ? j : 1 - j;
          if (i < 4) mbar_wait(BAR(B_PRDY + (i & 1) * 2 + (q | (!FK_LF && i == 0))), 0);
          if (i) delay_until(cn, FK_PPACE);
          cn = clk();
          if (lane == 0) {
            tma_store_2d(&maps.ps, sb + q * STAGE + half * 8192, m4 * 256 + q * 64, j * S_ + t * 128 + half * 64);
            bulk_commit();
            if (i && !(i & 1)) { bulk_wait_read<1>(); mbar_arrive(BAR(B_PL + q - 1)); }
          }
          __syncwarp();
        }
        if (lane == 0) { bulk_wait_read<0>(); mbar_arrive(BAR(B_PL + 3)); }
        if (lane == 0) TRACE(8);
      }
      named_bar<7, 64>();
      delay_until(clk(), FK_E2DLY);
      const uint2* cp = &pp.mail->cand[lane];
      auto select = [&](uint2 m) {
        if (!__all_sync(~0u, m.y != 0)) return false;
        uint32_t k1, k2;
        warp_top2(m.y, m.x, k1, k2);
        if (lane == 0) { sts64u(sb + SEL_OFF, k1, k2); mbar_arrive(BAR(B_SEL)); TRACE(19); }
        return true;
      };
      int it = 0;
      while (!select(ld_msg8(cp))) { delay_until(clk(), -(FK_E2GAP)); if (++it > SPIN_LIMIT) SPIN_FAIL(0x206); }
    } else {
      const int kh = warp - 2;
      const uint32_t reg = sb + SPARE + kh * 16384;
      const uint4 cw0 = ldg_nc(pp.c + (kh * 64 + lane) * 16), cw1 = ldg_nc(pp.c + (kh * 64 + lane + 32) * 16);
#pragma unroll 1
      for (int i = 0; i < 2; i++) {
        const uint4 cw4 = i ? cw1 : cw0;
        const uint32_t ad = reg + 12288 + (lane + 32 * i) * 32;
        sts128(ad, round_bf16(silu_f(bf_lo(cw4.x))), round_bf16(silu_f(bf_hi(cw4.x))), round_bf16(silu_f(bf_lo(cw4.y))), round_bf16(silu_f(bf_hi(cw4.y))));
        sts128(ad + 16, round_bf16(silu_f(bf_lo(cw4.z))), round_bf16(silu_f(bf_hi(cw4.z))), round_bf16(silu_f(bf_lo(cw4.w))), round_bf16(silu_f(bf_hi(cw4.w))));
      }
      asm volatile("add.u32 %0, %0, 1;" : "+r"(tag)::"memory");
      if (lane == 0) prefetch_tmap(&maps.wm);
      unsigned ph = 0;
      if (kh == 0) {
#pragma unroll 1
        for (int s = 0; s < 4; s++) {
          const uint32_t ra = sb + s * STAGE + SLOT + lane * 128 + ((lane & 7) << 4);
          int it = 0;
          while (true) {
            mbar_wait(BAR(B_LAND + s), (ph >> s) & 1);
            ph ^= 1u << s;
            if (lane == 0 && it == 0) TRACE(120 + s);
            uint32_t bad = 0;
#pragma unroll
            for (int u = 0; u < 8; u++) bad |= lds32u(ra + u * 4096) ^ tag;
            if (!__any_sync(~0u, bad & 1)) break;
            if (lane == 0) { mbar_expect_tx(BAR(B_LAND + s), 2 * SLOT); tma_3d(sb + s * STAGE + SLOT, &maps.n, 0, s * 64, m4 * 4, BAR(B_LAND + s)); TRACE(92 + s); }
            if (++it > (1 << 16)) SPIN_FAIL(0x203);
          }
          if (lane == 0) mbar_arrive(BAR(B_FULL + s));
        }
      } else {
        named_bar<8, 96>();
        uint32_t rbk = ld_rlx(pp.n + (size_t)((2 + (lane >> 4)) * 128 + rb) * (2 * D_) + (lane & 15) * 128);
        uint4 w[FK_GX - FK_G0][4];
        delay_until(c0, FK_ROW8DLY);
#pragma unroll
        for (int k = 0; k < FK_GX - FK_G0; k++)
#pragma unroll
          for (int i = 0; i < 4; i++) w[k][i] = ldg_nc(pp.x + (size_t)((FK_G0 + k) * 128 + rb) * (2 * D_) + lane * 16 + i * 512);
        uint32_t z = landed(rbk, pp.zero);
        if (lane < 2) red_add(&pp.cnt[(2 + lane) * 32], 1 + z);
        named_bar<9, 32 * (FK_G0 - 3)>();
        rbk = 0;
#pragma unroll
        for (int g = 4; g < FK_G0; g += 2) rbk |= ld_rlx(pp.n + (size_t)(min(g + (lane >> 4), FK_G0 - 1) * 128 + rb) * (2 * D_) + (lane & 15) * 128);
        z = landed(rbk, pp.zero);
        if (lane >= 4 && lane < FK_G0) red_add(&pp.cnt[lane * 32], 1 + z);
#pragma unroll
        for (int k = 0; k < FK_GX - FK_G0; k++) {
          ln_row(w[k]);
#pragma unroll
          for (int i = 0; i < 4; i++) stg128(pp.n + (size_t)((FK_G0 + k) * 128 + rb) * (2 * D_) + lane * 16 + i * 512, w[k][i]);
        }
        z = landed(ld_rlx(pp.n + (size_t)(min(FK_G0 + (lane >> 4), FK_GX - 1) * 128 + rb) * (2 * D_) + (lane & 15) * 128), pp.zero);
        if (lane >= FK_G0 && lane < FK_GX) red_add(&pp.cnt[lane * 32], 1 + z);
        if (lane == 0) TRACE(56);
      }
      {
        float acc[3][8];
        uint32_t sad[3];
#pragma unroll
        for (int a = 0; a < 3; a++) {
          sad[a] = reg + 12288 + ((32 * a + lane) / 6) * 4;
#pragma unroll
          for (int i = 0; i < 8; i++) acc[a][i] = 0.f;
        }
        const char* wpf = pp.wm + (size_t)kh * (512 * 12 * D_) + b * 6144;
        const char* wsrc = (j ? pp.ws_im : pp.ws_re) + (size_t)(t * 128 + m4 * 32 + kh * 16 - 16) * (2 * S_) + 28 * 128 + lane * 16;
        if (FK_WMPF && lane == 0) pf_bulk(wpf, 6144);
        uint32_t cn = c0 + FK_GSTART + kh * (FK_PACE / 2);
        auto request = [&](int c) {
          mbar_expect_tx(BAR(B_WM + kh * 2 + (c & 1)), 6144 + ((__float_as_uint(acc[0][0]) | __float_as_uint(acc[1][0]) | __float_as_uint(acc[2][0])) & pp.zero));
          tma_2d_hint(reg + (c & 1) * 6144, &maps.wm, b * 48, kh * 512 + c * 64, BAR(B_WM + kh * 2 + (c & 1)), pol_first);
        };
        uint4 e[4];
#pragma unroll 1
        for (int c = -2; c < 8; c++) {
          while ((int)(clk() - cn) < 0) __nanosleep(40);
          cn += c < 0 ? FK_PACE0 : FK_PACE;
          if (lane == 0) {
            if (FK_WMPF && c < 5) pf_bulk(wpf + (size_t)(c + 3) * (64 * 12 * D_), 6144);
          }
          __syncwarp();
          if (c < 0) {
            if (lane == 0) request(c + 2);
            __syncwarp();
            continue;
          }
          if (c >= 4) {
            const float v0 = sum8(e[0]), v1 = sum8(e[1]), v2 = sum8(e[2]), v3 = sum8(e[3]);
            const bool u4 = lane & 16, u3 = lane & 8;
            const float w0 = (u4 ? v2 : v0) + __shfl_xor_sync(~0u, u4 ? v0 : v2, 16), w1 = (u4 ? v3 : v1) + __shfl_xor_sync(~0u, u4 ? v1 : v3, 16);
            float v = (u3 ? w1 : w0) + __shfl_xor_sync(~0u, u3 ? w0 : w1, 8);
            v += __shfl_xor_sync(~0u, v, 4); v += __shfl_xor_sync(~0u, v, 2); v += __shfl_xor_sync(~0u, v, 1);
            if (!(lane & 7)) sts32(sb + RS_OFF + 256 + (kh * 16 + c * 4 - 16 + (lane >> 3)) * 4, v);
          }
          if (c >= 3 && c < 7) {
#pragma unroll
            for (int i = 0; i < 4; i++) e[i] = ldg_nc(wsrc + (size_t)(c * 4 + 4 + i) * (2 * S_));
          }
          mbar_wait(BAR(B_WM + kh * 2 + (c & 1)), (c >> 1) & 1);
#pragma unroll
          for (int u = 0; u < 12; u++) {
            const uint4 v = lds128u(reg + (c & 1) * 6144 + lane * 16 + u * 512);
            const float sc = lds32(sad[u % 3] + (u / 3) * 64);
            float (&ac)[8] = acc[u % 3];
            ac[0] = fmaf(sc, bf_lo(v.x), ac[0]); ac[1] = fmaf(sc, bf_hi(v.x), ac[1]);
            ac[2] = fmaf(sc, bf_lo(v.y), ac[2]); ac[3] = fmaf(sc, bf_hi(v.y), ac[3]);
            ac[4] = fmaf(sc, bf_lo(v.z), ac[4]); ac[5] = fmaf(sc, bf_hi(v.z), ac[5]);
            ac[6] = fmaf(sc, bf_lo(v.w), ac[6]); ac[7] = fmaf(sc, bf_hi(v.w), ac[7]);
          }
#pragma unroll
          for (int a = 0; a < 3; a++) sad[a] += 256;
          __syncwarp();
          if (lane == 0 && c < 6) request(c + 2);
        }
        __syncwarp();
#pragma unroll
        for (int a = 0; a < 3; a++) {
          sts128(reg + (32 * a + lane) * 32, acc[a][0], acc[a][1], acc[a][2], acc[a][3]);
          sts128(reg + (32 * a + lane) * 32 + 16, acc[a][4], acc[a][5], acc[a][6], acc[a][7]);
        }
        __syncwarp();
        float s0 = 0.f, s1 = 0.f;
#pragma unroll 8
        for (int m = 0; m < 16; m++) { const float2 v = lds64(reg + (lane < 24 ? lane * 8 : 0) + m * 192); s0 += v.x; s1 += v.y; }
        if (kh == 0) sts64(sb + RS_OFF + lane * 8, s0, s1);
        if (lane == 0) TRACE(80 + kh);
        named_bar<5, 64>();
        if (kh == 1) {
          const float2 p = lds64(sb + RS_OFF + lane * 8);
          unsigned* dst = pp.mod + b * 24 + (lane < 24 ? lane : 0);
          if (lane < 24) st_rlx(dst, pack_bf16(s0 + p.x, s1 + p.y));
          uint32_t rbk = ld_rlx(dst);
          if (b == 0) { st_msg8(&pp.mail->cand[lane], 0, 0); rbk |= ld_rlx(&pp.mail->cand[lane]); }
          const uint32_t z = landed(rbk, pp.zero);
          if (lane == 0) { red_add(&pp.cnt[16 * 32], 1 + z); mbar_arrive(BAR(B_MODOK)); TRACE(9); }
          __syncwarp();
        }
      }
      if (kh == 0) {
        if (lane == 0) { mbar_arrive(BAR(B_MODOK)); TRACE(57); }
#pragma unroll 1
        for (int i = 0; i < 4; i++) {
          const int w = i ^ 2;
          if (lane == 0) {
            if (moe) { mbar_expect_tx(BAR(B_WB + w), 8192); tma_2d_hint(sb + SPARE + w * 8192, &maps.wg, b * 32, w * 128, BAR(B_WB + w), pol_first); }
            else mbar_arrive(BAR(B_WB + w));
          }
          __nanosleep(FK_BSLEEP);
        }
        take(IntC<0>{});
        take(IntC<1>{});
        if (lane == 0) TRACE(98);
        int sib = 1, pc = 0;
#pragma unroll 1
        for (int q = 4; q < 16; q++) {
          const int s = q & 3;
          const uint32_t ra = sb + s * STAGE + lane * 128 + ((lane & 7) << 4);
          int it = 0;
          while (true) {
            mbar_wait(BAR(B_LAND + s), (ph >> s) & 1);
            ph ^= 1u << s;
            const uint32_t bad = ((lds32u(ra) ^ tag) | (lds32u(ra + 4096) ^ tag) | (lds32u(ra + 8192) ^ tag) | (lds32u(ra + 12288) ^ tag)) & 1;
            if (!__any_sync(~0u, bad)) break;
            if (lane == 0) {
              mbar_expect_tx(BAR(B_LAND + s), SLOT);
              tma_2d(sb + s * STAGE, &maps.p, sibling(m4, sib) * 256 + pc * 64, j * S_ + t * 128, BAR(B_LAND + s));
            }
            if (++it > (1 << 16)) SPIN_FAIL(0x202);
          }
          if (lane == 0) mbar_arrive(BAR(B_FULL + s));
          if (++sib == 4) { sib = 1; pc++; }
        }
        if (lane == 0) TRACE(99);
      } else {
        take(IntC<0>{});
        {
          const unsigned tgt = tag * 128u; int it = 0;
          while ((int)(ld_rlx(&pp.cnt[16 * 32]) - tgt) < 0) { __nanosleep(100); if (++it > SPIN_LIMIT) SPIN_FAIL(0x204); }
        }
        if (lane == 0) TRACE(10);
        {
          const uint32_t sgn = j ? 0x80008000u : 0u;
          uint32_t sa[4], ca[4]; uint4 sv[4], cv[4], wr[4];
#pragma unroll
          for (int i = 0; i < 4; i++) {
            const int p = lane + 32 * i;
            sa[i] = ld_rlx(pp.mod + m4 * 128 + p); ca[i] = ld_rlx(pp.mod + 512 + m4 * 128 + p);
            sv[i] = ld_msg(reinterpret_cast<const uint4*>(pp.mod + 1536) + p); cv[i] = ld_msg(reinterpret_cast<const uint4*>(pp.mod + 2048) + p);
            wr[i] = ldg_nc(pp.wr + p * 16);
          }
          float c1 = 0.f, c2 = 0.f;
#pragma unroll
          for (int i = 0; i < 4; i++) {
            const int p = lane + 32 * i;
            sts64(sb + T1_OFF + ((p >> 3) * 4 + (p & 3)) * 16 + ((p >> 2) & 1) * 8, __uint_as_float(add1_bf2(ca[i]) ^ sgn), __uint_as_float(sa[i] ^ sgn));
            const uint32_t s4[4] = {sv[i].x, sv[i].y, sv[i].z, sv[i].w}, c4[4] = {cv[i].x, cv[i].y, cv[i].z, cv[i].w}, w4[4] = {wr[i].x, wr[i].y, wr[i].z, wr[i].w};
#pragma unroll
            for (int u = 0; u < 4; u++) {
              const uint32_t A = add1_bf2(c4[u]);
              c1 = fmaf(bf_lo(A), bf_lo(w4[u]), c1); c1 = fmaf(bf_hi(A), bf_hi(w4[u]), c1);
              c2 = fmaf(bf_lo(s4[u]), bf_lo(w4[u]), c2); c2 = fmaf(bf_hi(s4[u]), bf_hi(w4[u]), c2);
            }
          }
#pragma unroll
          for (int o = 16; o; o >>= 1) { c1 += __shfl_xor_sync(~0u, c1, o); c2 += __shfl_xor_sync(~0u, c2, o); }
          __syncwarp();
          if (lane == 0) { sts128(sb + CST_OFF, c1, c2, __uint_as_float(tag), 0.f); mbar_arrive(BAR(B_T1)); TRACE(30); }
        }
        take(IntC<1>{});
        const int G = lane >> 2, q = lane & 3, p0 = m4 * 128 + G * 16 + q;
        mbar_wait(BAR(B_PRDY + 1), 0);
        mbar_wait(BAR(B_PRDY + 3), 0);
        uint32_t ga[4], hi[4], lo[4];
#pragma unroll
        for (int u = 0; u < 4; u++) {
          ga[u] = ld_rlx(pp.mod + 1024 + p0 + 4 * u);
          const uint32_t cb = ld_rlx(pp.mod + 2048 + p0 + 4 * u), wr = __ldg(reinterpret_cast<const uint32_t*>(pp.wr) + p0 + 4 * u);
          const float w0 = bf_lo(add1_bf2(cb)) * bf_lo(wr), w1 = bf_hi(add1_bf2(cb)) * bf_hi(wr);
          hi[u] = pack_bf16(w0, w1);
          lo[u] = pack_bf16(w0 - bf_lo(hi[u]), w1 - bf_hi(hi[u]));
        }
        sts128u(sb + GA_OFF + lane * 16, ga[0], ga[1], ga[2], ga[3]);
        sts128u(sb + W_OFF + G * 144 + q * 16, hi[0], hi[1], hi[2], hi[3]);
        sts128u(sb + W_OFF + G * 144 + 64 + q * 16, lo[0], lo[1], lo[2], lo[3]);
        sts32u(sb + W_OFF + G * 144 + 128 + q * 4, 0x3F803F80u);
        mbar_wait(BAR(B_PL + 3), 0);
        __nanosleep(FK_RSLEEP);
        const uint4 sv = make_uint4(SENT, SENT, SENT, SENT);
#pragma unroll 1
        for (int i = 0; i < 7; i++) stg128(&pp.mail->part[(size_t)b * (NMOE * 2) + lane + 32 * i], sv);
#pragma unroll 1
        for (int i = 0; i < 2; i++) {
          stg128(&pp.mail->stats[(blk * 4 + m4) * 64 + lane + 32 * i], sv);
          stg128(&pp.mail->rowh[(blk * 2 + i) * 128 + m4 * 32 + lane], sv);
          stg128(&pp.mail->rowx[(blk * 2 + i) * 128 + m4 * 32 + lane], sv);
        }
        if (lane == 0) { red_max8(&pp.mail->cand[blk], 1, 0); red_add(&pp.cnt[18 * 32], 1); }
        __syncwarp();
        if (lane == 0) { fence_gpu(); mbar_arrive(BAR(B_T2)); TRACE(97); }
      }
    }
    mbar_wait(BAR(B_SEL), 0);
    if (moe) gate_up(pp, wf, sb, scr, warp, lane);
    if (warp == 1) {
      const uint2 sel = lds64u(sb + SEL_OFF);
      const int n = (lane >> 3) & 1;
      const int col = (b >> 4) * 128 + (lane & 1) * 64 + ((b >> 2) & 3) * 16 + (b & 3) * 2 + ((lane >> 1) & 1) + (lane >> 4) * 8;
      const int slot = sel_slot(sel, n) * 512, wofs = slot + ((col >> 5) * 4 + ((col >> 1) & 3)) * 4 + ((col >> 3) & 3);
      const uint32_t gbp = ld_rlx(pp.mod + 2560 + (col >> 1));
      uint32_t hp, xp; int it = 0;
      while (true) {
        hp = ld_rlx(reinterpret_cast<const uint32_t*>(pp.mail->rowh) + wofs); xp = ld_rlx(reinterpret_cast<const uint32_t*>(pp.mail->rowx) + slot + (col >> 1));
        if (__all_sync(~0u, hp != SENT && xp != SENT)) break;
        if (++it > SPIN_LIMIT) SPIN_FAIL(0x2ff);
      }
      const float sg = round_bf16(sigmoid_f(round_bf16(key_val(n ? sel.y : sel.x))));
      const bool odd = col & 1;
      float gbv = odd ? bf_hi(gbp) : bf_lo(gbp), hv = odd ? bf_hi(hp) : bf_lo(hp), xv = odd ? bf_hi(xp) : bf_lo(xp);
      char* optr = pp.out + ((size_t)key_row(n ? sel.y : sel.x) * D_ + col) * 2;
      asm volatile("" : "+f"(gbv), "+f"(hv), "+f"(xv), "+l"(optr));
      const int gq = lane >> 2;
      const uint32_t one = (lane & 1) == (gq >> 2) ? ((gq & 1) ? 0x3F800000u : 0x00003F80u) : 0u;
      const uint32_t s0 = (gq & 2) ? 0u : one, s1 = (gq & 2) ? one : 0u;
      const uint4* src = &pp.mail->part[(size_t)b * (NMOE * 2) + lane];
      uint4 m[7];
      it = 0;
      while ((int)(ld_rlx(&pp.cnt[18 * 32]) - tag * (NCTA + NMOE)) < 0) { if (++it > SPIN_LIMIT) SPIN_FAIL(0x20d); }
      delay_until(clk(), FK_E4DLY);
      it = 0;
      while (true) {
        bool ok = true;
#pragma unroll
        for (int i = 0; i < 7; i++) m[i] = ld_msg(src + 32 * i);
#pragma unroll
        for (int i = 0; i < 7; i++) ok &= m[i].x != SENT;
        if (__all_sync(~0u, ok)) break;
        if (++it > SPIN_LIMIT) SPIN_FAIL(0x20b);
      }
      if (lane == 0) TRACE(23);
      float c[3][4];
#pragma unroll
      for (int i = 0; i < 3; i++) { c[i][0] = c[i][1] = c[i][2] = c[i][3] = 0.f; }
#pragma unroll
      for (int i = 0; i < 7; i++) mma_16816(c[i % 3], m[i].x, m[i].y, m[i].z, m[i].w, s0, s1);
#pragma unroll
      for (int i = 0; i < 4; i++) c[0][i] += c[1][i] + c[2][i];
      const bool u4 = lane & 16, u3 = lane & 8;
      const float a0 = (u4 ? c[0][2] : c[0][0]) + __shfl_xor_sync(~0u, u4 ? c[0][0] : c[0][2], 16), a1 = (u4 ? c[0][3] : c[0][1]) + __shfl_xor_sync(~0u, u4 ? c[0][1] : c[0][3], 16);
      float y = (u3 ? a1 : a0) + __shfl_xor_sync(~0u, u3 ? a0 : a1, 8);
      y += __shfl_xor_sync(~0u, y, 4);
      const float upd = round_bf16(round_bf16(y) * sg);
      const uint32_t o = pack_bf16(fmaf(gbv, hv + upd, xv), 0.f);
      if (!(lane & 4)) asm volatile("st.global.u16 [%0], %1;" ::"l"(optr), "h"((unsigned short)o) : "memory");
      if (lane == 0) { TRACE(24); TRACE_CLK(54); if (b == 0) pp.cnt[17 * 32] = tag; }
    }
  } else {
    const int cw = (warp - 4) >> 2;
    const int wq = warp & 3;
    const int wtid = tid & 127;
    const int gq = lane >> 2, q4 = lane & 3;
    const bool lag = cw == j;
    const bool elect = wtid == 0;
    const uint32_t rel = wtid < 2 ? mapa(BAR(B_EMPTY), wtid) : 0;

    if (cw) named_bar<3, 256>(); else named_bar<0, 256>();
    if (tid == 128) TRACE(124);
    asm volatile("barrier.cluster.wait.acquire.aligned;" ::: "memory");
    if (tid == 128) TRACE(125);

    const int mrow = wq * 16 + (lane & 7) + ((lane >> 3) & 1) * 8;
    {
      float acc[128];
      gemm_phase<1, 0, 32>(pp, acc, sb, cw, lag, elect, rel);
      mbar_wait(BAR(B_T1), 0);
      const uint32_t tad = sb + T1_OFF + q4 * 16;
      uint4 tb[16];
#pragma unroll
      for (int c = 0; c < 4; c++) tb[c] = lds128u(tad + c * 64);
      const uint32_t rs0 = lds32u(sb + RS_OFF + (cw * 64 + wq * 16 + gq) * 4), rs1 = lds32u(sb + RS_OFF + (cw * 64 + wq * 16 + gq + 8) * 4);
      const uint32_t dst = sb + cw * 8192 + mrow * 128, pb = BAR(B_PRDY + (lag ? 2 : 0));
      const uint32_t pmask = q4 ? 0u : 1u, par = lds32u(sb + CST_OFF + 8);
      gemm_finish(acc, rel);
      if (elect) { TRACE(lag ? 5 : 4); if (lag) TRACE_CLK(51); }
#pragma unroll
      for (int i = 0; i < 16; i++) {
        uint32_t r[4];
        const int o = 8 * i;
        r[0] = fma_bf2(pack_bf16(acc[o], acc[o + 1]), tb[i].x, mul_bf2(rs0, tb[i].y));
        r[1] = fma_bf2(pack_bf16(acc[o + 2], acc[o + 3]), tb[i].x, mul_bf2(rs1, tb[i].y));
        r[2] = fma_bf2(pack_bf16(acc[o + 4], acc[o + 5]), tb[i].z, mul_bf2(rs0, tb[i].w));
        r[3] = fma_bf2(pack_bf16(acc[o + 6], acc[o + 7]), tb[i].z, mul_bf2(rs1, tb[i].w));
        if (!(i & 3)) { r[0] = (r[0] & ~pmask) | (par & pmask); r[1] = (r[1] & ~pmask) | (par & pmask); }
        if (i < 12) tb[i + 4] = lds128u(tad + (i + 4) * 64);
        stsm_x4(dst + (i >> 2) * STAGE + (uint32_t)(((((2 * i) & 7) + (lane >> 4)) ^ (lane & 7)) << 4), r[0], r[1], r[2], r[3]);
        if ((i == 3 && (lag || FK_LF)) || i == 15) {
          fence_async_smem();
          __syncwarp();
          if (lane == 0) mbar_arrive(pb + (i >> 3) * 8);
        }
      }
      if (FK_WB) mbar_wait(pb + 8, 0);
    }
    if (elect) TRACE(lag ? 7 : 6);
    float acc[128];
    gemm_phase<0, 32, 48>(pp, acc, sb, cw, lag, elect, rel);

    if (!lag) {
      const uint32_t rdst = mapa(sb + STAGE + j * 8192 + wtid * 16, j ^ 1), rbar = mapa(BAR(B_RECV), j ^ 1);
      mbar_wait(BAR(B_PEER), 0);
      gemm_finish(acc, rel);
      if (elect) { mbar_arrive_cluster(rbar + (B_PEER + 1 - B_RECV) * 8); TRACE(12); }
#pragma unroll
      for (int i = 0; i < 16; i++) {
        const int o = 8 * i;
        if (i == 8) mbar_wait(BAR(B_PEER + 1), 0);
        if (i == 12) mbar_wait(BAR(B_EMPTY + 1), 1);
        asm volatile("st.async.weak.shared::cluster.mbarrier::complete_tx::bytes.v4.b32 [%0], {%1, %2, %3, %4}, [%5];"
                     ::"r"(i < 12 ? rdst + (i >> 2) * STAGE + (i & 3) * 2048 : rdst + (1 - 2 * j) * 8192 + (i & 3) * 2048),
                       "r"(pack_bf16(acc[o], acc[o + 1])), "r"(pack_bf16(acc[o + 2], acc[o + 3])), "r"(pack_bf16(acc[o + 4], acc[o + 5])),
                       "r"(pack_bf16(acc[o + 6], acc[o + 7])), "r"(rbar + (i >> 2) * 8) : "memory");
      }
      if (elect) TRACE(13);
      if (b < NMOE) {
        uint32_t wf[128];
        named_bar<1, 256>();
        mbar_wait(BAR(B_GU), 0);
        const uint32_t box = sb + (wq < 3 ? wq : 4) * SLOT;
        take_box<0>(wf, box, lane);
        take_box<1>(wf, box + 8192, lane);
        if (elect) TRACE(26);
        mbar_wait(BAR(B_SEL), 0);
        gate_up(pp, wf, sb, scr, 4 + wq, lane);
        if (elect) red_add(&pp.cnt[18 * 32], 1);
        if (FK_QUIET) named_bar<8, 256>();
      }
      OutTab tb;
      {
        const uint4* mp = reinterpret_cast<const uint4*>(pp.mod) + m4 * 32 + lane;
        out_tab(tb, ldg128(mp + 512), ldg128(mp + 384), ldg128(mp + 640));
      }
      mbar_wait(BAR(B_SEL), 0);
      const uint2 sel = lds64u(sb + SEL_OFF), cnd = lds64u(sb + TOP_OFF + 32);
      char* odst = pp.out + (size_t)blk * (64 * 2 * D_) + m4 * 512 + lane * 16;
      const int g0 = blk * 64 + wq * 16;
      mbar_wait(BAR(B_OUT), 0);
      const uint32_t done = lds32u(sb + TOP_OFF + 48 + wq * 4);
      out_group(tb, sb, scr, wq * 16, ((0xFFFFu & (0xFFFFu << done)) | row_bit(cnd.x, g0) | row_bit(cnd.y, g0)) & ~(row_bit(sel.x, g0) | row_bit(sel.y, g0)),
                lane, odst, FK_OPACE2, 0);
      if (elect) TRACE(28);
    } else {
      mbar_wait(BAR(B_T2), 0);
      uint32_t xa[64];
      float dl[2][4], dq[4][4];
#pragma unroll
      for (int i = 0; i < 4; i++) { dl[0][i] = dl[1][i] = dq[0][i] = dq[1][i] = dq[2][i] = dq[3][i] = 0.f; }
      {
        uint32_t wad = sb + W_OFF + ((gq & 2) ? 128 : (gq & 1) * 64 + q4 * 16), gad = sb + GA_OFF + q4 * 16;
        uint32_t rsrc = sb + STAGE + (1 - j) * 8192 + wtid * 16, xad = sb + SPARE + mrow * 128 + (uint32_t)(((lane >> 4) ^ (lane & 7)) << 4);
        asm volatile("" : "+r"(wad), "+r"(gad), "+r"(rsrc), "+r"(xad));
        uint4 rv[16], wb[8], ga[8];
        uint32_t xf[16][4];
        auto loadx = [&](int i) { ldsm_x4((xad ^ (uint32_t)((i & 3) << 5)) + (i >> 2) * 8192, xf[i][0], xf[i][1], xf[i][2], xf[i][3]); };
        auto loadr = [&](int i) { rv[i] = lds128u(i < 12 ? rsrc + (i >> 2) * STAGE + (i & 3) * 2048 : rsrc + (2 * j - 1) * 8192 + (i & 3) * 2048); };
        auto loadt = [&](int h) { loadx(2 * h); loadx(2 * h + 1); ga[h] = lds128u(gad + h * 64); wb[h] = lds128u(wad + h * 144); };
        mbar_wait(BAR(B_X), 0);
        mbar_wait(BAR(B_RECV), 0);
        loadx(0); loadr(0); ga[0] = lds128u(gad);
        mbar_wait(BAR(B_RECV + 1), 0);
        gemm_finish(acc, rel);
        if (elect) { TRACE(14); TRACE_CLK(53); }
#pragma unroll
        for (int u = 0; u < 8 * FK_PK; u++) {
          xa[u] = pack_bf16(acc[2 * u], acc[2 * u + 1]);
          if (u == 15) { loadx(1); loadr(1); wb[0] = lds128u(wad); }
        }
#pragma unroll
        for (int h = 0; h < 8; h++) {
          if (h == FK_W2 || h == 6) mbar_wait(BAR(B_RECV + (h == 6 ? 3 : 2)), 0);
          if (h == 6) { loadr(12); loadr(13); }
          if (h < 7) loadt(h + 1);
          if (h < 7 && h != 5) { loadr(2 * h + 2); loadr(2 * h + 3); }
          if (h + FK_PK < 8) {
#pragma unroll
            for (int u = 8 * (h + FK_PK); u < 8 * (h + FK_PK) + 8; u++) xa[u] = pack_bf16(acc[2 * u], acc[2 * u + 1]);
          }
#pragma unroll
          for (int i = 2 * h; i < 2 * h + 2; i++) {
            const uint32_t g0 = (i & 1) ? ga[h].z : ga[h].x, g1 = (i & 1) ? ga[h].w : ga[h].y;
            const uint32_t a0 = fma_bf2(g0, add_bf2(xa[4 * i], rv[i].x), xf[i][0]), a1 = fma_bf2(g0, add_bf2(xa[4 * i + 1], rv[i].y), xf[i][1]);
            const uint32_t a2 = fma_bf2(g1, add_bf2(xa[4 * i + 2], rv[i].z), xf[i][2]), a3 = fma_bf2(g1, add_bf2(xa[4 * i + 3], rv[i].w), xf[i][3]);
            xa[4 * i] = a0; xa[4 * i + 1] = a1; xa[4 * i + 2] = a2; xa[4 * i + 3] = a3;
            mma_1688(dq[0], a0, a1, a0); mma_1688(dq[1], a0, a1, a1);
            mma_1688(dq[2 % FK_NQ], a2, a3, a2); mma_1688(dq[3 % FK_NQ], a2, a3, a3);
            mma_16816(dl[i & (FK_NL - 1)], a0, a1, a2, a3, (i & 1) ? wb[h].z : wb[h].x, (i & 1) ? wb[h].w : wb[h].y);
          }
        }
      }
      const float4 cst = lds128(sb + CST_OFF);
      const uint32_t tag = __float_as_uint(cst.z);
      uint4 own;
      {
        const bool odd = q4 & 1;
        const float l0 = dl[0][0] + dl[1][0], l1 = dl[0][1] + dl[1][1], l2 = dl[0][2] + dl[1][2], l3 = dl[0][3] + dl[1][3];
        const float mine = odd ? l2 : l0 + l1;
        const float other = __shfl_xor_sync(~0u, odd ? l0 : l2 + l3, 1);
        const int dsrc = (lane & ~3) | (gq >> 1);
        const float qa = __shfl_sync(~0u, (gq & 1) ? dq[0][1] + dq[2][1] : dq[0][0] + dq[2][0], dsrc);
        const float qb = __shfl_sync(~0u, (gq & 1) ? dq[1][3] + dq[3][3] : dq[1][2] + dq[3][2], dsrc);
        own = make_uint4(__float_as_uint(odd ? mine : other), __float_as_uint(odd ? qb : qa), __float_as_uint(odd ? other : mine), tag);
        if (q4 < 2) st_msg(&pp.mail->stats[(blk * 4 + m4) * 64 + wq * 16 + gq + 8 * q4], own.x, own.y, own.z, tag);
      }
      if (lane == 0) mbar_arrive(BAR(B_XDONE));
      if (elect) TRACE(15);
      const int srow = wq * 16 + gq + 8 * (q4 & 1);
      const uint4* src0 = &pp.mail->stats[(blk * 4 + (m4 ^ (q4 | 1))) * 64 + srow];
      const uint4* src1 = &pp.mail->stats[(blk * 4 + (m4 ^ 2)) * 64 + srow];
      if (FK_E1DLY) delay_until(clk(), FK_E1DLY);
      uint4 m0 = ld_msg(src0), m1 = own;
      if (q4 >= 2) m1 = ld_msg(src1);
      mbar_wait(BAR(B_EMPTY + 3), 1);
#pragma unroll
      for (int i = 0; i < 16; i++)
        stsm_x4(sb + XST_OFF + mrow * 512 + (i >> 2) * 128 + (uint32_t)(((((2 * i) & 7) + (lane >> 4)) ^ (lane & 7)) << 4), xa[4 * i], xa[4 * i + 1], xa[4 * i + 2], xa[4 * i + 3]);
      uint4 cbv, sbv, gbv;
      const uint4* mp = reinterpret_cast<const uint4*>(pp.mod) + m4 * 32 + lane;
      cbv = ldg128(mp + 512); sbv = ldg128(mp + 384); gbv = ldg128(mp + 640);
      uint32_t k1, k2;
      uint2* cdst = &pp.mail->cand[blk];
      uint32_t tad = sb + TOP_OFF + (lane & 3) * 8, rad = scr + RST_REL + srow * 8, krow = 2047 - (blk * 64 + srow);
      asm volatile("" : "+l"(cdst), "+r"(tad), "+r"(rad), "+r"(krow));
      {
        int it = 0;
        while (!__all_sync(~0u, m0.w == tag && m1.w == tag)) {
          m0 = ld_msg(src0);
          if (q4 >= 2) m1 = ld_msg(src1);
          if (++it > SPIN_LIMIT) SPIN_FAIL(0x209);
        }
        if (elect) TRACE(16);
        float sa = __uint_as_float(m0.x) + __uint_as_float(m1.x), qa = __uint_as_float(m0.y) + __uint_as_float(m1.y), da = __uint_as_float(m0.z) + __uint_as_float(m1.z);
        sa += __shfl_xor_sync(~0u, sa, 2); qa += __shfl_xor_sync(~0u, qa, 2); da += __shfl_xor_sync(~0u, da, 2);
        const float mean = sa * (1.f / D_);
        const float rstd = rsqrt_f(fmaxf(fmaf(-mean, mean, qa * (1.f / D_)), 0.f) + 1e-5f);
        const float rme = fmaf(rstd, fmaf(-mean, cst.x, da), cst.y);
        warp_top2(fkey(rme, 2047 - krow), 0u, k1, k2);
        if (lane == wq) sts64u(tad, k1, k2);
        if (q4 < 2) sts64(rad, rstd, -mean * rstd);
        named_bar<2, 128>();
        const uint2 c = lds64u(tad);
        warp_top2(c.x, c.y, k1, k2);
        if (wq == 0) {
          if (lane == 0 && (FK_PUSHALL || m4 == (t & 3))) red_max8(cdst, k2, k1);
          if (lane == 0) sts64u(sb + TOP_OFF + 32, k1, k2);
          named_arrive<7, 64>();
        }
      }
      if (b < NMOE) named_arrive<1, 256>();
      if (elect) TRACE(17);
      const int c1 = key_row(k1) - blk * 64, c2 = key_row(k2) - blk * 64;
      if (wq >= 2) {
        const int r = wq == 2 ? c1 : c2;
        const uint4 v = lds128u(sb + XST_OFF + r * 512 + ((lane ^ (r & 7)) << 4));
        const float2 st = lds64(scr + RST_REL + r * 8);
        auto h2 = [&](uint32_t xv, uint32_t cv, uint32_t sv) {
          const uint32_t av = add1_bf2(cv);
          return pack_bf16(fmaf(fmaf(bf_lo(xv), st.x, st.y), bf_lo(av), bf_lo(sv)), fmaf(fmaf(bf_hi(xv), st.x, st.y), bf_hi(av), bf_hi(sv)));
        };
        const uint32_t sc = scr + SCR_REL + wq * 512;
        sts128u(sc + lane * 16, h2(v.x, cbv.x, sbv.x), h2(v.y, cbv.y, sbv.y), h2(v.z, cbv.z, sbv.z), h2(v.w, cbv.w, sbv.w));
        __syncwarp();
        const uint32_t fa = sc + gq * 64 + q4 * 4;
        const int o = (blk * 2 + wq - 2) * 128 + m4 * 32 + lane;
        st_msg(&pp.mail->rowh[o], lds32u(fa), lds32u(fa + 16), lds32u(fa + 32), lds32u(fa + 48));
        st_msg(&pp.mail->rowx[o], v.x, v.y, v.z, v.w);
        if (lane == 0 && wq == 3) TRACE(18);
      }
      {
        OutTab tb;
        out_tab(tb, cbv, sbv, gbv);
        char* odst = pp.out + (size_t)blk * (64 * 2 * D_) + m4 * 512 + lane * 16;
        const int g0 = blk * 64 + wq * 16;
        const int done = out_group(tb, sb, scr, wq * 16, 0xFFFFu & ~(row_bit(k1, g0) | row_bit(k2, g0)), lane, odst, FK_OPACE, b < NMOE ? BAR(B_SEL) : 0);
        if (lane == 0) { sts32u(sb + TOP_OFF + 48 + wq * 4, done); mbar_arrive(BAR(B_OUT)); }
      }
      if (elect) TRACE(25);
      if (b < NMOE) {
        uint32_t wd[128];
        mbar_wait(BAR(B_DN + wq), 0);
        {
          const int fr = (lane & 7) + (lane >> 4) * 8;
          const uint32_t base = sb + dn_box(wq) + fr * 128;
#pragma unroll
          for (int c = 0; c < 4; c++) {
            const uint32_t ad = base + (((uint32_t)(c * 2 + ((lane >> 3) & 1)) ^ (uint32_t)(lane & 7)) << 4);
#pragma unroll
            for (int gI = 0; gI < 4; gI++)
#pragma unroll
              for (int ks = 0; ks < 2; ks++) {
                const int o = ((gI * 4 + c) * 2 + ks) * 4;
                ldsm_x4_t(ad + gI * 4096 + ks * 2048, wd[o], wd[o + 1], wd[o + 2], wd[o + 3]);
              }
          }
        }
        uint4* dst = &pp.mail->part[((size_t)(wq * 32 + q4 * 4 + (gq >> 1)) * NMOE + b) * 2 + (gq & 1)];
        uint32_t pad = scr + PART_REL + lane * 16;
        asm volatile("" : "+l"(dst), "+r"(pad));
        if (lane == 0 && wq == 3) TRACE(27);
        named_bar<4, 384>();
        if (elect) TRACE(21);
        float4 ps[4];
#pragma unroll
        for (int w = 0; w < 4; w++) {
          const float4 p0 = lds128(pad + w * 1024), p1 = lds128(pad + w * 1024 + 512);
          ps[w] = make_float4(p0.x + p1.x, p0.y + p1.y, p0.z + p1.z, p0.w + p1.w);
        }
        const uint32_t gp = pack_bf16((ps[0].x + ps[1].x) + (ps[2].x + ps[3].x), (ps[0].y + ps[1].y) + (ps[2].y + ps[3].y));
        const uint32_t up = pack_bf16((ps[0].z + ps[1].z) + (ps[2].z + ps[3].z), (ps[0].w + ps[1].w) + (ps[2].w + ps[3].w));
        const uint32_t act = mul_bf2(pack_bf16(silu_f(bf_lo(gp)), silu_f(bf_hi(gp))), up);
        uint32_t ab[4];
#pragma unroll
        for (int u = 0; u < 4; u++) {
          const uint32_t v0 = __shfl_sync(~0u, act, 8 * u + 2 * q4), v1 = __shfl_sync(~0u, act, 8 * u + 2 * q4 + 1);
          ab[u] = __byte_perm(v0, v1, (gq & 1) ? 0x7632 : 0x5410);
        }
        if (FK_QUIET == 1) named_arrive<8, 256>();
        float c[4][4];
#pragma unroll
        for (int v = 0; v < 4; v++) { c[v][0] = c[v][1] = c[v][2] = c[v][3] = 0.f; }
#pragma unroll
        for (int q = 0; q < 4; q++) {
          const uint32_t mk = (gq >> 1) == q ? ~0u : 0u;
          const uint32_t b0 = ab[0] & mk, b1 = ab[1] & mk, b2 = ab[2] & mk, b3 = ab[3] & mk;
#pragma unroll
          for (int v = 0; v < 4; v++) { const int o = (4 * v + q) * 8; mma_16816(c[v], wd[o], wd[o + 1], wd[o + 2], wd[o + 3], b0, b1); }
#pragma unroll
          for (int v = 0; v < 4; v++) { const int o = (4 * v + q) * 8 + 4; mma_16816(c[v], wd[o], wd[o + 1], wd[o + 2], wd[o + 3], b2, b3); }
        }
#pragma unroll
        for (int u = 0; u < 2; u++)
          st_msg(dst + u * (16 * NMOE * 2), pack_bf16(c[2 * u][0], c[2 * u][1]), pack_bf16(c[2 * u][2], c[2 * u][3]),
                 pack_bf16(c[2 * u + 1][0], c[2 * u + 1][1]), pack_bf16(c[2 * u + 1][2], c[2 * u + 1][3]));
        if (FK_QUIET == 2) named_arrive<8, 256>();
        if (elect) TRACE(22);
      }
    }
  }
}

typedef CUresult (*PFN_encodeTiled)(CUtensorMap*, CUtensorMapDataType, cuuint32_t, void*, const cuuint64_t*, const cuuint64_t*,
                                    const cuuint32_t*, const cuuint32_t*, CUtensorMapInterleave, CUtensorMapSwizzle,
                                    CUtensorMapL2promotion, CUtensorMapFloatOOBfill);

static void map2d(PFN_encodeTiled enc, CUtensorMap* m, const void* p, uint64_t rows, uint64_t cols, uint32_t brows, uint32_t bcols, CUtensorMapSwizzle sw,
                  CUtensorMapL2promotion pr = CU_TENSOR_MAP_L2_PROMOTION_L2_128B) {
  cuuint64_t dims[2] = {cols, rows}; cuuint64_t str[1] = {cols * 2}; cuuint32_t box[2] = {bcols, brows}; cuuint32_t es[2] = {1, 1};
  enc(m, CU_TENSOR_MAP_DATA_TYPE_BFLOAT16, 2, (void*)p, dims, str, box, es, CU_TENSOR_MAP_INTERLEAVE_NONE, sw, pr,
      CU_TENSOR_MAP_FLOAT_OOB_FILL_NONE);
}
static void map3d(PFN_encodeTiled enc, CUtensorMap* m, const void* p, uint64_t rows, uint64_t cols, uint32_t brows, uint32_t bgroups) {
  cuuint64_t dims[3] = {64, rows, cols / 64}; cuuint64_t str[2] = {cols * 2, 128}; cuuint32_t box[3] = {64, brows, bgroups}; cuuint32_t es[3] = {1, 1, 1};
  enc(m, CU_TENSOR_MAP_DATA_TYPE_BFLOAT16, 3, (void*)p, dims, str, box, es, CU_TENSOR_MAP_INTERLEAVE_NONE, CU_TENSOR_MAP_SWIZZLE_128B,
      CU_TENSOR_MAP_L2_PROMOTION_L2_128B, CU_TENSOR_MAP_FLOAT_OOB_FILL_NONE);
}

}

extern "C" void kernel_launch(void* const* d_in, const int* in_sizes, int n_in, void* d_out, int out_size) {
  using namespace fk;
  (void)in_sizes; (void)n_in; (void)out_size;
  static PFN_encodeTiled enc = nullptr;
  static int maxClusters = -1;
  static void *pn = nullptr, *pP = nullptr, *pc = nullptr, *pm = nullptr, *pmod = nullptr;
  if (!enc) {
    void* fn = nullptr; cudaDriverEntryPointQueryResult qr;
    cudaGetDriverEntryPoint("cuTensorMapEncodeTiled", &fn, cudaEnableDefault, &qr);
    enc = (PFN_encodeTiled)fn;
    cudaGetSymbolAddress(&pn, g_n);
    cudaGetSymbolAddress(&pP, g_P);
    cudaGetSymbolAddress(&pc, g_cnt);
    cudaGetSymbolAddress(&pm, g_mail);
    cudaGetSymbolAddress(&pmod, g_mod);
    cudaFuncSetAttribute(fused_kernel, cudaFuncAttributeMaxDynamicSharedMemorySize, SMEM_BYTES);
  }
  Maps maps;
  map2d(enc, &maps.ws[0], d_in[1], S_, S_, 128, 64, CU_TENSOR_MAP_SWIZZLE_128B);
  map2d(enc, &maps.ws[1], d_in[2], S_, S_, 128, 64, CU_TENSOR_MAP_SWIZZLE_128B);
  map3d(enc, &maps.n, pn, S_, D_, 64, 4);
  map2d(enc, &maps.p, pP, 2 * S_, D_, 128, 64, CU_TENSOR_MAP_SWIZZLE_128B);
  map2d(enc, &maps.ps, pP, 2 * S_, D_, 64, 64, CU_TENSOR_MAP_SWIZZLE_128B);
  map2d(enc, &maps.wd[0], d_in[3], D_, D_, 256, 64, CU_TENSOR_MAP_SWIZZLE_128B);
  map2d(enc, &maps.wd[1], d_in[4], D_, D_, 256, 64, CU_TENSOR_MAP_SWIZZLE_128B);
  map2d(enc, &maps.x, d_in[0], S_, D_, 64, 64, CU_TENSOR_MAP_SWIZZLE_128B);
  map2d(enc, &maps.wg, d_in[7], D_, F_, 128, 32, CU_TENSOR_MAP_SWIZZLE_64B);
  map2d(enc, &maps.wu, d_in[8], D_, F_, 128, 32, CU_TENSOR_MAP_SWIZZLE_64B);
  map3d(enc, &maps.wdn, d_in[9], F_, D_, 32, 4);
  map2d(enc, &maps.wm, d_in[11], D_, 6 * D_, 64, 48, CU_TENSOR_MAP_SWIZZLE_NONE);

  cudaLaunchConfig_t cfg = {};
  cfg.gridDim = dim3(NCTA); cfg.blockDim = dim3(384); cfg.dynamicSmemBytes = SMEM_BYTES; cfg.stream = cudaStreamPerThread;
  cudaLaunchAttribute at[1];
  at[0].id = cudaLaunchAttributeClusterDimension; at[0].val.clusterDim.x = 2; at[0].val.clusterDim.y = 1; at[0].val.clusterDim.z = 1;
  cfg.attrs = at; cfg.numAttrs = 1;
  Ptrs pp{(const char*)d_in[0], (char*)pn, (unsigned*)pc, 0, 0, (Mail*)pm, (uint32_t*)pmod, (const char*)d_in[10], (const char*)d_in[1], (const char*)d_in[2],
          (const char*)d_in[3], (const char*)d_in[4], (const char*)d_in[6], (const char*)d_in[7], (const char*)d_in[8], (const char*)d_in[9], (const char*)d_in[11], (char*)d_out, nullptr};
  if (maxClusters < 0) {
    cfg.gridDim = dim3(NCTA + NEXTRA);
    if (cudaOccupancyMaxActiveClusters(&maxClusters, fused_kernel, &cfg) != cudaSuccess) maxClusters = 0;
  }
  pp.b0 = -NEXTRA;
  if (maxClusters >= (NCTA + NEXTRA) / 2) {
    cfg.gridDim = dim3(NCTA + NEXTRA);
  } else {
    cfg.gridDim = dim3(NEXTRA);
    cudaLaunchKernelEx(&cfg, fused_kernel, pp, maps);
    cfg.gridDim = dim3(NCTA); pp.b0 = 0;
  }
  cudaLaunchKernelEx(&cfg, fused_kernel, pp, maps);
}
```

```cpp
#include <cuda_runtime.h>
#include <cuda_bf16.h>
#include <cuda.h>
#include <stdint.h>

#define DEVINL __device__ __forceinline__

namespace fk {

constexpr int S_ = 2048, D_ = 1024, F_ = 3584;
constexpr int NCTA = 128;
constexpr int NEXTRA = 4;
constexpr int NMOE = 112;
constexpr int SLOT = 16384;
constexpr int STAGE = 3 * SLOT;
constexpr int SPARE = 4 * STAGE;
constexpr int MISC = SPARE + 32768;
constexpr int SMEM_BYTES = MISC + 3072;
constexpr int BAR_OFF = MISC;
constexpr int CST_OFF = MISC + 480;
constexpr int SEL_OFF = MISC + 496;
constexpr int T1_OFF = MISC + 512;
constexpr int RS_OFF = T1_OFF + 2048;
constexpr int GA_OFF = T1_OFF;
constexpr int W_OFF = GA_OFF + 512;
constexpr int TOP_OFF = GA_OFF + 1792;
constexpr int XST_OFF = 3 * STAGE + SLOT;
constexpr int PART_REL = 0;
constexpr int SCR_REL = 4096;
constexpr int RST_REL = 6144;
enum { B_FULL = 0, B_EMPTY = 4, B_EMPTYH = 8, B_PRDY = 12  , B_PL = 16  , B_WM = 20  , B_LAND = 24  ,
       B_WB = 28  , B_DN = 32  , B_RECV = 36  , B_STAG = 40, B_T1 = 41, B_MODOK = 42, B_PEER = 43  , B_X = 45, B_T2 = 46,
       B_GU = 47, B_XDONE = 48, B_SEL = 49, B_XF = 50, B_OUT = 51, B_NUM = 52 };

__host__ __device__ constexpr int bar_count(int i) {
  return (i >= B_EMPTY && i < B_EMPTYH) || (i >= B_PRDY && i < B_PL) || i == B_X || i == B_XDONE || i == B_XF || i == B_OUT ? 4
         : (i < B_EMPTY || i == B_T1 || i == B_GU || i == B_MODOK) ? 2 : 1;
}

#define FK_XDEPTH 2
#define FK_G0 8
#define FK_ROW1DLY 700
#define FK_ROW2DLY 1300
#define FK_A1EARLY 0
#define FK_XDLY 2500
#define FK_ROW4DLY 2600
#define FK_WS0DLY 500
#define FK_WS1DLY 1600
#define FK_ADLY 1200
#define FK_L1 2
#define FK_L2 3
#define FK_PF0 20
#define FK_E1DLY 300
#define FK_E2DLY 300
#define FK_E4DLY 550
#define FK_MAP 3
#define FK_PPACE 720
#define FK_PACE0 1000
#define FK_WMPF 0
#define FK_TG 28
#define FK_TU 31
#define FK_BSLEEP 250
#define FK_PFSKIP 0
#define FK_DNWIN 1
#define FK_OPACE 240
#define FK_WGATE -1
#define FK_RSLEEP 1000
#define FK_POLL0 2100
#define FK_GX 10
#define FK_ROW8DLY 3600
#define FK_GSTART 7000
#define FK_OPACE2 170
#define FK_E2GAP -1
#define FK_TABEARLY 1
#define FK_PUSHALL 0
#define FK_E3WEAK 1
#define FK_PK 8
#define FK_NQ 4
#define FK_NL 2
#define FK_W2 0
#define FK_XQ 0
#define FK_XS 1
#define FK_H1 0
#define FK_LF 1
#define FK_WB 1
#define FK_NOHINT 0
#define FK_QUIET 1
#define FK_OEXTRA 0
#define FK_ZB 32
#define FK_ZC0 0
#define FK_PACE 2000
constexpr int SPIN_LIMIT = 1 << 22;
constexpr uint32_t SENT = 0xFFFFFFFFu;

struct Maps {
  CUtensorMap ws[2];
  CUtensorMap n;
  CUtensorMap p;
  CUtensorMap ps;
  CUtensorMap wd[2];
  CUtensorMap x;
  CUtensorMap wg, wu;
  CUtensorMap wdn;
  CUtensorMap wm;
};
template <int V> struct IntC { static constexpr int value = V; };
struct Mail;
struct Ptrs { const char* x; char* n; unsigned* cnt; int b0; uint32_t zero; Mail* mail; uint32_t* mod; const char *c, *ws_re, *ws_im, *wd_re, *wd_im, *wr, *wg, *wu, *wdn, *wm; char *P, *out; unsigned long long* trace; };

__device__ __align__(1024) __nv_bfloat16 g_n[S_ * D_];
__device__ __align__(1024) __nv_bfloat16 g_P[2 * S_ * D_];
__device__ __align__(128) uint32_t g_mod[3 * D_];
__device__ __align__(128) unsigned g_cnt[19 * 32];
struct Mail {
  uint4 stats[32 * 4 * 64];
  uint2 cand[32];
  uint4 rowh[64 * 128];
  uint4 rowx[64 * 128];
  uint4 part[128 * NMOE * 2];
  uint2 rs[2 * 16 * 128];
};
static_assert(FK_L2 == 3, "the receive layout assumes a stagger of three k-blocks");
__device__ __align__(1024) Mail g_mail;

#define SPIN_FAIL(what) __trap()
DEVINL uint32_t smem_u32(const void* p) { return (uint32_t)__cvta_generic_to_shared(p); }
DEVINL void mbar_init(uint32_t bar, uint32_t cnt) { asm volatile("mbarrier.init.shared::cta.b64 [%0], %1;" ::"r"(bar), "r"(cnt) : "memory"); }
DEVINL void mbar_expect_tx(uint32_t bar, uint32_t bytes) { asm volatile("mbarrier.arrive.expect_tx.shared::cta.b64 _, [%0], %1;" ::"r"(bar), "r"(bytes) : "memory"); }
DEVINL void mbar_arrive(uint32_t bar) { asm volatile("mbarrier.arrive.shared::cta.b64 _, [%0];" ::"r"(bar) : "memory"); }
DEVINL void mbar_arrive_cluster(uint32_t bar) { asm volatile("mbarrier.arrive.shared::cluster.b64 _, [%0];" ::"r"(bar) : "memory"); }
DEVINL uint32_t mapa(uint32_t a, uint32_t cta) { uint32_t r; asm("mapa.shared::cluster.u32 %0, %1, %2;" : "=r"(r) : "r"(a), "r"(cta)); return r; }
DEVINL bool mbar_test(uint32_t bar, uint32_t parity) {
  uint32_t ok;
  asm volatile("{\n.reg .pred p;\nmbarrier.test_wait.parity.shared::cta.b64 p, [%1], %2;\nselp.u32 %0, 1, 0, p;\n}" : "=r"(ok) : "r"(bar), "r"(parity) : "memory");
  return ok;
}
DEVINL void mbar_wait(uint32_t bar, uint32_t parity) {
  asm volatile("{\n.reg .pred p;\n.reg .u32 c;\nmov.u32 c, 0;\n"
               "LW:\nmbarrier.try_wait.parity.shared::cta.b64 p, [%0], %1;\n@p bra LD;\n"
               "add.u32 c, c, 1;\nsetp.lt.u32 p, c, 4194304;\n@p bra LW;\ntrap;\nLD:\n}" ::"r"(bar), "r"(parity) : "memory");
}
DEVINL void fence_async_smem() { asm volatile("fence.proxy.async.shared::cta;" ::: "memory"); }
DEVINL void fence_async_global() { asm volatile("fence.proxy.async.global;" ::: "memory"); }
DEVINL void fence_gpu() { asm volatile("fence.acq_rel.gpu;" ::: "memory"); }
template <int ID, int N> DEVINL void named_bar() { asm volatile("bar.sync %0, %1;" ::"n"(ID), "n"(N) : "memory"); }
template <int ID, int N> DEVINL void named_arrive() { asm volatile("bar.arrive %0, %1;" ::"n"(ID), "n"(N) : "memory"); }

DEVINL void tma_2d(uint32_t dst, const CUtensorMap* m, int x, int y, uint32_t bar) {
  asm volatile("cp.async.bulk.tensor.2d.shared::cluster.global.mbarrier::complete_tx::bytes [%0], [%1, {%3, %4}], [%2];"
               ::"r"(dst), "l"(m), "r"(bar), "r"(x), "r"(y) : "memory");
}
DEVINL void tma_2d_hint(uint32_t dst, const CUtensorMap* m, int x, int y, uint32_t bar, uint64_t pol) {
  asm volatile("cp.async.bulk.tensor.2d.shared::cluster.global.mbarrier::complete_tx::bytes.L2::cache_hint [%0], [%1, {%3, %4}], [%2], %5;"
               ::"r"(dst), "l"(m), "r"(bar), "r"(x), "r"(y), "l"(pol) : "memory");
}
DEVINL void tma_3d(uint32_t dst, const CUtensorMap* m, int x, int y, int z, uint32_t bar) {
  asm volatile("cp.async.bulk.tensor.3d.shared::cluster.global.mbarrier::complete_tx::bytes [%0], [%1, {%3, %4, %5}], [%2];"
               ::"r"(dst), "l"(m), "r"(bar), "r"(x), "r"(y), "r"(z) : "memory");
}
DEVINL void tma_store_2d(const CUtensorMap* m, uint32_t src, int x, int y) {
  asm volatile("cp.async.bulk.tensor.2d.global.shared::cta.bulk_group [%0, {%2, %3}], [%1];" ::"l"(m), "r"(src), "r"(x), "r"(y) : "memory");
}
DEVINL void bulk_load(uint32_t dst, const void* src, uint32_t bytes, uint32_t bar) {
  asm volatile("cp.async.bulk.shared::cluster.global.mbarrier::complete_tx::bytes [%0], [%1], %2, [%3];" ::"r"(dst), "l"(src), "r"(bytes), "r"(bar) : "memory");
}
DEVINL void bulk_store(void* dst, uint32_t src, uint32_t bytes) {
  asm volatile("cp.async.bulk.global.shared::cta.bulk_group [%0], [%1], %2;" ::"l"(dst), "r"(src), "r"(bytes) : "memory");
}
DEVINL void pf_bulk(const void* p, uint32_t bytes) { asm volatile("cp.async.bulk.prefetch.L2.global [%0], %1;" ::"l"(p), "r"(bytes) : "memory"); }
DEVINL void pf_bulk_hint(const void* p, uint32_t bytes, uint64_t pol) {
  asm volatile("cp.async.bulk.prefetch.L2.global.L2::cache_hint [%0], %1, %2;" ::"l"(p), "r"(bytes), "l"(pol) : "memory");
}
DEVINL void pf_2d(const CUtensorMap* m, int x, int y) {
  asm volatile("cp.async.bulk.prefetch.tensor.2d.L2.global [%0, {%1, %2}];" ::"l"(m), "r"(x), "r"(y) : "memory");
}
DEVINL void bulk_commit() { asm volatile("cp.async.bulk.commit_group;" ::: "memory"); }
template <int N> DEVINL void bulk_wait() { asm volatile("cp.async.bulk.wait_group %0;" ::"n"(N) : "memory"); }
template <int N> DEVINL void bulk_wait_read() { asm volatile("cp.async.bulk.wait_group.read %0;" ::"n"(N) : "memory"); }
DEVINL void prefetch_tmap(const CUtensorMap* m) { asm volatile("prefetch.tensormap [%0];" ::"l"(m) : "memory"); }

DEVINL void wg_fence() { asm volatile("wgmma.fence.sync.aligned;" ::: "memory"); }
DEVINL void wg_commit() { asm volatile("wgmma.commit_group.sync.aligned;" ::: "memory"); }
template <int N> DEVINL void wg_wait() { asm volatile("wgmma.wait_group.sync.aligned %0;" ::"n"(N) : "memory"); }

DEVINL uint64_t make_desc(uint32_t addr, uint32_t lbo, uint32_t sbo) {
  return (uint64_t)((addr & 0x3FFFF) >> 4) | ((uint64_t)(lbo >> 4) << 16) | ((uint64_t)(sbo >> 4) << 32) | ((uint64_t)1 << 62);
}

#define R8(a, o) "+f"(a[o]), "+f"(a[o + 1]), "+f"(a[o + 2]), "+f"(a[o + 3]), "+f"(a[o + 4]), "+f"(a[o + 5]), "+f"(a[o + 6]), "+f"(a[o + 7])
#define R128(a) R8(a, 0), R8(a, 8), R8(a, 16), R8(a, 24), R8(a, 32), R8(a, 40), R8(a, 48), R8(a, 56), \
                R8(a, 64), R8(a, 72), R8(a, 80), R8(a, 88), R8(a, 96), R8(a, 104), R8(a, 112), R8(a, 120)
template <int TB>
DEVINL void wgmma_n256(float (&d)[128], uint64_t da, uint64_t db, int scale_d) {
  asm volatile(
      "{\n.reg .pred p;\nsetp.ne.b32 p, %130, 0;\n"
      "wgmma.mma_async.sync.aligned.m64n256k16.f32.bf16.bf16 "
      "{%0, %1, %2, %3, %4, %5, %6, %7, %8, %9, %10, %11, %12, %13, %14, %15, "
      "%16, %17, %18, %19, %20, %21, %22, %23, %24, %25, %26, %27, %28, %29, %30, %31, "
      "%32, %33, %34, %35, %36, %37, %38, %39, %40, %41, %42, %43, %44, %45, %46, %47, "
      "%48, %49, %50, %51, %52, %53, %54, %55, %56, %57, %58, %59, %60, %61, %62, %63, "
      "%64, %65, %66, %67, %68, %69, %70, %71, %72, %73, %74, %75, %76, %77, %78, %79, "
      "%80, %81, %82, %83, %84, %85, %86, %87, %88, %89, %90, %91, %92, %93, %94, %95, "
      "%96, %97, %98, %99, %100, %101, %102, %103, %104, %105, %106, %107, %108, %109, %110, %111, "
      "%112, %113, %114, %115, %116, %117, %118, %119, %120, %121, %122, %123, %124, %125, %126, %127}, "
      "%128, %129, p, 1, 1, 0, %131;\n}\n"
      : R128(d)
      : "l"(da), "l"(db), "r"(scale_d), "n"(TB));
}
DEVINL void reg_fence128(float (&a)[128]) {
#pragma unroll
  for (int i = 0; i < 128; i++) asm volatile("" : "+f"(a[i])::"memory");
}

DEVINL uint32_t pack_bf16(float lo, float hi) {
  uint32_t r;
  asm("cvt.rn.bf16x2.f32 %0, %1, %2;" : "=r"(r) : "f"(hi), "f"(lo));
  return r;
}
DEVINL uint32_t fma_bf2(uint32_t a, uint32_t b, uint32_t c) { uint32_t r; asm("fma.rn.bf16x2 %0, %1, %2, %3;" : "=r"(r) : "r"(a), "r"(b), "r"(c)); return r; }
DEVINL uint32_t mul_bf2(uint32_t a, uint32_t b) { uint32_t r; asm("mul.rn.bf16x2 %0, %1, %2;" : "=r"(r) : "r"(a), "r"(b)); return r; }
DEVINL uint32_t add_bf2(uint32_t a, uint32_t b) { uint32_t r; asm("add.rn.bf16x2 %0, %1, %2;" : "=r"(r) : "r"(a), "r"(b)); return r; }
DEVINL uint32_t add1_bf2(uint32_t a) { return fma_bf2(a, 0x3F803F80u, 0x3F803F80u); }
DEVINL float bf_lo(uint32_t w) { return __uint_as_float(w << 16); }
DEVINL float bf_hi(uint32_t w) { return __uint_as_float(w & 0xFFFF0000u); }
DEVINL float round_bf16(float v) { return bf_lo(pack_bf16(v, v)); }
DEVINL float sigmoid_f(float v) {
  float e, r;
  asm("ex2.approx.ftz.f32 %0, %1;" : "=f"(e) : "f"(v * -1.4426950408889634f));
  asm("rcp.approx.ftz.f32 %0, %1;" : "=f"(r) : "f"(1.f + e));
  return r;
}
DEVINL float rsqrt_f(float v) { float r; asm("rsqrt.approx.ftz.f32 %0, %1;" : "=f"(r) : "f"(v)); return r; }
DEVINL float silu_f(float v) { return v * sigmoid_f(v); }
DEVINL void stsm_x4(uint32_t addr, uint32_t r0, uint32_t r1, uint32_t r2, uint32_t r3) {
  asm volatile("stmatrix.sync.aligned.m8n8.x4.shared.b16 [%0], {%1, %2, %3, %4};" ::"r"(addr), "r"(r0), "r"(r1), "r"(r2), "r"(r3) : "memory");
}
DEVINL void ldsm_x4(uint32_t addr, uint32_t& r0, uint32_t& r1, uint32_t& r2, uint32_t& r3) {
  asm volatile("ldmatrix.sync.aligned.m8n8.x4.shared.b16 {%0, %1, %2, %3}, [%4];" : "=r"(r0), "=r"(r1), "=r"(r2), "=r"(r3) : "r"(addr) : "memory");
}
DEVINL void ldsm_x4_t(uint32_t addr, uint32_t& r0, uint32_t& r1, uint32_t& r2, uint32_t& r3) {
  asm volatile("ldmatrix.sync.aligned.m8n8.x4.trans.shared.b16 {%0, %1, %2, %3}, [%4];" : "=r"(r0), "=r"(r1), "=r"(r2), "=r"(r3) : "r"(addr) : "memory");
}
DEVINL void mma_16816(float (&c)[4], uint32_t a0, uint32_t a1, uint32_t a2, uint32_t a3, uint32_t b0, uint32_t b1) {
  asm("mma.sync.aligned.m16n8k16.row.col.f32.bf16.bf16.f32 {%0, %1, %2, %3}, {%4, %5, %6, %7}, {%8, %9}, {%0, %1, %2, %3};"
      : "+f"(c[0]), "+f"(c[1]), "+f"(c[2]), "+f"(c[3]) : "r"(a0), "r"(a1), "r"(a2), "r"(a3), "r"(b0), "r"(b1));
}
DEVINL void mma_1688(float (&c)[4], uint32_t a0, uint32_t a1, uint32_t b0) {
  asm("mma.sync.aligned.m16n8k8.row.col.f32.bf16.bf16.f32 {%0, %1, %2, %3}, {%4, %5}, {%6}, {%0, %1, %2, %3};"
      : "+f"(c[0]), "+f"(c[1]), "+f"(c[2]), "+f"(c[3]) : "r"(a0), "r"(a1), "r"(b0));
}
DEVINL float4 lds128(uint32_t a) { float4 v; asm volatile("ld.shared.v4.f32 {%0, %1, %2, %3}, [%4];" : "=f"(v.x), "=f"(v.y), "=f"(v.z), "=f"(v.w) : "r"(a)); return v; }
DEVINL uint4 lds128u(uint32_t a) { uint4 v; asm volatile("ld.shared.v4.u32 {%0, %1, %2, %3}, [%4];" : "=r"(v.x), "=r"(v.y), "=r"(v.z), "=r"(v.w) : "r"(a)); return v; }
DEVINL float2 lds64(uint32_t a) { float2 v; asm volatile("ld.shared.v2.f32 {%0, %1}, [%2];" : "=f"(v.x), "=f"(v.y) : "r"(a)); return v; }
DEVINL uint2 lds64u(uint32_t a) { uint2 v; asm volatile("ld.shared.v2.u32 {%0, %1}, [%2];" : "=r"(v.x), "=r"(v.y) : "r"(a)); return v; }
DEVINL float lds32(uint32_t a) { float v; asm volatile("ld.shared.f32 %0, [%1];" : "=f"(v) : "r"(a)); return v; }
DEVINL float lds16f(uint32_t a) { uint32_t v; asm volatile("ld.shared.u16 %0, [%1];" : "=r"(v) : "r"(a)); return __uint_as_float(v << 16); }
DEVINL uint32_t lds32u(uint32_t a) { uint32_t v; asm volatile("ld.shared.u32 %0, [%1];" : "=r"(v) : "r"(a)); return v; }
DEVINL void sts128(uint32_t a, float x, float y, float z, float w) { asm volatile("st.shared.v4.f32 [%0], {%1, %2, %3, %4};" ::"r"(a), "f"(x), "f"(y), "f"(z), "f"(w) : "memory"); }
DEVINL void sts128u(uint32_t a, uint32_t x, uint32_t y, uint32_t z, uint32_t w) { asm volatile("st.shared.v4.u32 [%0], {%1, %2, %3, %4};" ::"r"(a), "r"(x), "r"(y), "r"(z), "r"(w) : "memory"); }
DEVINL void sts64(uint32_t a, float x, float y) { asm volatile("st.shared.v2.f32 [%0], {%1, %2};" ::"r"(a), "f"(x), "f"(y) : "memory"); }
DEVINL void sts64u(uint32_t a, uint32_t x, uint32_t y) { asm volatile("st.shared.v2.u32 [%0], {%1, %2};" ::"r"(a), "r"(x), "r"(y) : "memory"); }
DEVINL void sts32(uint32_t a, float v) { asm volatile("st.shared.f32 [%0], %1;" ::"r"(a), "f"(v) : "memory"); }
DEVINL void sts32u(uint32_t a, uint32_t v) { asm volatile("st.shared.u32 [%0], %1;" ::"r"(a), "r"(v) : "memory"); }

DEVINL uint4 ld_msg(const uint4* p) {
  unsigned long long a, b;
  asm volatile("{\n.reg .b128 r;\nld.relaxed.gpu.global.b128 r, [%2];\nmov.b128 {%0, %1}, r;\n}" : "=l"(a), "=l"(b) : "l"(p) : "memory");
  return make_uint4((uint32_t)a, (uint32_t)(a >> 32), (uint32_t)b, (uint32_t)(b >> 32));
}
DEVINL void st_msg(uint4* p, uint32_t x, uint32_t y, uint32_t z, uint32_t w) {
  unsigned long long a = (unsigned long long)x | ((unsigned long long)y << 32), b = (unsigned long long)z | ((unsigned long long)w << 32);
  asm volatile("{\n.reg .b128 r;\nmov.b128 r, {%1, %2};\nst.relaxed.gpu.global.b128 [%0], r;\n}" ::"l"(p), "l"(a), "l"(b) : "memory");
}
DEVINL uint2 ld_msg8(const void* p) {
  unsigned long long a;
  asm volatile("ld.relaxed.gpu.global.b64 %0, [%1];" : "=l"(a) : "l"(p) : "memory");
  return make_uint2((uint32_t)a, (uint32_t)(a >> 32));
}
DEVINL void st_msg8(uint2* p, uint32_t x, uint32_t y) {
  asm volatile("st.relaxed.gpu.global.b64 [%0], %1;" ::"l"(p), "l"((unsigned long long)x | ((unsigned long long)y << 32)) : "memory");
}
DEVINL unsigned ld_rlx(const void* p) { unsigned v; asm volatile("ld.relaxed.gpu.global.u32 %0, [%1];" : "=r"(v) : "l"(p) : "memory"); return v; }
DEVINL void st_rlx(unsigned* p, unsigned v) { asm volatile("st.relaxed.gpu.global.u32 [%0], %1;" ::"l"(p), "r"(v) : "memory"); }
DEVINL void red_add(unsigned* p, unsigned v) { asm volatile("red.relaxed.gpu.global.add.u32 [%0], %1;" ::"l"(p), "r"(v) : "memory"); }
DEVINL void red_max8(uint2* p, uint32_t lo, uint32_t hi) {
  asm volatile("red.relaxed.gpu.global.max.u64 [%0], %1;" ::"l"(p), "l"((unsigned long long)lo | ((unsigned long long)hi << 32)) : "memory");
}
DEVINL void red_add_release(unsigned* p, unsigned v) { asm volatile("red.release.gpu.global.add.u32 [%0], %1;" ::"l"(p), "r"(v) : "memory"); }
DEVINL uint4 ldg_nc(const void* p) {
  uint4 v;
  asm volatile("ld.global.nc.L1::no_allocate.v4.u32 {%0, %1, %2, %3}, [%4];" : "=r"(v.x), "=r"(v.y), "=r"(v.z), "=r"(v.w) : "l"(p));
  return v;
}
DEVINL uint4 ldg128(const void* p) {
  uint4 v;
  asm volatile("ld.global.v4.u32 {%0, %1, %2, %3}, [%4];" : "=r"(v.x), "=r"(v.y), "=r"(v.z), "=r"(v.w) : "l"(p) : "memory");
  return v;
}
DEVINL void stg128(void* p, uint4 v) { asm volatile("st.global.v4.u32 [%0], {%1, %2, %3, %4};" ::"l"(p), "r"(v.x), "r"(v.y), "r"(v.z), "r"(v.w) : "memory"); }
DEVINL uint32_t landed(uint32_t readback, uint32_t zero) { return __reduce_or_sync(~0u, readback & zero); }
DEVINL uint32_t nonzero(uint32_t w) { return w ? w : 0x8000u; }
DEVINL uint32_t clk() { uint32_t c; asm volatile("mov.u32 %0, %%clock;" : "=r"(c)); return c; }
DEVINL void delay_until(uint32_t c0, uint32_t cycles) { while (clk() - c0 < cycles) {} }

#define TRACE(id)
#define TRACE_CLK(id)
#define FK_TTMASK 0x1111C1110101ull

DEVINL const char* piece_addr(const Ptrs& pp, int b, int i) {
  if (i >= 20) return pp.wdn + (size_t)b * 57344 + (i - 20) * 8192;
  if ((i >> 2) == 2) return (b < 64 ? pp.wd_re : pp.wd_im) + (size_t)(b & 63) * 32768 + (i & 3) * 8192;
  return (i < 4 || (i >> 2) == 3 ? pp.wg : pp.wu) + (size_t)((i < 8 ? ((i & 3) ^ 2) * 128 : 512 + (i & 3) * 128) + b) * (2 * F_);
}

DEVINL uint32_t dn_box(int i) { return i == 0 ? STAGE + 2 * SLOT : i == 3 ? SPARE : 2 * STAGE + i * SLOT; }
DEVINL int sibling(int m4, int r) {
  return r < 2 ? m4 ^ r : ((m4 & 2) ^ 2) + r - 2;
}

DEVINL uint32_t fkey(float v, int row) {
  const uint32_t u = __float_as_uint(v);
  return (((u & 0x80000000u) ? ~u : (u | 0x80000000u)) & ~2047u) | (uint32_t)(2047 - row);
}
DEVINL int key_row(uint32_t k) { return 2047 - (int)(k & 2047u); }
DEVINL float key_val(uint32_t k) { k = (k & ~2047u) | 1024u; return __uint_as_float((k & 0x80000000u) ? (k & 0x7FFFFFFFu) : ~k); }
DEVINL uint32_t redux_max(uint32_t v) { uint32_t r; asm volatile("redux.sync.max.u32 %0, %1, 0xffffffff;" : "=r"(r) : "r"(v)); return r; }
DEVINL void warp_top2(uint32_t ka, uint32_t kb, uint32_t& k1, uint32_t& k2) {
  k1 = redux_max(ka);
  k2 = redux_max(ka == k1 ? kb : ka);
}
DEVINL int sel_slot(uint2 sel, int n) {
  const int bA = key_row(sel.x) >> 6, bB = key_row(sel.y) >> 6;
  return n ? bB * 2 + (bA == bB ? 1 : 0) : bA * 2;
}

DEVINL void ln_stats(const uint4 (&w)[4], float (&v)[32], float& rstd, float& nmr) {
#pragma unroll
  for (int i = 0; i < 4; i++) {
    v[8 * i + 0] = bf_lo(w[i].x); v[8 * i + 1] = bf_hi(w[i].x); v[8 * i + 2] = bf_lo(w[i].y); v[8 * i + 3] = bf_hi(w[i].y);
    v[8 * i + 4] = bf_lo(w[i].z); v[8 * i + 5] = bf_hi(w[i].z); v[8 * i + 6] = bf_lo(w[i].w); v[8 * i + 7] = bf_hi(w[i].w);
  }
  float s[4] = {0.f, 0.f, 0.f, 0.f}, q[4] = {0.f, 0.f, 0.f, 0.f};
#pragma unroll
  for (int i = 0; i < 32; i++) { s[i & 3] += v[i]; q[i & 3] = fmaf(v[i], v[i], q[i & 3]); }
  rstd = (s[0] + s[1]) + (s[2] + s[3]); nmr = (q[0] + q[1]) + (q[2] + q[3]);
}
DEVINL void ln_apply(uint4 (&w)[4], const float (&v)[32], float sum, float sq) {
#pragma unroll
  for (int o = 16; o; o >>= 1) { sum += __shfl_xor_sync(~0u, sum, o); sq += __shfl_xor_sync(~0u, sq, o); }
  const float mean = sum * (1.f / D_);
  const float rstd = rsqrt_f(fmaxf(fmaf(-mean, mean, sq * (1.f / D_)), 0.f) + 1e-5f), nmr = -mean * rstd;
#pragma unroll
  for (int i = 0; i < 4; i++) {
    w[i].x = pack_bf16(fmaf(v[8 * i], rstd, nmr), fmaf(v[8 * i + 1], rstd, nmr)); w[i].y = pack_bf16(fmaf(v[8 * i + 2], rstd, nmr), fmaf(v[8 * i + 3], rstd, nmr));
    w[i].z = pack_bf16(fmaf(v[8 * i + 4], rstd, nmr), fmaf(v[8 * i + 5], rstd, nmr)); w[i].w = pack_bf16(fmaf(v[8 * i + 6], rstd, nmr), fmaf(v[8 * i + 7], rstd, nmr));
  }
}
DEVINL void ln_row(uint4 (&w)[4]) { float v[32], s, q; ln_stats(w, v, s, q); ln_apply(w, v, s, q); }
DEVINL float sum8(uint4 u) { return ((bf_lo(u.x) + bf_hi(u.x)) + (bf_lo(u.y) + bf_hi(u.y))) + ((bf_lo(u.z) + bf_hi(u.z)) + (bf_lo(u.w) + bf_hi(u.w))); }

template <int R> DEVINL void take_box(uint32_t (&wf)[128], uint32_t box, int lane) {
  const int kr = (lane & 7) + (lane >> 4) * 8;
  const uint32_t base = box + kr * 64, sw = (uint32_t)((kr >> 1) & 3), hb = (uint32_t)((lane >> 3) & 1);
#pragma unroll
  for (int mt = 0; mt < 2; mt++) {
    const uint32_t ad = base + (((mt * 2 + hb) ^ sw) << 4);
#pragma unroll
    for (int ks = 0; ks < 8; ks++) {
      const int o = (ks * 4 + R * 2 + mt) * 4;
      ldsm_x4_t(ad + ks * 1024, wf[o], wf[o + 1], wf[o + 2], wf[o + 3]);
    }
  }
}
DEVINL void gate_up(const Ptrs& pp, uint32_t (&wf)[128], uint32_t sb, uint32_t scr, int ksl, int lane) {
  const uint2 sel = lds64u(sb + SEL_OFF);
  const int gq = lane >> 2, q4 = lane & 3;
  const uint4* src = &pp.mail->rowh[sel_slot(sel, gq & 1) * 128 + ksl * 16 + q4];
  uint4 bf[4];
  int it = 0;
#pragma unroll
  for (int u = 0; u < 4; u++) bf[u] = FK_E3WEAK ? ldg128(src + u * 4) : ld_msg(src + u * 4);
  while (!__all_sync(~0u, bf[0].x != SENT && bf[1].x != SENT && bf[2].x != SENT && bf[3].x != SENT)) {
#pragma unroll
    for (int u = 0; u < 4; u++) bf[u] = ld_msg(src + u * 4);
    if (++it > SPIN_LIMIT) SPIN_FAIL(0x207);
  }
  if (lane == 0 && ksl == 4) TRACE(20);
  float acc[8][4];
#pragma unroll
  for (int i = 0; i < 8; i++) { acc[i][0] = acc[i][1] = acc[i][2] = acc[i][3] = 0.f; }
#pragma unroll
  for (int u = 0; u < 4; u++)
#pragma unroll
    for (int mt = 0; mt < 4; mt++) {
      const int o = (2 * u * 4 + mt) * 4;
      mma_16816(acc[mt], wf[o], wf[o + 1], wf[o + 2], wf[o + 3], bf[u].x, bf[u].y);
      mma_16816(acc[4 + mt], wf[o + 16], wf[o + 17], wf[o + 18], wf[o + 19], bf[u].z, bf[u].w);
    }
  {
    const bool h = q4 & 1, m = q4 & 2;
    float v[4][2];
#pragma unroll
    for (int mt = 0; mt < 4; mt++) {
      v[mt][0] = h ? acc[mt][2] + acc[4 + mt][2] : acc[mt][0] + acc[4 + mt][0];
      v[mt][1] = h ? acc[mt][3] + acc[4 + mt][3] : acc[mt][1] + acc[4 + mt][1];
    }
    sts128(scr + PART_REL + ksl * 512 + (q4 * 8 + gq) * 16, m ? v[1][0] : v[0][0], m ? v[1][1] : v[0][1], m ? v[3][0] : v[2][0], m ? v[3][1] : v[2][1]);
  }
  named_arrive<4, 384>();
}

struct OutTab { uint32_t A[4], S[4], G[4]; };
DEVINL void out_tab(OutTab& tb, uint4 cb, uint4 sv, uint4 gb) {
  tb.A[0] = add1_bf2(cb.x); tb.A[1] = add1_bf2(cb.y); tb.A[2] = add1_bf2(cb.z); tb.A[3] = add1_bf2(cb.w);
  tb.S[0] = sv.x; tb.S[1] = sv.y; tb.S[2] = sv.z; tb.S[3] = sv.w;
  tb.G[0] = gb.x; tb.G[1] = gb.y; tb.G[2] = gb.z; tb.G[3] = gb.w;
}
DEVINL void out_rows(const OutTab& tb, uint32_t sb, uint32_t scr, int r, uint32_t mask, int lane, char* dst) {
  const float4 st = lds128(scr + RST_REL + r * 8);
  uint4 v[2];
#pragma unroll
  for (int k = 0; k < 2; k++) v[k] = lds128u(sb + XST_OFF + (r + k) * 512 + ((lane ^ ((r + k) & 7)) << 4));
#pragma unroll
  for (int k = 0; k < 2; k++) {
    const float rs = k ? st.z : st.x, nm = k ? st.w : st.y;
    const uint32_t x4[4] = {v[k].x, v[k].y, v[k].z, v[k].w};
    uint32_t o[4];
#pragma unroll
    for (int u = 0; u < 4; u++)
      o[u] = fma_bf2(tb.G[u], fma_bf2(pack_bf16(fmaf(bf_lo(x4[u]), rs, nm), fmaf(bf_hi(x4[u]), rs, nm)), tb.A[u], tb.S[u]), x4[u]);
    if ((mask >> k) & 1) stg128(dst + (size_t)(r + k) * (2 * D_), make_uint4(o[0], o[1], o[2], o[3]));
  }
}
DEVINL int out_group(const OutTab& tb, uint32_t sb, uint32_t scr, int r0, uint32_t mask, int lane, char* dst, uint32_t pace, uint32_t stop) {
  int r = 0;
#pragma unroll 1
  for (; mask; r += 2, mask >>= 2) {
    if (!(mask & 3)) continue;
    const bool last = stop && mbar_test(stop, 0);
    if (last && !FK_OEXTRA) return r;
    const uint32_t cn = clk();
    out_rows(tb, sb, scr, r0 + r, mask, lane, dst);
    if (last) return r + 2;
    if (mask >> 2) delay_until(cn, pace);
  }
  return 16;
}
DEVINL uint32_t row_bit(uint32_t key, int g0) { const unsigned r = (unsigned)(key_row(key) - g0); return r < 16 ? 1u << r : 0u; }

template <int TB, int G0, int G1>
DEVINL void gemm_phase(const Ptrs& pp, float (&acc)[128], uint32_t sb, int cw, bool lag, bool elect, uint32_t rel) {
  const uint32_t bars = sb + BAR_OFF;
#pragma unroll 1
  for (int g = G0; g < G1; g++) {
    const int s = g & 3;
    mbar_wait(bars + (B_FULL + s) * 8, (g >> 2) & 1);
    const bool hold = lag && g == G1 - (TB ? FK_L1 : FK_L2) && !(TB && FK_H1);
    if (hold) {
      wg_wait<0>();
      if (rel) mbar_arrive_cluster(rel + ((g - 1) & 3) * 8);
      mbar_wait(bars + B_STAG * 8, TB ? 0 : 1);
    }
    const uint32_t sa = sb + s * STAGE;
    const uint64_t da = make_desc(sa + cw * 8192, 16, 1024), db = make_desc(sa + SLOT, TB ? 8192 : 16, 1024);
    constexpr int KB = TB ? 128 : 2;
    wg_fence();
    wgmma_n256<TB>(acc, da, db, g > G0);
    wgmma_n256<TB>(acc, da + 2, db + KB, 1);
    wg_commit();
    wg_wait<1>();
    if (rel && g > G0 && !hold) mbar_arrive_cluster(rel + ((g - 1) & 3) * 8);
    if (!TB && g == G1 - 1 && !lag && elect) mbar_arrive_cluster(mapa(bars + B_PEER * 8, cw));
    if (TB && FK_H1 && lag && g == G1 - FK_L1 - 1) mbar_wait(bars + B_STAG * 8, 0);
    wg_fence();
    wgmma_n256<TB>(acc, da + 4, db + 2 * KB, 1);
    wgmma_n256<TB>(acc, da + 6, db + 3 * KB, 1);
    wg_commit();
  }
  if (!lag) {
    wg_wait<1>();
    if (elect) mbar_arrive(bars + B_STAG * 8);
  }
}
DEVINL void gemm_finish(float (&acc)[128], uint32_t rel) {
  wg_wait<0>();
  reg_fence128(acc);
  if (rel) mbar_arrive_cluster(rel + 24);
}

__global__ void __launch_bounds__(384, 1)
fused_kernel(const Ptrs pp, const __grid_constant__ Maps maps) {
  extern __shared__ __align__(1024) uint8_t smem_raw[];
  const uint32_t c0 = clk();
  if (threadIdx.x == 0 && blockIdx.x >= NEXTRA) TRACE(0);
  const uint32_t sb = smem_u32(smem_raw);
  const int tid = threadIdx.x, lane = tid & 31;
  const int warp = __shfl_sync(~0u, tid >> 5, 0);
  const int rb = (int)blockIdx.x + pp.b0;
  const uint32_t bars = sb + BAR_OFF;
  auto BAR = [&](int i) { return bars + i * 8; };

  if (rb < 0) {
    const uint32_t ring = sb + warp * 16384, rbar = sb + MISC + warp * 64;
    const int row0 = FK_GX * 128 + ((rb + NEXTRA) * 12 + warp) * 2;
    if (lane == 0) {
#pragma unroll 1
      for (int i = 0; i < 4; i++) mbar_init(rbar + i * 8, 1);
      asm volatile("fence.mbarrier_init.release.cluster;" ::: "memory");
      delay_until(c0, FK_XDLY);
#pragma unroll 1
      for (int i = 0; i < FK_XDEPTH; i++) { mbar_expect_tx(rbar + i * 8, 4096); bulk_load(ring + i * 4096, pp.x + (size_t)(row0 + 96 * i) * (2 * D_), 4096, rbar + i * 8); }
    }
    __syncwarp();
    int row = row0;
#pragma unroll 1
    for (int it = 0; row < S_; it++, row += 96) {
      const uint32_t st = ring + (it & 3) * 4096;
      mbar_wait(rbar + (it & 3) * 8, (it >> 2) & 1);
      uint4 w[4], w2[4];
#pragma unroll
      for (int i = 0; i < 4; i++) { w[i] = lds128u(st + lane * 16 + i * 512); w2[i] = lds128u(st + 2048 + lane * 16 + i * 512); }
      ln_row(w);
      uint32_t rbk = 0;
      if (it) {
        if (lane == 0) bulk_wait<0>();
        __syncwarp();
        rbk = ld_rlx(pp.n + (size_t)(row - 96) * (2 * D_) + lane * 128);
      }
      ln_row(w2);
#pragma unroll
      for (int i = 0; i < 4; i++) { sts128u(st + lane * 16 + i * 512, w[i].x, w[i].y, w[i].z, w[i].w); sts128u(st + 2048 + lane * 16 + i * 512, w2[i].x, w2[i].y, w2[i].z, w2[i].w); }
      fence_async_smem();
      const uint32_t z = landed(rbk, pp.zero);
      if (lane == 0) {
        if (it) red_add(&pp.cnt[((row - 96) >> 7) * 32], 2 + z);
        bulk_store(pp.n + (size_t)row * (2 * D_), st, 4096); bulk_commit();
        if (row + 96 * FK_XDEPTH < S_) {
          const int sn = (it + FK_XDEPTH) & 3;
          mbar_expect_tx(rbar + sn * 8, 4096); bulk_load(ring + sn * 4096, pp.x + (size_t)(row + 96 * FK_XDEPTH) * (2 * D_), 4096, rbar + sn * 8);
        }
      }
      __syncwarp();
    }
    if (lane == 0) bulk_wait<0>();
    __syncwarp();
    const uint32_t z = landed(ld_rlx(pp.n + (size_t)(row - 96) * (2 * D_) + lane * 128), pp.zero);
    if (lane == 0) red_add(&pp.cnt[((row - 96) >> 7) * 32], 2 + z);
    return;
  }
  if (warp > 4) asm volatile("barrier.cluster.arrive.relaxed.aligned;" ::: "memory");
  if ((unsigned)(warp - 4) < FK_G0) {
    const int row = (warp - 4) * 128 + rb;
    uint4 w[4];
    const bool first = warp < 6;
    {
      if (warp > 4) delay_until(c0, warp == 5 ? FK_ROW1DLY : warp < 8 ? FK_ROW2DLY : FK_ROW4DLY);
#pragma unroll
      for (int i = 0; i < 4; i++) w[i] = ldg_nc(pp.x + (size_t)row * (2 * D_) + lane * 16 + i * 512);
      if (warp == 4) asm volatile("barrier.cluster.arrive.relaxed.aligned;" ::: "memory");
      if (first) {
        const uint32_t z = landed(w[0].x | w[1].x | w[2].x | w[3].x, pp.zero);
        if (lane == 0) red_add(&pp.cnt[(warp - 4) * 32], 1 + z);
        if (tid == 128) TRACE(1);
      }
      ln_row(w);
      char* dst = pp.n + (size_t)row * (2 * D_);
#pragma unroll
      for (int i = 0; i < 4; i++) { w[i].x = nonzero(w[i].x); stg128(dst + lane * 16 + i * 512, w[i]); }
    }
    if (tid == 128) TRACE(31);
    if (lane == 0 && warp == 3 + FK_G0) TRACE(55);
    if (!first) { if (warp < 8) named_arrive<8, 96>(); else named_arrive<9, 32 * (FK_G0 - 3)>(); }
  }
  int m4, t;
  {
    const int c = (rb >> 1) - 2;
    int g = 8, i = c + 2;
    if (c >= 32) { i = ((c - 32) * 37) >> 8; g = c - 32 - 7 * i; g += g >= 2; i += 4; }
    else if (c >= 0) { g = c & 7; i = c >> 3; }
    if (g == 8) { g = 2; i += 6; } else if (i == 8) { i = 4 + g; g = 2; }
    m4 = (g >> 2) * 2 + (i & 1); t = (g & 3) * 4 + (i >> 1);
  }
  const int j = rb & 1, b = t * 8 + m4 * 2 + j;
  const int blk = t * 2 + j;
  const uint32_t scr = sb + 2 * STAGE + j * 8192;
  if (warp < 4) {
    uint32_t tag = ld_rlx(&pp.cnt[17 * 32]);
    auto ws_touch = [&](int o) {
      uint32_t v;
      asm volatile("ld.global.nc.L1::no_allocate.L2::128B.u32 %0, [%1];" : "=r"(v)
                   : "l"((j ? pp.ws_im : pp.ws_re) + (size_t)(t * 128 + m4 * 32 + lane) * (2 * S_) + o));
      return v;
    };
    uint32_t early = 0;
    if (warp == 1) { delay_until(c0, FK_WS0DLY); early = ws_touch(0); if (lane == 0) TRACE(126); }
    if (warp == 0) early = ld_rlx(&pp.cnt[(lane & 1) * 32]);
    if (lane == 0) {
      if (warp < 2) {
        if (warp == 0) {
          prefetch_tmap(&maps.ws[j]); prefetch_tmap(&maps.n);
          if (sb & 1023) __trap();
#pragma unroll
          for (int i = 0; i < 8; i++) mbar_init(BAR(i), bar_count(i));
        } else {
#pragma unroll
          for (int i = 8; i < 22; i++) mbar_init(BAR(i), bar_count(i));
        }
      } else if (warp == 2) {
#pragma unroll
        for (int i = 22; i < 36; i++) mbar_init(BAR(i), bar_count(i));
      } else {
#pragma unroll
        for (int i = 36; i < B_NUM; i++) mbar_init(BAR(i), bar_count(i));
#pragma unroll
        for (int i = 0; i < 4; i++) mbar_expect_tx(BAR(B_RECV + i), 8192);
      }
      asm volatile("fence.mbarrier_init.release.cluster;" ::: "memory");
    }
    named_bar<6, 128>();
    named_arrive<0, 256>(); named_arrive<3, 256>();
    asm volatile("barrier.cluster.arrive.relaxed.aligned;" ::: "memory");
    uint64_t pol_first;
    asm volatile("createpolicy.fractional.L2::evict_first.b64 %0, 1.0;" : "=l"(pol_first));
    const bool moe = b < NMOE;
    uint32_t wf[128];
    auto take = [&](auto R) {
      constexpr int r = decltype(R)::value;
      const uint32_t box = sb + SPARE + warp * 8192;
      if (moe || r == 0) mbar_wait(BAR(B_WB + warp), r);
      if (moe) take_box<r>(wf, box, lane);
      fence_async_smem();
      __syncwarp();
      if (lane == 0) {
        if (r) {
          mbar_arrive(BAR(B_XF));
        }
        else if (moe) { mbar_expect_tx(BAR(B_WB + warp), 8192); tma_2d_hint(box, &maps.wu, b * 32, warp * 128, BAR(B_WB + warp), pol_first); }
      }
      __syncwarp();
    };

    if (warp == 0) {
      auto loadA = [&](int g) {
        mbar_expect_tx(BAR(B_FULL + (g & 3)), SLOT);
        tma_2d_hint(sb + (g & 3) * STAGE, &maps.ws[j], g * 64, t * 128, BAR(B_FULL + (g & 3)), pol_first);
      };
      auto loadB = [&](int g, int bar) { mbar_expect_tx(BAR(bar + (g & 3)), 2 * SLOT); tma_3d(sb + (g & 3) * STAGE + SLOT, &maps.n, 0, g * 64, m4 * 4, BAR(bar + (g & 3))); };
      delay_until(c0, FK_ADLY);
      if (lane == 0) { loadA(0); if (FK_A1EARLY) loadA(1); TRACE(63); }
      asm volatile("add.u32 %0, %0, 1;" : "+r"(tag)::"memory");
      delay_until(c0, FK_POLL0 + (early & pp.zero));
#pragma unroll 1
      for (int gi = 0; gi < 2; gi++) {
        int it = 0;
        const unsigned* cp = &pp.cnt[gi * 32];
        if (gi >= FK_NOHINT) while ((int)(ld_rlx(cp) - tag * 128u) < 0) { if (++it > SPIN_LIMIT) SPIN_FAIL(0x201); }
        if (gi && FK_NOHINT == 2) delay_until(c0, FK_POLL0 + 600);
        if (lane == 0) {
          if (gi == 0) TRACE(2);
          loadB(2 * gi, B_LAND);
          if (gi) loadA(2);
          if (gi || !FK_A1EARLY) loadA(2 * gi + 1);
          loadB(2 * gi + 1, B_LAND);
        }
        __syncwarp();
      }
      if (lane == 0) { prefetch_tmap(&maps.p); prefetch_tmap(&maps.wd[j]); }
      const unsigned tgt = tag * 128u;
      unsigned pend = ld_rlx(&pp.cnt[2 * 32]);
      const char* pfa = piece_addr(pp, b, lane);
      const uint32_t pfn = (lane >> 2) == 2 || lane >= 20 ? 8192 : 7168;
      auto produce1 = [&](int g0, int g1) {
#pragma unroll 1
        for (int g = g0; g < g1; g++) {
          mbar_wait(BAR(B_EMPTYH + (g & 3)), ((g >> 2) - 1) & 1);
          mbar_wait(BAR(B_EMPTY + (g & 3)), ((g >> 2) - 1) & 1);
          if (!(g & 1)) {
            if ((int)(pend - tgt) < 0) {
              int it = 0;
              while ((int)(ld_rlx(&pp.cnt[(g >> 1) * 32]) - tgt) < 0) { if (++it > SPIN_LIMIT) SPIN_FAIL(0x20c); }
            }
            fence_async_global();
            pend = ld_rlx(&pp.cnt[((g >> 1) + 1) * 32]);
          }
          if (lane == 0) {
            loadA(g); loadB(g, B_FULL);
          }
          if (lane == g - FK_PF0 && lane >= FK_PFSKIP) pf_bulk(pfa, pfn);
          __syncwarp();
        }
      };
      produce1(4, FK_TG);
      take(IntC<0>{});
      produce1(FK_TG, FK_TU);
      take(IntC<1>{});
      produce1(FK_TU, 32);
      int sib = 0, pc = 0;
      auto produce2 = [&](int q0, int q1) {
#pragma unroll 1
        for (int q = q0; q < q1; q++) {
          const int s = q & 3, k0 = sibling(m4, sib) * 256 + pc * 64;
          const uint32_t sa = sb + s * STAGE;
          mbar_wait(BAR(B_EMPTY + s), ((q >> 2) + 1) & 1);
          if (lane == 0) {
            mbar_expect_tx(BAR(B_FULL + s), 2 * SLOT);
            tma_2d(sa + SLOT, &maps.wd[j], k0, m4 * 256, BAR(B_FULL + s));
            if (q < 4) mbar_arrive(BAR(B_FULL + s));
          }
          __syncwarp();
          if (q >= 4) {
            mbar_wait(BAR(B_PL + s), 0);
            if (lane == 0) { mbar_expect_tx(BAR(B_LAND + s), SLOT); tma_2d(sa, &maps.p, k0, j * S_ + t * 128, BAR(B_LAND + s)); }
            if (++sib == 4) { sib = 1; pc++; }
          } else if (++pc == 4) { pc = 0; sib = 1; }
          if (lane == 32 + q - FK_PF0 && lane < 27) pf_bulk(pfa, pfn);
          if (q >= FK_XQ && q < FK_XQ + 4 * FK_XS && (q - FK_XQ) % FK_XS == 0) {
            const int w = (q - FK_XQ) / FK_XS;
            mbar_wait(BAR(B_XF), 0);
            if (lane == 0) { mbar_expect_tx(BAR(B_X), 8192); tma_2d(sb + SPARE + w * 8192, &maps.x, m4 * 256 + w * 64, t * 128 + j * 64, BAR(B_X)); }
          }
          __syncwarp();
        }
      };
      produce2(0, 16);
      if (moe) {
        mbar_wait(BAR(B_EMPTY + 0), 1);
        if (lane == 0) {
          mbar_expect_tx(BAR(B_GU), 49152);
#pragma unroll 1
          for (int i = 0; i < 3; i++) {
            tma_2d(sb + i * SLOT, &maps.wg, b * 32, 512 + i * 128, BAR(B_GU));
            tma_2d(sb + i * SLOT + 8192, &maps.wu, b * 32, 512 + i * 128, BAR(B_GU));
          }
        }
        mbar_wait(BAR(B_EMPTY + 1), 1);
        if (FK_WGATE >= 0) mbar_wait(BAR(B_RECV + FK_WGATE), 0);
        if (lane == 0) {
          mbar_expect_tx(BAR(B_GU), 16384);
          tma_2d(sb + STAGE + SLOT, &maps.wg, b * 32, 896, BAR(B_GU));
          tma_2d(sb + STAGE + SLOT + 8192, &maps.wu, b * 32, 896, BAR(B_GU));
        }
#pragma unroll 1
        for (int i = 0; i < 4; i++) {
          if (i == 1) mbar_wait(BAR(B_EMPTY + 2), 1);
          if (i == 3) mbar_wait(BAR(B_XDONE), 0);
          if (i >= FK_DNWIN) mbar_wait(BAR(B_DN + i - FK_DNWIN), 0);
          if (lane == 0) {
            mbar_expect_tx(BAR(B_DN + i), 16384);
            tma_3d(sb + dn_box(i), &maps.wdn, 0, b * 32, i * 4, BAR(B_DN + i));
          }
        }
      }
      __syncwarp();
    } else if (warp == 1) {
      asm volatile("add.u32 %0, %0, 1;" : "+r"(tag)::"memory");
      if (lane == 0) prefetch_tmap(&maps.ps);
      delay_until(c0, FK_WS1DLY);
      float a0 = __uint_as_float(early & pp.zero), a1 = __uint_as_float(ws_touch(128) & pp.zero);
      auto rowsum = [&](int g0, int g1) {
        const uint32_t rb = sb + (m4 * 32 + lane) * 128 + ((lane & 7) << 4);
#pragma unroll 1
        for (int g = g0; g < g1; g++) {
          const int s = g & 3;
          mbar_wait(BAR(B_FULL + s), (g >> 2) & 1);
          uint4 u[8];
#pragma unroll
          for (int c = 0; c < 8; c++) u[c] = lds128u((rb ^ (uint32_t)(c << 4)) + s * STAGE);
#pragma unroll
          for (int c = 0; c < 8; c += 2) { a0 += sum8(u[c]); a1 += sum8(u[c + 1]); }
          if (lane == 0) mbar_arrive(BAR(B_EMPTYH + s) + ((__float_as_uint(a0) | __float_as_uint(a1)) & pp.zero));
        }
      };
      rowsum(0, FK_TG - 2);
      take(IntC<0>{});
      rowsum(FK_TG - 2, 28);
      mbar_wait(BAR(B_MODOK), 0);
      a0 += lds32(sb + RS_OFF + 256 + lane * 4);
      __syncwarp();
      uint2* rsp = &pp.mail->rs[(j * 16 + t) * 128 + lane];
      st_msg8(rsp + m4 * 32, __float_as_uint(a0 + a1), tag);
      {
        uint2 m[4]; int it = 0;
        while (true) {
#pragma unroll
          for (int i = 0; i < 4; i++) m[i] = ld_msg8(rsp + 32 * i);
          if (__all_sync(~0u, m[0].y == tag && m[1].y == tag && m[2].y == tag && m[3].y == tag)) break;
          if (++it > SPIN_LIMIT) SPIN_FAIL(0x208);
        }
#pragma unroll
        for (int i = 0; i < 4; i++) sts32u(sb + RS_OFF + (lane + 32 * i) * 4, pack_bf16(__uint_as_float(m[i].x), __uint_as_float(m[i].x)));
      }
      __syncwarp();
      if (lane == 0) { mbar_arrive(BAR(B_T1)); TRACE(11); }
      take(IntC<1>{});
      {
        uint32_t cn = 0;
#pragma unroll 1
        for (int i = 0; i < 8; i++) {
          const int q = i >> 1, half = (i & 1) ? j : 1 - j;
          if (i < 4) mbar_wait(BAR(B_PRDY + (i & 1) * 2 + (q | (!FK_LF && i == 0))), 0);
          if (i) delay_until(cn, FK_PPACE);
          cn = clk();
          if (lane == 0) {
            tma_store_2d(&maps.ps, sb + q * STAGE + half * 8192, m4 * 256 + q * 64, j * S_ + t * 128 + half * 64);
            bulk_commit();
            if (i && !(i & 1)) { bulk_wait_read<1>(); mbar_arrive(BAR(B_PL + q - 1)); }
          }
          __syncwarp();
        }
        if (lane == 0) { bulk_wait_read<0>(); mbar_arrive(BAR(B_PL + 3)); }
        if (lane == 0) TRACE(8);
      }
      named_bar<7, 64>();
      delay_until(clk(), FK_E2DLY);
      const uint2* cp = &pp.mail->cand[lane];
      auto select = [&](uint2 m) {
        if (!__all_sync(~0u, m.y != 0)) return false;
        uint32_t k1, k2;
        warp_top2(m.y, m.x, k1, k2);
        if (lane == 0) { sts64u(sb + SEL_OFF, k1, k2); mbar_arrive(BAR(B_SEL)); TRACE(19); }
        return true;
      };
      int it = 0;
      while (!select(ld_msg8(cp))) { delay_until(clk(), -(FK_E2GAP)); if (++it > SPIN_LIMIT) SPIN_FAIL(0x206); }
    } else {
      const int kh = warp - 2;
      const uint32_t reg = sb + SPARE + kh * 16384;
      const uint4 cw0 = ldg_nc(pp.c + (kh * 64 + lane) * 16), cw1 = ldg_nc(pp.c + (kh * 64 + lane + 32) * 16);
#pragma unroll 1
      for (int i = 0; i < 2; i++) {
        const uint4 cw4 = i ? cw1 : cw0;
        const uint32_t ad = reg + 12288 + (lane + 32 * i) * 32;
        sts128(ad, round_bf16(silu_f(bf_lo(cw4.x))), round_bf16(silu_f(bf_hi(cw4.x))), round_bf16(silu_f(bf_lo(cw4.y))), round_bf16(silu_f(bf_hi(cw4.y))));
        sts128(ad + 16, round_bf16(silu_f(bf_lo(cw4.z))), round_bf16(silu_f(bf_hi(cw4.z))), round_bf16(silu_f(bf_lo(cw4.w))), round_bf16(silu_f(bf_hi(cw4.w))));
      }
      asm volatile("add.u32 %0, %0, 1;" : "+r"(tag)::"memory");
      if (lane == 0) prefetch_tmap(&maps.wm);
      unsigned ph = 0;
      if (kh == 0) {
#pragma unroll 1
        for (int s = 0; s < 4; s++) {
          const uint32_t ra = sb + s * STAGE + SLOT + lane * 128 + ((lane & 7) << 4);
          int it = 0;
          while (true) {
            mbar_wait(BAR(B_LAND + s), (ph >> s) & 1);
            ph ^= 1u << s;
            if (lane == 0 && it == 0) TRACE(120 + s);
            uint32_t mn = ~0u;
#pragma unroll
            for (int u = 0; u < 8; u++) mn = min(mn, lds32u(ra + u * 4096));
            if (__all_sync(~0u, mn)) break;
            if (lane == 0) { mbar_expect_tx(BAR(B_LAND + s), 2 * SLOT); tma_3d(sb + s * STAGE + SLOT, &maps.n, 0, s * 64, m4 * 4, BAR(B_LAND + s)); TRACE(92 + s); }
            if (++it > (1 << 16)) SPIN_FAIL(0x203);
          }
          if (lane == 0) mbar_arrive(BAR(B_FULL + s));
        }
      } else {
        named_bar<8, 96>();
        uint32_t rbk = ld_rlx(pp.n + (size_t)((2 + (lane >> 4)) * 128 + rb) * (2 * D_) + (lane & 15) * 128);
        uint4 w[FK_GX - FK_G0][4];
        delay_until(c0, FK_ROW8DLY);
#pragma unroll
        for (int k = 0; k < FK_GX - FK_G0; k++)
#pragma unroll
          for (int i = 0; i < 4; i++) w[k][i] = ldg_nc(pp.x + (size_t)((FK_G0 + k) * 128 + rb) * (2 * D_) + lane * 16 + i * 512);
        uint32_t z = landed(rbk, pp.zero);
        if (lane < 2) red_add(&pp.cnt[(2 + lane) * 32], 1 + z);
        named_bar<9, 32 * (FK_G0 - 3)>();
        rbk = 0;
#pragma unroll
        for (int g = 4; g < FK_G0; g += 2) rbk |= ld_rlx(pp.n + (size_t)(min(g + (lane >> 4), FK_G0 - 1) * 128 + rb) * (2 * D_) + (lane & 15) * 128);
        z = landed(rbk, pp.zero);
        if (lane >= 4 && lane < FK_G0) red_add(&pp.cnt[lane * 32], 1 + z);
#pragma unroll
        for (int k = 0; k < FK_GX - FK_G0; k++) {
          ln_row(w[k]);
#pragma unroll
          for (int i = 0; i < 4; i++) stg128(pp.n + (size_t)((FK_G0 + k) * 128 + rb) * (2 * D_) + lane * 16 + i * 512, w[k][i]);
        }
        z = landed(ld_rlx(pp.n + (size_t)(min(FK_G0 + (lane >> 4), FK_GX - 1) * 128 + rb) * (2 * D_) + (lane & 15) * 128), pp.zero);
        if (lane >= FK_G0 && lane < FK_GX) red_add(&pp.cnt[lane * 32], 1 + z);
        if (lane == 0) TRACE(56);
      }
      {
        float acc[3][8];
        uint32_t sad[3];
#pragma unroll
        for (int a = 0; a < 3; a++) {
          sad[a] = reg + 12288 + ((32 * a + lane) / 6) * 4;
#pragma unroll
          for (int i = 0; i < 8; i++) acc[a][i] = 0.f;
        }
        const char* wpf = pp.wm + (size_t)kh * (512 * 12 * D_) + b * 6144;
        const char* wsrc = (j ? pp.ws_im : pp.ws_re) + (size_t)(t * 128 + m4 * 32 + kh * 16 - 16) * (2 * S_) + 28 * 128 + lane * 16;
        if (FK_WMPF && lane == 0) pf_bulk(wpf, 6144);
        uint32_t cn = c0 + FK_GSTART + kh * (FK_PACE / 2);
        auto request = [&](int c) {
          mbar_expect_tx(BAR(B_WM + kh * 2 + (c & 1)), 6144 + ((__float_as_uint(acc[0][0]) | __float_as_uint(acc[1][0]) | __float_as_uint(acc[2][0])) & pp.zero));
          tma_2d_hint(reg + (c & 1) * 6144, &maps.wm, b * 48, kh * 512 + c * 64, BAR(B_WM + kh * 2 + (c & 1)), pol_first);
        };
        uint4 e[4];
#pragma unroll 1
        for (int c = -2; c < 8; c++) {
          while ((int)(clk() - cn) < 0) __nanosleep(40);
          cn += c < 0 ? FK_PACE0 : FK_PACE;
          if (lane == 0) {
            if (FK_WMPF && c < 5) pf_bulk(wpf + (size_t)(c + 3) * (64 * 12 * D_), 6144);
          }
          __syncwarp();
          if (c < 0) {
            if (lane == 0) request(c + 2);
            __syncwarp();
            continue;
          }
          if (c >= 4) {
            const float v0 = sum8(e[0]), v1 = sum8(e[1]), v2 = sum8(e[2]), v3 = sum8(e[3]);
            const bool u4 = lane & 16, u3 = lane & 8;
            const float w0 = (u4 ? v2 : v0) + __shfl_xor_sync(~0u, u4 ? v0 : v2, 16), w1 = (u4 ? v3 : v1) + __shfl_xor_sync(~0u, u4 ? v1 : v3, 16);
            float v = (u3 ? w1 : w0) + __shfl_xor_sync(~0u, u3 ? w0 : w1, 8);
            v += __shfl_xor_sync(~0u, v, 4); v += __shfl_xor_sync(~0u, v, 2); v += __shfl_xor_sync(~0u, v, 1);
            if (!(lane & 7)) sts32(sb + RS_OFF + 256 + (kh * 16 + c * 4 - 16 + (lane >> 3)) * 4, v);
          }
          if (c >= FK_ZC0) {
            constexpr int LPR = FK_ZB / 16, RPI = 8 / LPR, NI = 64 / RPI / (8 - FK_ZC0);
            char* pr = pp.P + (size_t)(j * S_ + t * 128 + kh * 64 + (c - FK_ZC0) * NI * RPI + lane / (4 * LPR)) * (2 * D_) + m4 * 512 + ((lane / LPR) & 3) * 128 + (lane % LPR) * 16;
#pragma unroll
            for (int i = 0; i < NI; i++) stg128(pr + (size_t)i * (RPI * 2 * D_), make_uint4(0, 0, 0, 0));
          }
          if (c >= 3 && c < 7) {
#pragma unroll
            for (int i = 0; i < 4; i++) e[i] = ldg_nc(wsrc + (size_t)(c * 4 + 4 + i) * (2 * S_));
          }
          mbar_wait(BAR(B_WM + kh * 2 + (c & 1)), (c >> 1) & 1);
#pragma unroll
          for (int u = 0; u < 12; u++) {
            const uint4 v = lds128u(reg + (c & 1) * 6144 + lane * 16 + u * 512);
            const float sc = lds32(sad[u % 3] + (u / 3) * 64);
            float (&ac)[8] = acc[u % 3];
            ac[0] = fmaf(sc, bf_lo(v.x), ac[0]); ac[1] = fmaf(sc, bf_hi(v.x), ac[1]);
            ac[2] = fmaf(sc, bf_lo(v.y), ac[2]); ac[3] = fmaf(sc, bf_hi(v.y), ac[3]);
            ac[4] = fmaf(sc, bf_lo(v.z), ac[4]); ac[5] = fmaf(sc, bf_hi(v.z), ac[5]);
            ac[6] = fmaf(sc, bf_lo(v.w), ac[6]); ac[7] = fmaf(sc, bf_hi(v.w), ac[7]);
          }
#pragma unroll
          for (int a = 0; a < 3; a++) sad[a] += 256;
          __syncwarp();
          if (lane == 0 && c < 6) request(c + 2);
        }
        __syncwarp();
#pragma unroll
        for (int a = 0; a < 3; a++) {
          sts128(reg + (32 * a + lane) * 32, acc[a][0], acc[a][1], acc[a][2], acc[a][3]);
          sts128(reg + (32 * a + lane) * 32 + 16, acc[a][4], acc[a][5], acc[a][6], acc[a][7]);
        }
        __syncwarp();
        float s0 = 0.f, s1 = 0.f;
#pragma unroll 8
        for (int m = 0; m < 16; m++) { const float2 v = lds64(reg + (lane < 24 ? lane * 8 : 0) + m * 192); s0 += v.x; s1 += v.y; }
        if (kh == 0) sts64(sb + RS_OFF + lane * 8, s0, s1);
        if (lane == 0) TRACE(80 + kh);
        named_bar<5, 64>();
        if (kh == 1) {
          const float2 p = lds64(sb + RS_OFF + lane * 8);
          unsigned* dst = pp.mod + b * 24 + (lane < 24 ? lane : 0);
          if (lane < 24) st_rlx(dst, pack_bf16(s0 + p.x, s1 + p.y));
          uint32_t rbk = ld_rlx(dst);
          if (b == 0) { st_msg8(&pp.mail->cand[lane], 0, 0); rbk |= ld_rlx(&pp.mail->cand[lane]); }
          const uint32_t z = landed(rbk, pp.zero);
          if (lane == 0) { red_add(&pp.cnt[16 * 32], 1 + z); mbar_arrive(BAR(B_MODOK)); TRACE(9); }
          __syncwarp();
        }
      }
      if (kh == 0) {
#pragma unroll 1
        for (int i = 0; i < 4; i++) {
          const int w = i ^ 2;
          if (lane == 0) {
            if (moe) { mbar_expect_tx(BAR(B_WB + w), 8192); tma_2d_hint(sb + SPARE + w * 8192, &maps.wg, b * 32, w * 128, BAR(B_WB + w), pol_first); }
            else mbar_arrive(BAR(B_WB + w));
          }
          __nanosleep(FK_BSLEEP);
        }
        take(IntC<0>{});
        if (lane == 0) { fence_gpu(); mbar_arrive(BAR(B_MODOK)); TRACE(57); }
        __syncwarp();
        take(IntC<1>{});
        if (lane == 0) TRACE(98);
        int sib = 1, pc = 0;
#pragma unroll 1
        for (int q = 4; q < 16; q++) {
          const int s = q & 3;
          const uint32_t ra = sb + s * STAGE + lane * 128 + ((lane & 7) << 4);
          int it = 0;
          while (true) {
            mbar_wait(BAR(B_LAND + s), (ph >> s) & 1);
            ph ^= 1u << s;
            if (__all_sync(~0u, min(min(lds32u(ra), lds32u(ra + 4096)), min(lds32u(ra + 8192), lds32u(ra + 12288))))) break;
            if (lane == 0) {
              mbar_expect_tx(BAR(B_LAND + s), SLOT);
              tma_2d(sb + s * STAGE, &maps.p, sibling(m4, sib) * 256 + pc * 64, j * S_ + t * 128, BAR(B_LAND + s));
            }
            if (++it > (1 << 16)) SPIN_FAIL(0x202);
          }
          if (lane == 0) mbar_arrive(BAR(B_FULL + s));
          if (++sib == 4) { sib = 1; pc++; }
        }
        if (lane == 0) TRACE(99);
      } else {
        take(IntC<0>{});
        {
          const unsigned tgt = tag * 128u; int it = 0;
          while ((int)(ld_rlx(&pp.cnt[16 * 32]) - tgt) < 0) { __nanosleep(100); if (++it > SPIN_LIMIT) SPIN_FAIL(0x204); }
        }
        if (lane == 0) TRACE(10);
        st_rlx(reinterpret_cast<unsigned*>(pp.n + (size_t)((lane >> 4) * 128 + rb) * (2 * D_) + (lane & 15) * 128), 0);
        {
          const uint32_t sgn = j ? 0x80008000u : 0u;
          uint32_t sa[4], ca[4]; uint4 sv[4], cv[4], wr[4];
#pragma unroll
          for (int i = 0; i < 4; i++) {
            const int p = lane + 32 * i;
            sa[i] = ld_rlx(pp.mod + m4 * 128 + p); ca[i] = ld_rlx(pp.mod + 512 + m4 * 128 + p);
            sv[i] = ld_msg(reinterpret_cast<const uint4*>(pp.mod + 1536) + p); cv[i] = ld_msg(reinterpret_cast<const uint4*>(pp.mod + 2048) + p);
            wr[i] = ldg_nc(pp.wr + p * 16);
          }
          float c1 = 0.f, c2 = 0.f;
#pragma unroll
          for (int i = 0; i < 4; i++) {
            const int p = lane + 32 * i;
            sts64(sb + T1_OFF + ((p >> 3) * 4 + (p & 3)) * 16 + ((p >> 2) & 1) * 8, __uint_as_float(add1_bf2(ca[i]) ^ sgn), __uint_as_float(sa[i] ^ sgn));
            const uint32_t s4[4] = {sv[i].x, sv[i].y, sv[i].z, sv[i].w}, c4[4] = {cv[i].x, cv[i].y, cv[i].z, cv[i].w}, w4[4] = {wr[i].x, wr[i].y, wr[i].z, wr[i].w};
#pragma unroll
            for (int u = 0; u < 4; u++) {
              const uint32_t A = add1_bf2(c4[u]);
              c1 = fmaf(bf_lo(A), bf_lo(w4[u]), c1); c1 = fmaf(bf_hi(A), bf_hi(w4[u]), c1);
              c2 = fmaf(bf_lo(s4[u]), bf_lo(w4[u]), c2); c2 = fmaf(bf_hi(s4[u]), bf_hi(w4[u]), c2);
            }
          }
#pragma unroll
          for (int o = 16; o; o >>= 1) { c1 += __shfl_xor_sync(~0u, c1, o); c2 += __shfl_xor_sync(~0u, c2, o); }
          __syncwarp();
          if (lane == 0) { sts128(sb + CST_OFF, c1, c2, __uint_as_float(tag), 0.f); mbar_arrive(BAR(B_T1)); TRACE(30); }
        }
        take(IntC<1>{});
        const int G = lane >> 2, q = lane & 3, p0 = m4 * 128 + G * 16 + q;
        mbar_wait(BAR(B_PRDY + 1), 0);
        mbar_wait(BAR(B_PRDY + 3), 0);
        uint32_t ga[4], hi[4], lo[4];
#pragma unroll
        for (int u = 0; u < 4; u++) {
          ga[u] = ld_rlx(pp.mod + 1024 + p0 + 4 * u);
          const uint32_t cb = ld_rlx(pp.mod + 2048 + p0 + 4 * u), wr = __ldg(reinterpret_cast<const uint32_t*>(pp.wr) + p0 + 4 * u);
          const float w0 = bf_lo(add1_bf2(cb)) * bf_lo(wr), w1 = bf_hi(add1_bf2(cb)) * bf_hi(wr);
          hi[u] = pack_bf16(w0, w1);
          lo[u] = pack_bf16(w0 - bf_lo(hi[u]), w1 - bf_hi(hi[u]));
        }
        sts128u(sb + GA_OFF + lane * 16, ga[0], ga[1], ga[2], ga[3]);
        sts128u(sb + W_OFF + G * 144 + q * 16, hi[0], hi[1], hi[2], hi[3]);
        sts128u(sb + W_OFF + G * 144 + 64 + q * 16, lo[0], lo[1], lo[2], lo[3]);
        sts32u(sb + W_OFF + G * 144 + 128 + q * 4, 0x3F803F80u);
        mbar_wait(BAR(B_PL + 3), 0);
        __nanosleep(FK_RSLEEP);
        const uint4 sv = make_uint4(SENT, SENT, SENT, SENT);
#pragma unroll 1
        for (int i = 0; i < 7; i++) stg128(&pp.mail->part[(size_t)b * (NMOE * 2) + lane + 32 * i], sv);
#pragma unroll 1
        for (int i = 0; i < 2; i++) {
          stg128(&pp.mail->stats[(blk * 4 + m4) * 64 + lane + 32 * i], sv);
          stg128(&pp.mail->rowh[(blk * 2 + i) * 128 + m4 * 32 + lane], sv);
          stg128(&pp.mail->rowx[(blk * 2 + i) * 128 + m4 * 32 + lane], sv);
        }
        if (lane == 0) { red_max8(&pp.mail->cand[blk], 1, 0); red_add(&pp.cnt[18 * 32], 1); }
        __syncwarp();
        if (lane == 0) { fence_gpu(); mbar_arrive(BAR(B_T2)); TRACE(97); }
      }
    }
    mbar_wait(BAR(B_SEL), 0);
    if (moe) gate_up(pp, wf, sb, scr, warp, lane);
    if (warp == 1) {
      const uint2 sel = lds64u(sb + SEL_OFF);
      const int n = (lane >> 3) & 1;
      const int col = (b >> 4) * 128 + (lane & 1) * 64 + ((b >> 2) & 3) * 16 + (b & 3) * 2 + ((lane >> 1) & 1) + (lane >> 4) * 8;
      const int slot = sel_slot(sel, n) * 512, wofs = slot + ((col >> 5) * 4 + ((col >> 1) & 3)) * 4 + ((col >> 3) & 3);
      const uint32_t gbp = ld_rlx(pp.mod + 2560 + (col >> 1));
      uint32_t hp, xp; int it = 0;
      while (true) {
        hp = ld_rlx(reinterpret_cast<const uint32_t*>(pp.mail->rowh) + wofs); xp = ld_rlx(reinterpret_cast<const uint32_t*>(pp.mail->rowx) + slot + (col >> 1));
        if (__all_sync(~0u, hp != SENT && xp != SENT)) break;
        if (++it > SPIN_LIMIT) SPIN_FAIL(0x2ff);
      }
      const float sg = round_bf16(sigmoid_f(round_bf16(key_val(n ? sel.y : sel.x))));
      const bool odd = col & 1;
      float gbv = odd ? bf_hi(gbp) : bf_lo(gbp), hv = odd ? bf_hi(hp) : bf_lo(hp), xv = odd ? bf_hi(xp) : bf_lo(xp);
      char* optr = pp.out + ((size_t)key_row(n ? sel.y : sel.x) * D_ + col) * 2;
      asm volatile("" : "+f"(gbv), "+f"(hv), "+f"(xv), "+l"(optr));
      const int gq = lane >> 2;
      const uint32_t one = (lane & 1) == (gq >> 2) ? ((gq & 1) ? 0x3F800000u : 0x00003F80u) : 0u;
      const uint32_t s0 = (gq & 2) ? 0u : one, s1 = (gq & 2) ? one : 0u;
      const uint4* src = &pp.mail->part[(size_t)b * (NMOE * 2) + lane];
      uint4 m[7];
      it = 0;
      while ((int)(ld_rlx(&pp.cnt[18 * 32]) - tag * (NCTA + NMOE)) < 0) { if (++it > SPIN_LIMIT) SPIN_FAIL(0x20d); }
      delay_until(clk(), FK_E4DLY);
      it = 0;
      while (true) {
        bool ok = true;
#pragma unroll
        for (int i = 0; i < 7; i++) m[i] = ld_msg(src + 32 * i);
#pragma unroll
        for (int i = 0; i < 7; i++) ok &= m[i].x != SENT;
        if (__all_sync(~0u, ok)) break;
        if (++it > SPIN_LIMIT) SPIN_FAIL(0x20b);
      }
      if (lane == 0) TRACE(23);
      float c[3][4];
#pragma unroll
      for (int i = 0; i < 3; i++) { c[i][0] = c[i][1] = c[i][2] = c[i][3] = 0.f; }
#pragma unroll
      for (int i = 0; i < 7; i++) mma_16816(c[i % 3], m[i].x, m[i].y, m[i].z, m[i].w, s0, s1);
#pragma unroll
      for (int i = 0; i < 4; i++) c[0][i] += c[1][i] + c[2][i];
      const bool u4 = lane & 16, u3 = lane & 8;
      const float a0 = (u4 ? c[0][2] : c[0][0]) + __shfl_xor_sync(~0u, u4 ? c[0][0] : c[0][2], 16), a1 = (u4 ? c[0][3] : c[0][1]) + __shfl_xor_sync(~0u, u4 ? c[0][1] : c[0][3], 16);
      float y = (u3 ? a1 : a0) + __shfl_xor_sync(~0u, u3 ? a0 : a1, 8);
      y += __shfl_xor_sync(~0u, y, 4);
      const float upd = round_bf16(round_bf16(y) * sg);
      const uint32_t o = pack_bf16(fmaf(gbv, hv + upd, xv), 0.f);
      if (!(lane & 4)) asm volatile("st.global.u16 [%0], %1;" ::"l"(optr), "h"((unsigned short)o) : "memory");
      if (lane == 0) { TRACE(24); TRACE_CLK(54); if (b == 0) pp.cnt[17 * 32] = tag; }
    }
  } else {
    const int cw = (warp - 4) >> 2;
    const int wq = warp & 3;
    const int wtid = tid & 127;
    const int gq = lane >> 2, q4 = lane & 3;
    const bool lag = cw == j;
    const bool elect = wtid == 0;
    const uint32_t rel = wtid < 2 ? mapa(BAR(B_EMPTY), wtid) : 0;

    if (cw) named_bar<3, 256>(); else named_bar<0, 256>();
    if (tid == 128) TRACE(124);
    asm volatile("barrier.cluster.wait.acquire.aligned;" ::: "memory");
    if (tid == 128) TRACE(125);

    const int mrow = wq * 16 + (lane & 7) + ((lane >> 3) & 1) * 8;
    {
      float acc[128];
      gemm_phase<1, 0, 32>(pp, acc, sb, cw, lag, elect, rel);
      mbar_wait(BAR(B_T1), 0);
      const uint32_t tad = sb + T1_OFF + q4 * 16;
      uint4 tb[16];
#pragma unroll
      for (int c = 0; c < 4; c++) tb[c] = lds128u(tad + c * 64);
      const uint32_t rs0 = lds32u(sb + RS_OFF + (cw * 64 + wq * 16 + gq) * 4), rs1 = lds32u(sb + RS_OFF + (cw * 64 + wq * 16 + gq + 8) * 4);
      const uint32_t dst = sb + cw * 8192 + mrow * 128, pb = BAR(B_PRDY + (lag ? 2 : 0));
      gemm_finish(acc, rel);
      if (elect) { TRACE(lag ? 5 : 4); if (lag) TRACE_CLK(51); }
#pragma unroll
      for (int i = 0; i < 16; i++) {
        uint32_t r[4];
        const int o = 8 * i;
        r[0] = fma_bf2(pack_bf16(acc[o], acc[o + 1]), tb[i].x, mul_bf2(rs0, tb[i].y));
        r[1] = fma_bf2(pack_bf16(acc[o + 2], acc[o + 3]), tb[i].x, mul_bf2(rs1, tb[i].y));
        r[2] = fma_bf2(pack_bf16(acc[o + 4], acc[o + 5]), tb[i].z, mul_bf2(rs0, tb[i].w));
        r[3] = fma_bf2(pack_bf16(acc[o + 6], acc[o + 7]), tb[i].z, mul_bf2(rs1, tb[i].w));
        if (!(i & 3)) { r[0] = nonzero(r[0]); r[1] = nonzero(r[1]); }
        if (i < 12) tb[i + 4] = lds128u(tad + (i + 4) * 64);
        stsm_x4(dst + (i >> 2) * STAGE + (uint32_t)(((((2 * i) & 7) + (lane >> 4)) ^ (lane & 7)) << 4), r[0], r[1], r[2], r[3]);
        if ((i == 3 && (lag || FK_LF)) || i == 15) {
          fence_async_smem();
          __syncwarp();
          if (lane == 0) mbar_arrive(pb + (i >> 3) * 8);
        }
      }
      if (FK_WB) mbar_wait(pb + 8, 0);
    }
    if (elect) TRACE(lag ? 7 : 6);
    float acc[128];
    gemm_phase<0, 32, 48>(pp, acc, sb, cw, lag, elect, rel);

    if (!lag) {
      const uint32_t rdst = mapa(sb + STAGE + j * 8192 + wtid * 16, j ^ 1), rbar = mapa(BAR(B_RECV), j ^ 1);
      mbar_wait(BAR(B_PEER), 0);
      gemm_finish(acc, rel);
      if (elect) { mbar_arrive_cluster(rbar + (B_PEER + 1 - B_RECV) * 8); TRACE(12); }
#pragma unroll
      for (int i = 0; i < 16; i++) {
        const int o = 8 * i;
        if (i == 8) mbar_wait(BAR(B_PEER + 1), 0);
        if (i == 12) mbar_wait(BAR(B_EMPTY + 1), 1);
        asm volatile("st.async.weak.shared::cluster.mbarrier::complete_tx::bytes.v4.b32 [%0], {%1, %2, %3, %4}, [%5];"
                     ::"r"(i < 12 ? rdst + (i >> 2) * STAGE + (i & 3) * 2048 : rdst + (1 - 2 * j) * 8192 + (i & 3) * 2048),
                       "r"(pack_bf16(acc[o], acc[o + 1])), "r"(pack_bf16(acc[o + 2], acc[o + 3])), "r"(pack_bf16(acc[o + 4], acc[o + 5])),
                       "r"(pack_bf16(acc[o + 6], acc[o + 7])), "r"(rbar + (i >> 2) * 8) : "memory");
      }
      if (elect) TRACE(13);
      if (b < NMOE) {
        uint32_t wf[128];
        named_bar<1, 256>();
        mbar_wait(BAR(B_GU), 0);
        const uint32_t box = sb + (wq < 3 ? wq : 4) * SLOT;
        take_box<0>(wf, box, lane);
        take_box<1>(wf, box + 8192, lane);
        if (elect) TRACE(26);
        mbar_wait(BAR(B_SEL), 0);
        gate_up(pp, wf, sb, scr, 4 + wq, lane);
        if (elect) red_add(&pp.cnt[18 * 32], 1);
        if (FK_QUIET) named_bar<8, 256>();
      }
      OutTab tb;
      {
        const uint4* mp = reinterpret_cast<const uint4*>(pp.mod) + m4 * 32 + lane;
        out_tab(tb, ldg128(mp + 512), ldg128(mp + 384), ldg128(mp + 640));
      }
      mbar_wait(BAR(B_SEL), 0);
      const uint2 sel = lds64u(sb + SEL_OFF), cnd = lds64u(sb + TOP_OFF + 32);
      char* odst = pp.out + (size_t)blk * (64 * 2 * D_) + m4 * 512 + lane * 16;
      const int g0 = blk * 64 + wq * 16;
      mbar_wait(BAR(B_OUT), 0);
      const uint32_t done = lds32u(sb + TOP_OFF + 48 + wq * 4);
      out_group(tb, sb, scr, wq * 16, ((0xFFFFu & (0xFFFFu << done)) | row_bit(cnd.x, g0) | row_bit(cnd.y, g0)) & ~(row_bit(sel.x, g0) | row_bit(sel.y, g0)),
                lane, odst, FK_OPACE2, 0);
      if (elect) TRACE(28);
    } else {
      mbar_wait(BAR(B_T2), 0);
      uint32_t xa[64];
      float dl[2][4], dq[4][4];
#pragma unroll
      for (int i = 0; i < 4; i++) { dl[0][i] = dl[1][i] = dq[0][i] = dq[1][i] = dq[2][i] = dq[3][i] = 0.f; }
      {
        uint32_t wad = sb + W_OFF + ((gq & 2) ? 128 : (gq & 1) * 64 + q4 * 16), gad = sb + GA_OFF + q4 * 16;
        uint32_t rsrc = sb + STAGE + (1 - j) * 8192 + wtid * 16, xad = sb + SPARE + mrow * 128 + (uint32_t)(((lane >> 4) ^ (lane & 7)) << 4);
        asm volatile("" : "+r"(wad), "+r"(gad), "+r"(rsrc), "+r"(xad));
        uint4 rv[16], wb[8], ga[8];
        uint32_t xf[16][4];
        auto loadx = [&](int i) { ldsm_x4((xad ^ (uint32_t)((i & 3) << 5)) + (i >> 2) * 8192, xf[i][0], xf[i][1], xf[i][2], xf[i][3]); };
        auto loadr = [&](int i) { rv[i] = lds128u(i < 12 ? rsrc + (i >> 2) * STAGE + (i & 3) * 2048 : rsrc + (2 * j - 1) * 8192 + (i & 3) * 2048); };
        auto loadt = [&](int h) { loadx(2 * h); loadx(2 * h + 1); ga[h] = lds128u(gad + h * 64); wb[h] = lds128u(wad + h * 144); };
        mbar_wait(BAR(B_X), 0);
        mbar_wait(BAR(B_RECV), 0);
        loadx(0); loadr(0); ga[0] = lds128u(gad);
        mbar_wait(BAR(B_RECV + 1), 0);
        gemm_finish(acc, rel);
        if (elect) { TRACE(14); TRACE_CLK(53); }
#pragma unroll
        for (int u = 0; u < 8 * FK_PK; u++) {
          xa[u] = pack_bf16(acc[2 * u], acc[2 * u + 1]);
          if (u == 15) { loadx(1); loadr(1); wb[0] = lds128u(wad); }
        }
#pragma unroll
        for (int h = 0; h < 8; h++) {
          if (h == FK_W2 || h == 6) mbar_wait(BAR(B_RECV + (h == 6 ? 3 : 2)), 0);
          if (h == 6) { loadr(12); loadr(13); }
          if (h < 7) loadt(h + 1);
          if (h < 7 && h != 5) { loadr(2 * h + 2); loadr(2 * h + 3); }
          if (h + FK_PK < 8) {
#pragma unroll
            for (int u = 8 * (h + FK_PK); u < 8 * (h + FK_PK) + 8; u++) xa[u] = pack_bf16(acc[2 * u], acc[2 * u + 1]);
          }
#pragma unroll
          for (int i = 2 * h; i < 2 * h + 2; i++) {
            const uint32_t g0 = (i & 1) ? ga[h].z : ga[h].x, g1 = (i & 1) ? ga[h].w : ga[h].y;
            const uint32_t a0 = fma_bf2(g0, add_bf2(xa[4 * i], rv[i].x), xf[i][0]), a1 = fma_bf2(g0, add_bf2(xa[4 * i + 1], rv[i].y), xf[i][1]);
            const uint32_t a2 = fma_bf2(g1, add_bf2(xa[4 * i + 2], rv[i].z), xf[i][2]), a3 = fma_bf2(g1, add_bf2(xa[4 * i + 3], rv[i].w), xf[i][3]);
            xa[4 * i] = a0; xa[4 * i + 1] = a1; xa[4 * i + 2] = a2; xa[4 * i + 3] = a3;
            mma_1688(dq[0], a0, a1, a0); mma_1688(dq[1], a0, a1, a1);
            mma_1688(dq[2 % FK_NQ], a2, a3, a2); mma_1688(dq[3 % FK_NQ], a2, a3, a3);
            mma_16816(dl[i & (FK_NL - 1)], a0, a1, a2, a3, (i & 1) ? wb[h].z : wb[h].x, (i & 1) ? wb[h].w : wb[h].y);
          }
        }
      }
      const float4 cst = lds128(sb + CST_OFF);
      const uint32_t tag = __float_as_uint(cst.z);
      uint4 own;
      {
        const bool odd = q4 & 1;
        const float l0 = dl[0][0] + dl[1][0], l1 = dl[0][1] + dl[1][1], l2 = dl[0][2] + dl[1][2], l3 = dl[0][3] + dl[1][3];
        const float mine = odd ? l2 : l0 + l1;
        const float other = __shfl_xor_sync(~0u, odd ? l0 : l2 + l3, 1);
        const int dsrc = (lane & ~3) | (gq >> 1);
        const float qa = __shfl_sync(~0u, (gq & 1) ? dq[0][1] + dq[2][1] : dq[0][0] + dq[2][0], dsrc);
        const float qb = __shfl_sync(~0u, (gq & 1) ? dq[1][3] + dq[3][3] : dq[1][2] + dq[3][2], dsrc);
        own = make_uint4(__float_as_uint(odd ? mine : other), __float_as_uint(odd ? qb : qa), __float_as_uint(odd ? other : mine), tag);
        if (q4 < 2) st_msg(&pp.mail->stats[(blk * 4 + m4) * 64 + wq * 16 + gq + 8 * q4], own.x, own.y, own.z, tag);
      }
      if (lane == 0) mbar_arrive(BAR(B_XDONE));
      if (elect) TRACE(15);
      const int srow = wq * 16 + gq + 8 * (q4 & 1);
      const uint4* src0 = &pp.mail->stats[(blk * 4 + (m4 ^ (q4 | 1))) * 64 + srow];
      const uint4* src1 = &pp.mail->stats[(blk * 4 + (m4 ^ 2)) * 64 + srow];
      if (FK_E1DLY) delay_until(clk(), FK_E1DLY);
      uint4 m0 = ld_msg(src0), m1 = own;
      if (q4 >= 2) m1 = ld_msg(src1);
      mbar_wait(BAR(B_EMPTY + 3), 1);
#pragma unroll
      for (int i = 0; i < 16; i++)
        stsm_x4(sb + XST_OFF + mrow * 512 + (i >> 2) * 128 + (uint32_t)(((((2 * i) & 7) + (lane >> 4)) ^ (lane & 7)) << 4), xa[4 * i], xa[4 * i + 1], xa[4 * i + 2], xa[4 * i + 3]);
      uint4 cbv, sbv, gbv;
      const uint4* mp = reinterpret_cast<const uint4*>(pp.mod) + m4 * 32 + lane;
      cbv = ldg128(mp + 512); sbv = ldg128(mp + 384); gbv = ldg128(mp + 640);
      uint32_t k1, k2;
      uint2* cdst = &pp.mail->cand[blk];
      uint32_t tad = sb + TOP_OFF + (lane & 3) * 8, rad = scr + RST_REL + srow * 8, krow = 2047 - (blk * 64 + srow);
      asm volatile("" : "+l"(cdst), "+r"(tad), "+r"(rad), "+r"(krow));
      {
        int it = 0;
        while (!__all_sync(~0u, m0.w == tag && m1.w == tag)) {
          m0 = ld_msg(src0);
          if (q4 >= 2) m1 = ld_msg(src1);
          if (++it > SPIN_LIMIT) SPIN_FAIL(0x209);
        }
        if (elect) TRACE(16);
        float sa = __uint_as_float(m0.x) + __uint_as_float(m1.x), qa = __uint_as_float(m0.y) + __uint_as_float(m1.y), da = __uint_as_float(m0.z) + __uint_as_float(m1.z);
        sa += __shfl_xor_sync(~0u, sa, 2); qa += __shfl_xor_sync(~0u, qa, 2); da += __shfl_xor_sync(~0u, da, 2);
        const float mean = sa * (1.f / D_);
        const float rstd = rsqrt_f(fmaxf(fmaf(-mean, mean, qa * (1.f / D_)), 0.f) + 1e-5f);
        const float rme = fmaf(rstd, fmaf(-mean, cst.x, da), cst.y);
        warp_top2(fkey(rme, 2047 - krow), 0u, k1, k2);
        if (lane == wq) sts64u(tad, k1, k2);
        if (q4 < 2) sts64(rad, rstd, -mean * rstd);
        named_bar<2, 128>();
        const uint2 c = lds64u(tad);
        warp_top2(c.x, c.y, k1, k2);
        if (wq == 0) {
          if (lane == 0 && (FK_PUSHALL || m4 == (t & 3))) red_max8(cdst, k2, k1);
          if (lane == 0) sts64u(sb + TOP_OFF + 32, k1, k2);
          named_arrive<7, 64>();
        }
      }
      if (b < NMOE) named_arrive<1, 256>();
      if (elect) TRACE(17);
      const int c1 = key_row(k1) - blk * 64, c2 = key_row(k2) - blk * 64;
      if (wq >= 2) {
        const int r = wq == 2 ? c1 : c2;
        const uint4 v = lds128u(sb + XST_OFF + r * 512 + ((lane ^ (r & 7)) << 4));
        const float2 st = lds64(scr + RST_REL + r * 8);
        auto h2 = [&](uint32_t xv, uint32_t cv, uint32_t sv) {
          const uint32_t av = add1_bf2(cv);
          return pack_bf16(fmaf(fmaf(bf_lo(xv), st.x, st.y), bf_lo(av), bf_lo(sv)), fmaf(fmaf(bf_hi(xv), st.x, st.y), bf_hi(av), bf_hi(sv)));
        };
        const uint32_t sc = scr + SCR_REL + wq * 512;
        sts128u(sc + lane * 16, h2(v.x, cbv.x, sbv.x), h2(v.y, cbv.y, sbv.y), h2(v.z, cbv.z, sbv.z), h2(v.w, cbv.w, sbv.w));
        __syncwarp();
        const uint32_t fa = sc + gq * 64 + q4 * 4;
        const int o = (blk * 2 + wq - 2) * 128 + m4 * 32 + lane;
        st_msg(&pp.mail->rowh[o], lds32u(fa), lds32u(fa + 16), lds32u(fa + 32), lds32u(fa + 48));
        st_msg(&pp.mail->rowx[o], v.x, v.y, v.z, v.w);
        if (lane == 0 && wq == 3) TRACE(18);
      }
      {
        OutTab tb;
        out_tab(tb, cbv, sbv, gbv);
        char* odst = pp.out + (size_t)blk * (64 * 2 * D_) + m4 * 512 + lane * 16;
        const int g0 = blk * 64 + wq * 16;
        const int done = out_group(tb, sb, scr, wq * 16, 0xFFFFu & ~(row_bit(k1, g0) | row_bit(k2, g0)), lane, odst, FK_OPACE, b < NMOE ? BAR(B_SEL) : 0);
        if (lane == 0) { sts32u(sb + TOP_OFF + 48 + wq * 4, done); mbar_arrive(BAR(B_OUT)); }
      }
      if (elect) TRACE(25);
      if (b < NMOE) {
        uint32_t wd[128];
        mbar_wait(BAR(B_DN + wq), 0);
        {
          const int fr = (lane & 7) + (lane >> 4) * 8;
          const uint32_t base = sb + dn_box(wq) + fr * 128;
#pragma unroll
          for (int c = 0; c < 4; c++) {
            const uint32_t ad = base + (((uint32_t)(c * 2 + ((lane >> 3) & 1)) ^ (uint32_t)(lane & 7)) << 4);
#pragma unroll
            for (int gI = 0; gI < 4; gI++)
#pragma unroll
              for (int ks = 0; ks < 2; ks++) {
                const int o = ((gI * 4 + c) * 2 + ks) * 4;
                ldsm_x4_t(ad + gI * 4096 + ks * 2048, wd[o], wd[o + 1], wd[o + 2], wd[o + 3]);
              }
          }
        }
        uint4* dst = &pp.mail->part[((size_t)(wq * 32 + q4 * 4 + (gq >> 1)) * NMOE + b) * 2 + (gq & 1)];
        uint32_t pad = scr + PART_REL + lane * 16;
        asm volatile("" : "+l"(dst), "+r"(pad));
        if (lane == 0 && wq == 3) TRACE(27);
        named_bar<4, 384>();
        if (elect) TRACE(21);
        float4 ps[4];
#pragma unroll
        for (int w = 0; w < 4; w++) {
          const float4 p0 = lds128(pad + w * 1024), p1 = lds128(pad + w * 1024 + 512);
          ps[w] = make_float4(p0.x + p1.x, p0.y + p1.y, p0.z + p1.z, p0.w + p1.w);
        }
        const uint32_t gp = pack_bf16((ps[0].x + ps[1].x) + (ps[2].x + ps[3].x), (ps[0].y + ps[1].y) + (ps[2].y + ps[3].y));
        const uint32_t up = pack_bf16((ps[0].z + ps[1].z) + (ps[2].z + ps[3].z), (ps[0].w + ps[1].w) + (ps[2].w + ps[3].w));
        const uint32_t act = mul_bf2(pack_bf16(silu_f(bf_lo(gp)), silu_f(bf_hi(gp))), up);
        uint32_t ab[4];
#pragma unroll
        for (int u = 0; u < 4; u++) {
          const uint32_t v0 = __shfl_sync(~0u, act, 8 * u + 2 * q4), v1 = __shfl_sync(~0u, act, 8 * u + 2 * q4 + 1);
          ab[u] = __byte_perm(v0, v1, (gq & 1) ? 0x7632 : 0x5410);
        }
        if (FK_QUIET == 1) named_arrive<8, 256>();
        float c[4][4];
#pragma unroll
        for (int v = 0; v < 4; v++) { c[v][0] = c[v][1] = c[v][2] = c[v][3] = 0.f; }
#pragma unroll
        for (int q = 0; q < 4; q++) {
          const uint32_t mk = (gq >> 1) == q ? ~0u : 0u;
          const uint32_t b0 = ab[0] & mk, b1 = ab[1] & mk, b2 = ab[2] & mk, b3 = ab[3] & mk;
#pragma unroll
          for (int v = 0; v < 4; v++) { const int o = (4 * v + q) * 8; mma_16816(c[v], wd[o], wd[o + 1], wd[o + 2], wd[o + 3], b0, b1); }
#pragma unroll
          for (int v = 0; v < 4; v++) { const int o = (4 * v + q) * 8 + 4; mma_16816(c[v], wd[o], wd[o + 1], wd[o + 2], wd[o + 3], b2, b3); }
        }
#pragma unroll
        for (int u = 0; u < 2; u++)
          st_msg(dst + u * (16 * NMOE * 2), pack_bf16(c[2 * u][0], c[2 * u][1]), pack_bf16(c[2 * u][2], c[2 * u][3]),
                 pack_bf16(c[2 * u + 1][0], c[2 * u + 1][1]), pack_bf16(c[2 * u + 1][2], c[2 * u + 1][3]));
        if (FK_QUIET == 2) named_arrive<8, 256>();
        if (elect) TRACE(22);
      }
    }
  }
}

typedef CUresult (*PFN_encodeTiled)(CUtensorMap*, CUtensorMapDataType, cuuint32_t, void*, const cuuint64_t*, const cuuint64_t*,
                                    const cuuint32_t*, const cuuint32_t*, CUtensorMapInterleave, CUtensorMapSwizzle,
                                    CUtensorMapL2promotion, CUtensorMapFloatOOBfill);

static void map2d(PFN_encodeTiled enc, CUtensorMap* m, const void* p, uint64_t rows, uint64_t cols, uint32_t brows, uint32_t bcols, CUtensorMapSwizzle sw,
                  CUtensorMapL2promotion pr = CU_TENSOR_MAP_L2_PROMOTION_L2_128B) {
  cuuint64_t dims[2] = {cols, rows}; cuuint64_t str[1] = {cols * 2}; cuuint32_t box[2] = {bcols, brows}; cuuint32_t es[2] = {1, 1};
  enc(m, CU_TENSOR_MAP_DATA_TYPE_BFLOAT16, 2, (void*)p, dims, str, box, es, CU_TENSOR_MAP_INTERLEAVE_NONE, sw, pr,
      CU_TENSOR_MAP_FLOAT_OOB_FILL_NONE);
}
static void map3d(PFN_encodeTiled enc, CUtensorMap* m, const void* p, uint64_t rows, uint64_t cols, uint32_t brows, uint32_t bgroups) {
  cuuint64_t dims[3] = {64, rows, cols / 64}; cuuint64_t str[2] = {cols * 2, 128}; cuuint32_t box[3] = {64, brows, bgroups}; cuuint32_t es[3] = {1, 1, 1};
  enc(m, CU_TENSOR_MAP_DATA_TYPE_BFLOAT16, 3, (void*)p, dims, str, box, es, CU_TENSOR_MAP_INTERLEAVE_NONE, CU_TENSOR_MAP_SWIZZLE_128B,
      CU_TENSOR_MAP_L2_PROMOTION_L2_128B, CU_TENSOR_MAP_FLOAT_OOB_FILL_NONE);
}

}

extern "C" void kernel_launch(void* const* d_in, const int* in_sizes, int n_in, void* d_out, int out_size) {
  using namespace fk;
  (void)in_sizes; (void)n_in; (void)out_size;
  static PFN_encodeTiled enc = nullptr;
  static int maxClusters = -1;
  static void *pn = nullptr, *pP = nullptr, *pc = nullptr, *pm = nullptr, *pmod = nullptr;
  if (!enc) {
    void* fn = nullptr; cudaDriverEntryPointQueryResult qr;
    cudaGetDriverEntryPoint("cuTensorMapEncodeTiled", &fn, cudaEnableDefault, &qr);
    enc = (PFN_encodeTiled)fn;
    cudaGetSymbolAddress(&pn, g_n);
    cudaGetSymbolAddress(&pP, g_P);
    cudaGetSymbolAddress(&pc, g_cnt);
    cudaGetSymbolAddress(&pm, g_mail);
    cudaGetSymbolAddress(&pmod, g_mod);
    cudaFuncSetAttribute(fused_kernel, cudaFuncAttributeMaxDynamicSharedMemorySize, SMEM_BYTES);
  }
  Maps maps;
  map2d(enc, &maps.ws[0], d_in[1], S_, S_, 128, 64, CU_TENSOR_MAP_SWIZZLE_128B);
  map2d(enc, &maps.ws[1], d_in[2], S_, S_, 128, 64, CU_TENSOR_MAP_SWIZZLE_128B);
  map3d(enc, &maps.n, pn, S_, D_, 64, 4);
  map2d(enc, &maps.p, pP, 2 * S_, D_, 128, 64, CU_TENSOR_MAP_SWIZZLE_128B);
  map2d(enc, &maps.ps, pP, 2 * S_, D_, 64, 64, CU_TENSOR_MAP_SWIZZLE_128B);
  map2d(enc, &maps.wd[0], d_in[3], D_, D_, 256, 64, CU_TENSOR_MAP_SWIZZLE_128B);
  map2d(enc, &maps.wd[1], d_in[4], D_, D_, 256, 64, CU_TENSOR_MAP_SWIZZLE_128B);
  map2d(enc, &maps.x, d_in[0], S_, D_, 64, 64, CU_TENSOR_MAP_SWIZZLE_128B);
  map2d(enc, &maps.wg, d_in[7], D_, F_, 128, 32, CU_TENSOR_MAP_SWIZZLE_64B);
  map2d(enc, &maps.wu, d_in[8], D_, F_, 128, 32, CU_TENSOR_MAP_SWIZZLE_64B);
  map3d(enc, &maps.wdn, d_in[9], F_, D_, 32, 4);
  map2d(enc, &maps.wm, d_in[11], D_, 6 * D_, 64, 48, CU_TENSOR_MAP_SWIZZLE_NONE);

  cudaLaunchConfig_t cfg = {};
  cfg.gridDim = dim3(NCTA); cfg.blockDim = dim3(384); cfg.dynamicSmemBytes = SMEM_BYTES; cfg.stream = cudaStreamPerThread;
  cudaLaunchAttribute at[1];
  at[0].id = cudaLaunchAttributeClusterDimension; at[0].val.clusterDim.x = 2; at[0].val.clusterDim.y = 1; at[0].val.clusterDim.z = 1;
  cfg.attrs = at; cfg.numAttrs = 1;
  Ptrs pp{(const char*)d_in[0], (char*)pn, (unsigned*)pc, 0, 0, (Mail*)pm, (uint32_t*)pmod, (const char*)d_in[10], (const char*)d_in[1], (const char*)d_in[2],
          (const char*)d_in[3], (const char*)d_in[4], (const char*)d_in[6], (const char*)d_in[7], (const char*)d_in[8], (const char*)d_in[9], (const char*)d_in[11], (char*)pP, (char*)d_out, nullptr};
  if (maxClusters < 0) {
    cfg.gridDim = dim3(NCTA + NEXTRA);
    if (cudaOccupancyMaxActiveClusters(&maxClusters, fused_kernel, &cfg) != cudaSuccess) maxClusters = 0;
  }
  pp.b0 = -NEXTRA;
  if (maxClusters >= (NCTA + NEXTRA) / 2) {
    cfg.gridDim = dim3(NCTA + NEXTRA);
  } else {
    cfg.gridDim = dim3(NEXTRA);
    cudaLaunchKernelEx(&cfg, fused_kernel, pp, maps);
    cfg.gridDim = dim3(NCTA); pp.b0 = 0;
  }
  cudaLaunchKernelEx(&cfg, fused_kernel, pp, maps);
}
```

```cpp
#include <cuda_runtime.h>
#include <cuda_bf16.h>
#include <cuda.h>
#include <stdint.h>

#define DEVINL __device__ __forceinline__

namespace fk {

constexpr int S_ = 2048, D_ = 1024, F_ = 3584;
constexpr int NCTA = 128;
constexpr int NEXTRA = 4;
constexpr int NMOE = 112;
constexpr int SLOT = 16384;
constexpr int STAGE = 3 * SLOT;
constexpr int SPARE = 4 * STAGE;
constexpr int MISC = SPARE + 32768;
constexpr int SMEM_BYTES = MISC + 3072;
constexpr int BAR_OFF = MISC;
constexpr int CST_OFF = MISC + 480;
constexpr int SEL_OFF = MISC + 496;
constexpr int T1_OFF = MISC + 512;
constexpr int RS_OFF = T1_OFF + 2048;
constexpr int GA_OFF = T1_OFF;
constexpr int W_OFF = GA_OFF + 512;
constexpr int TOP_OFF = GA_OFF + 1792;
constexpr int XST_OFF = 3 * STAGE + SLOT;
constexpr int PART_REL = 0;
constexpr int SCR_REL = 4096;
constexpr int RST_REL = 6144;
enum { B_FULL = 0, B_EMPTY = 4, B_EMPTYH = 8, B_PRDY = 12  , B_PL = 16  , B_WM = 20  , B_LAND = 24  ,
       B_WB = 28  , B_DN = 32  , B_RECV = 36  , B_STAG = 40, B_T1 = 41, B_MODOK = 42, B_PEER = 43  , B_X = 45, B_T2 = 46,
       B_GU = 47, B_XDONE = 48, B_SEL = 49, B_XF = 50, B_OUT = 51, B_XR = 52  , B_NUM = 54 };

__host__ __device__ constexpr int bar_count(int i) {
  return (i >= B_EMPTY && i < B_EMPTYH) || (i >= B_PRDY && i < B_PL) || i == B_X || i == B_XDONE || i == B_XF || i == B_OUT ? 4
         : (i < B_EMPTY || i == B_T1 || i == B_GU || i == B_MODOK) ? 2 : 1;
}

#define FK_XDEPTH 2
#define FK_G0 6
#define FK_GA 1
#define FK_ROW1DLY 700
#define FK_ROW2DLY 450
#define FK_AEARLY 0
#define FK_ASTEP 200
#define FK_XDLY 2500
#define FK_ROW4DLY 1500
#define FK_WS0DLY 700
#define FK_WS1DLY 1600
#define FK_ADLY 1600
#define FK_L1 2
#define FK_L2 3
#define FK_PF0 20
#define FK_E1DLY 300
#define FK_E2DLY 300
#define FK_E4DLY 550
#define FK_MAP 3
#define FK_PPACE 720
#define FK_TG 28
#define FK_TU 31
#define FK_BSLEEP 350
#define FK_PFSKIP 0
#define FK_DNWIN 1
#define FK_OPACE 240
#define FK_WGATE -1
#define FK_RSLEEP 1000
#define FK_POLL0 2300
#define FK_ROW8DLY 4200
#define FK_GSTART 8500
#define FK_OPACE2 170
#define FK_E2GAP -1
#define FK_TABEARLY 1
#define FK_PUSHALL 0
#define FK_E3WEAK 1
#define FK_PK 8
#define FK_NQ 4
#define FK_NL 2
#define FK_W2 0
#define FK_XQ 0
#define FK_XS 1
#define FK_H1 0
#define FK_LF 1
#define FK_WB 1
#define FK_NOHINT 0
#define FK_QUIET 1
#define FK_OEXTRA 0
#define FK_ZB 32
#define FK_ZC0 0
#define FK_RS 1
#define FK_GX (FK_G0 + 4)
#define FK_PACE 1900
constexpr int SPIN_LIMIT = 1 << 22;
constexpr uint32_t SENT = 0xFFFFFFFFu;

struct Maps {
  CUtensorMap ws[2];
  CUtensorMap n;
  CUtensorMap p;
  CUtensorMap ps;
  CUtensorMap wd[2];
  CUtensorMap x;
  CUtensorMap wg, wu;
  CUtensorMap wdn;
  CUtensorMap wm;
};
template <int V> struct IntC { static constexpr int value = V; };
struct Mail;
struct Ptrs { const char* x; char* n; unsigned* cnt; int b0; uint32_t zero; Mail* mail; uint32_t* mod; const char *c, *ws_re, *ws_im, *wd_re, *wd_im, *wr, *wg, *wu, *wdn; char *P, *out; unsigned long long* trace; };

__device__ __align__(1024) __nv_bfloat16 g_n[S_ * D_];
__device__ __align__(1024) __nv_bfloat16 g_P[2 * S_ * D_];
__device__ __align__(128) uint32_t g_mod[3 * D_];
__device__ __align__(128) unsigned g_cnt[19 * 32];
struct Mail {
  uint4 stats[32 * 4 * 64];
  uint2 cand[32];
  uint4 rowh[64 * 128];
  uint4 rowx[64 * 128];
  uint4 part[128 * NMOE * 2];
  uint2 rs[2 * 16 * 128];
};
static_assert(FK_L2 == 3, "the receive layout assumes a stagger of three k-blocks");
__device__ __align__(1024) Mail g_mail;

#define SPIN_FAIL(what) __trap()
DEVINL uint32_t smem_u32(const void* p) { return (uint32_t)__cvta_generic_to_shared(p); }
DEVINL void mbar_init(uint32_t bar, uint32_t cnt) { asm volatile("mbarrier.init.shared::cta.b64 [%0], %1;" ::"r"(bar), "r"(cnt) : "memory"); }
DEVINL void mbar_expect_tx(uint32_t bar, uint32_t bytes) { asm volatile("mbarrier.arrive.expect_tx.shared::cta.b64 _, [%0], %1;" ::"r"(bar), "r"(bytes) : "memory"); }
DEVINL void mbar_arrive(uint32_t bar) { asm volatile("mbarrier.arrive.shared::cta.b64 _, [%0];" ::"r"(bar) : "memory"); }
DEVINL void mbar_arrive_cluster(uint32_t bar) { asm volatile("mbarrier.arrive.shared::cluster.b64 _, [%0];" ::"r"(bar) : "memory"); }
DEVINL uint32_t mapa(uint32_t a, uint32_t cta) { uint32_t r; asm("mapa.shared::cluster.u32 %0, %1, %2;" : "=r"(r) : "r"(a), "r"(cta)); return r; }
DEVINL bool mbar_test(uint32_t bar, uint32_t parity) {
  uint32_t ok;
  asm volatile("{\n.reg .pred p;\nmbarrier.test_wait.parity.shared::cta.b64 p, [%1], %2;\nselp.u32 %0, 1, 0, p;\n}" : "=r"(ok) : "r"(bar), "r"(parity) : "memory");
  return ok;
}
DEVINL void mbar_wait(uint32_t bar, uint32_t parity) {
  asm volatile("{\n.reg .pred p;\n.reg .u32 c;\nmov.u32 c, 0;\n"
               "LW:\nmbarrier.try_wait.parity.shared::cta.b64 p, [%0], %1;\n@p bra LD;\n"
               "add.u32 c, c, 1;\nsetp.lt.u32 p, c, 4194304;\n@p bra LW;\ntrap;\nLD:\n}" ::"r"(bar), "r"(parity) : "memory");
}
DEVINL void fence_async_smem() { asm volatile("fence.proxy.async.shared::cta;" ::: "memory"); }
DEVINL void fence_async_global() { asm volatile("fence.proxy.async.global;" ::: "memory"); }
DEVINL void fence_gpu() { asm volatile("fence.acq_rel.gpu;" ::: "memory"); }
template <int ID, int N> DEVINL void named_bar() { asm volatile("bar.sync %0, %1;" ::"n"(ID), "n"(N) : "memory"); }
template <int ID, int N> DEVINL void named_arrive() { asm volatile("bar.arrive %0, %1;" ::"n"(ID), "n"(N) : "memory"); }

DEVINL void tma_2d(uint32_t dst, const CUtensorMap* m, int x, int y, uint32_t bar) {
  asm volatile("cp.async.bulk.tensor.2d.shared::cluster.global.mbarrier::complete_tx::bytes [%0], [%1, {%3, %4}], [%2];"
               ::"r"(dst), "l"(m), "r"(bar), "r"(x), "r"(y) : "memory");
}
DEVINL void tma_2d_hint(uint32_t dst, const CUtensorMap* m, int x, int y, uint32_t bar, uint64_t pol) {
  asm volatile("cp.async.bulk.tensor.2d.shared::cluster.global.mbarrier::complete_tx::bytes.L2::cache_hint [%0], [%1, {%3, %4}], [%2], %5;"
               ::"r"(dst), "l"(m), "r"(bar), "r"(x), "r"(y), "l"(pol) : "memory");
}
DEVINL void tma_3d(uint32_t dst, const CUtensorMap* m, int x, int y, int z, uint32_t bar) {
  asm volatile("cp.async.bulk.tensor.3d.shared::cluster.global.mbarrier::complete_tx::bytes [%0], [%1, {%3, %4, %5}], [%2];"
               ::"r"(dst), "l"(m), "r"(bar), "r"(x), "r"(y), "r"(z) : "memory");
}
DEVINL void tma_store_2d(const CUtensorMap* m, uint32_t src, int x, int y) {
  asm volatile("cp.async.bulk.tensor.2d.global.shared::cta.bulk_group [%0, {%2, %3}], [%1];" ::"l"(m), "r"(src), "r"(x), "r"(y) : "memory");
}
DEVINL void bulk_load(uint32_t dst, const void* src, uint32_t bytes, uint32_t bar) {
  asm volatile("cp.async.bulk.shared::cluster.global.mbarrier::complete_tx::bytes [%0], [%1], %2, [%3];" ::"r"(dst), "l"(src), "r"(bytes), "r"(bar) : "memory");
}
DEVINL void bulk_store(void* dst, uint32_t src, uint32_t bytes) {
  asm volatile("cp.async.bulk.global.shared::cta.bulk_group [%0], [%1], %2;" ::"l"(dst), "r"(src), "r"(bytes) : "memory");
}
DEVINL void pf_bulk(const void* p, uint32_t bytes) { asm volatile("cp.async.bulk.prefetch.L2.global [%0], %1;" ::"l"(p), "r"(bytes) : "memory"); }
DEVINL void pf_bulk_hint(const void* p, uint32_t bytes, uint64_t pol) {
  asm volatile("cp.async.bulk.prefetch.L2.global.L2::cache_hint [%0], %1, %2;" ::"l"(p), "r"(bytes), "l"(pol) : "memory");
}
DEVINL void pf_2d(const CUtensorMap* m, int x, int y) {
  asm volatile("cp.async.bulk.prefetch.tensor.2d.L2.global [%0, {%1, %2}];" ::"l"(m), "r"(x), "r"(y) : "memory");
}
DEVINL void bulk_commit() { asm volatile("cp.async.bulk.commit_group;" ::: "memory"); }
template <int N> DEVINL void bulk_wait() { asm volatile("cp.async.bulk.wait_group %0;" ::"n"(N) : "memory"); }
template <int N> DEVINL void bulk_wait_read() { asm volatile("cp.async.bulk.wait_group.read %0;" ::"n"(N) : "memory"); }
DEVINL void prefetch_tmap(const CUtensorMap* m) { asm volatile("prefetch.tensormap [%0];" ::"l"(m) : "memory"); }

DEVINL void wg_fence() { asm volatile("wgmma.fence.sync.aligned;" ::: "memory"); }
DEVINL void wg_commit() { asm volatile("wgmma.commit_group.sync.aligned;" ::: "memory"); }
template <int N> DEVINL void wg_wait() { asm volatile("wgmma.wait_group.sync.aligned %0;" ::"n"(N) : "memory"); }

DEVINL uint64_t make_desc(uint32_t addr, uint32_t lbo, uint32_t sbo) {
  return (uint64_t)((addr & 0x3FFFF) >> 4) | ((uint64_t)(lbo >> 4) << 16) | ((uint64_t)(sbo >> 4) << 32) | ((uint64_t)1 << 62);
}

#define R8(a, o) "+f"(a[o]), "+f"(a[o + 1]), "+f"(a[o + 2]), "+f"(a[o + 3]), "+f"(a[o + 4]), "+f"(a[o + 5]), "+f"(a[o + 6]), "+f"(a[o + 7])
#define R128(a) R8(a, 0), R8(a, 8), R8(a, 16), R8(a, 24), R8(a, 32), R8(a, 40), R8(a, 48), R8(a, 56), \
                R8(a, 64), R8(a, 72), R8(a, 80), R8(a, 88), R8(a, 96), R8(a, 104), R8(a, 112), R8(a, 120)
template <int TB>
DEVINL void wgmma_n256(float (&d)[128], uint64_t da, uint64_t db, int scale_d) {
  asm volatile(
      "{\n.reg .pred p;\nsetp.ne.b32 p, %130, 0;\n"
      "wgmma.mma_async.sync.aligned.m64n256k16.f32.bf16.bf16 "
      "{%0, %1, %2, %3, %4, %5, %6, %7, %8, %9, %10, %11, %12, %13, %14, %15, "
      "%16, %17, %18, %19, %20, %21, %22, %23, %24, %25, %26, %27, %28, %29, %30, %31, "
      "%32, %33, %34, %35, %36, %37, %38, %39, %40, %41, %42, %43, %44, %45, %46, %47, "
      "%48, %49, %50, %51, %52, %53, %54, %55, %56, %57, %58, %59, %60, %61, %62, %63, "
      "%64, %65, %66, %67, %68, %69, %70, %71, %72, %73, %74, %75, %76, %77, %78, %79, "
      "%80, %81, %82, %83, %84, %85, %86, %87, %88, %89, %90, %91, %92, %93, %94, %95, "
      "%96, %97, %98, %99, %100, %101, %102, %103, %104, %105, %106, %107, %108, %109, %110, %111, "
      "%112, %113, %114, %115, %116, %117, %118, %119, %120, %121, %122, %123, %124, %125, %126, %127}, "
      "%128, %129, p, 1, 1, 0, %131;\n}\n"
      : R128(d)
      : "l"(da), "l"(db), "r"(scale_d), "n"(TB));
}
DEVINL void reg_fence128(float (&a)[128]) {
#pragma unroll
  for (int i = 0; i < 128; i++) asm volatile("" : "+f"(a[i])::"memory");
}

DEVINL uint32_t pack_bf16(float lo, float hi) {
  uint32_t r;
  asm("cvt.rn.bf16x2.f32 %0, %1, %2;" : "=r"(r) : "f"(hi), "f"(lo));
  return r;
}
DEVINL uint32_t fma_bf2(uint32_t a, uint32_t b, uint32_t c) { uint32_t r; asm("fma.rn.bf16x2 %0, %1, %2, %3;" : "=r"(r) : "r"(a), "r"(b), "r"(c)); return r; }
DEVINL uint32_t mul_bf2(uint32_t a, uint32_t b) { uint32_t r; asm("mul.rn.bf16x2 %0, %1, %2;" : "=r"(r) : "r"(a), "r"(b)); return r; }
DEVINL uint32_t add_bf2(uint32_t a, uint32_t b) { uint32_t r; asm("add.rn.bf16x2 %0, %1, %2;" : "=r"(r) : "r"(a), "r"(b)); return r; }
DEVINL uint32_t add1_bf2(uint32_t a) { return fma_bf2(a, 0x3F803F80u, 0x3F803F80u); }
DEVINL float bf_lo(uint32_t w) { return __uint_as_float(w << 16); }
DEVINL float bf_hi(uint32_t w) { return __uint_as_float(w & 0xFFFF0000u); }
DEVINL float round_bf16(float v) { return bf_lo(pack_bf16(v, v)); }
DEVINL float sigmoid_f(float v) {
  float e, r;
  asm("ex2.approx.ftz.f32 %0, %1;" : "=f"(e) : "f"(v * -1.4426950408889634f));
  asm("rcp.approx.ftz.f32 %0, %1;" : "=f"(r) : "f"(1.f + e));
  return r;
}
DEVINL float rsqrt_f(float v) { float r; asm("rsqrt.approx.ftz.f32 %0, %1;" : "=f"(r) : "f"(v)); return r; }
DEVINL float silu_f(float v) { return v * sigmoid_f(v); }
DEVINL void stsm_x4(uint32_t addr, uint32_t r0, uint32_t r1, uint32_t r2, uint32_t r3) {
  asm volatile("stmatrix.sync.aligned.m8n8.x4.shared.b16 [%0], {%1, %2, %3, %4};" ::"r"(addr), "r"(r0), "r"(r1), "r"(r2), "r"(r3) : "memory");
}
DEVINL void ldsm_x4(uint32_t addr, uint32_t& r0, uint32_t& r1, uint32_t& r2, uint32_t& r3) {
  asm volatile("ldmatrix.sync.aligned.m8n8.x4.shared.b16 {%0, %1, %2, %3}, [%4];" : "=r"(r0), "=r"(r1), "=r"(r2), "=r"(r3) : "r"(addr) : "memory");
}
DEVINL void ldsm_x4_t(uint32_t addr, uint32_t& r0, uint32_t& r1, uint32_t& r2, uint32_t& r3) {
  asm volatile("ldmatrix.sync.aligned.m8n8.x4.trans.shared.b16 {%0, %1, %2, %3}, [%4];" : "=r"(r0), "=r"(r1), "=r"(r2), "=r"(r3) : "r"(addr) : "memory");
}
DEVINL void mma_16816(float (&c)[4], uint32_t a0, uint32_t a1, uint32_t a2, uint32_t a3, uint32_t b0, uint32_t b1) {
  asm("mma.sync.aligned.m16n8k16.row.col.f32.bf16.bf16.f32 {%0, %1, %2, %3}, {%4, %5, %6, %7}, {%8, %9}, {%0, %1, %2, %3};"
      : "+f"(c[0]), "+f"(c[1]), "+f"(c[2]), "+f"(c[3]) : "r"(a0), "r"(a1), "r"(a2), "r"(a3), "r"(b0), "r"(b1));
}
DEVINL void mma_1688(float (&c)[4], uint32_t a0, uint32_t a1, uint32_t b0) {
  asm("mma.sync.aligned.m16n8k8.row.col.f32.bf16.bf16.f32 {%0, %1, %2, %3}, {%4, %5}, {%6}, {%0, %1, %2, %3};"
      : "+f"(c[0]), "+f"(c[1]), "+f"(c[2]), "+f"(c[3]) : "r"(a0), "r"(a1), "r"(b0));
}
DEVINL float4 lds128(uint32_t a) { float4 v; asm volatile("ld.shared.v4.f32 {%0, %1, %2, %3}, [%4];" : "=f"(v.x), "=f"(v.y), "=f"(v.z), "=f"(v.w) : "r"(a)); return v; }
DEVINL uint4 lds128u(uint32_t a) { uint4 v; asm volatile("ld.shared.v4.u32 {%0, %1, %2, %3}, [%4];" : "=r"(v.x), "=r"(v.y), "=r"(v.z), "=r"(v.w) : "r"(a)); return v; }
DEVINL float2 lds64(uint32_t a) { float2 v; asm volatile("ld.shared.v2.f32 {%0, %1}, [%2];" : "=f"(v.x), "=f"(v.y) : "r"(a)); return v; }
DEVINL uint2 lds64u(uint32_t a) { uint2 v; asm volatile("ld.shared.v2.u32 {%0, %1}, [%2];" : "=r"(v.x), "=r"(v.y) : "r"(a)); return v; }
DEVINL float lds32(uint32_t a) { float v; asm volatile("ld.shared.f32 %0, [%1];" : "=f"(v) : "r"(a)); return v; }
DEVINL float lds16f(uint32_t a) { uint32_t v; asm volatile("ld.shared.u16 %0, [%1];" : "=r"(v) : "r"(a)); return __uint_as_float(v << 16); }
DEVINL uint32_t lds32u(uint32_t a) { uint32_t v; asm volatile("ld.shared.u32 %0, [%1];" : "=r"(v) : "r"(a)); return v; }
DEVINL void sts128(uint32_t a, float x, float y, float z, float w) { asm volatile("st.shared.v4.f32 [%0], {%1, %2, %3, %4};" ::"r"(a), "f"(x), "f"(y), "f"(z), "f"(w) : "memory"); }
DEVINL void sts128u(uint32_t a, uint32_t x, uint32_t y, uint32_t z, uint32_t w) { asm volatile("st.shared.v4.u32 [%0], {%1, %2, %3, %4};" ::"r"(a), "r"(x), "r"(y), "r"(z), "r"(w) : "memory"); }
DEVINL void sts64(uint32_t a, float x, float y) { asm volatile("st.shared.v2.f32 [%0], {%1, %2};" ::"r"(a), "f"(x), "f"(y) : "memory"); }
DEVINL void sts64u(uint32_t a, uint32_t x, uint32_t y) { asm volatile("st.shared.v2.u32 [%0], {%1, %2};" ::"r"(a), "r"(x), "r"(y) : "memory"); }
DEVINL void sts32(uint32_t a, float v) { asm volatile("st.shared.f32 [%0], %1;" ::"r"(a), "f"(v) : "memory"); }
DEVINL void sts32u(uint32_t a, uint32_t v) { asm volatile("st.shared.u32 [%0], %1;" ::"r"(a), "r"(v) : "memory"); }

DEVINL uint4 ld_msg(const uint4* p) {
  unsigned long long a, b;
  asm volatile("{\n.reg .b128 r;\nld.relaxed.gpu.global.b128 r, [%2];\nmov.b128 {%0, %1}, r;\n}" : "=l"(a), "=l"(b) : "l"(p) : "memory");
  return make_uint4((uint32_t)a, (uint32_t)(a >> 32), (uint32_t)b, (uint32_t)(b >> 32));
}
DEVINL void st_msg(uint4* p, uint32_t x, uint32_t y, uint32_t z, uint32_t w) {
  unsigned long long a = (unsigned long long)x | ((unsigned long long)y << 32), b = (unsigned long long)z | ((unsigned long long)w << 32);
  asm volatile("{\n.reg .b128 r;\nmov.b128 r, {%1, %2};\nst.relaxed.gpu.global.b128 [%0], r;\n}" ::"l"(p), "l"(a), "l"(b) : "memory");
}
DEVINL uint2 ld_msg8(const void* p) {
  unsigned long long a;
  asm volatile("ld.relaxed.gpu.global.b64 %0, [%1];" : "=l"(a) : "l"(p) : "memory");
  return make_uint2((uint32_t)a, (uint32_t)(a >> 32));
}
DEVINL void st_msg8(uint2* p, uint32_t x, uint32_t y) {
  asm volatile("st.relaxed.gpu.global.b64 [%0], %1;" ::"l"(p), "l"((unsigned long long)x | ((unsigned long long)y << 32)) : "memory");
}
DEVINL unsigned ld_rlx(const void* p) { unsigned v; asm volatile("ld.relaxed.gpu.global.u32 %0, [%1];" : "=r"(v) : "l"(p) : "memory"); return v; }
DEVINL void st_rlx(unsigned* p, unsigned v) { asm volatile("st.relaxed.gpu.global.u32 [%0], %1;" ::"l"(p), "r"(v) : "memory"); }
DEVINL void red_add(unsigned* p, unsigned v) { asm volatile("red.relaxed.gpu.global.add.u32 [%0], %1;" ::"l"(p), "r"(v) : "memory"); }
DEVINL void red_max8(uint2* p, uint32_t lo, uint32_t hi) {
  asm volatile("red.relaxed.gpu.global.max.u64 [%0], %1;" ::"l"(p), "l"((unsigned long long)lo | ((unsigned long long)hi << 32)) : "memory");
}
DEVINL void red_add_release(unsigned* p, unsigned v) { asm volatile("red.release.gpu.global.add.u32 [%0], %1;" ::"l"(p), "r"(v) : "memory"); }
DEVINL uint4 ldg_nc(const void* p) {
  uint4 v;
  asm volatile("ld.global.nc.L1::no_allocate.v4.u32 {%0, %1, %2, %3}, [%4];" : "=r"(v.x), "=r"(v.y), "=r"(v.z), "=r"(v.w) : "l"(p));
  return v;
}
DEVINL uint4 ldg128(const void* p) {
  uint4 v;
  asm volatile("ld.global.v4.u32 {%0, %1, %2, %3}, [%4];" : "=r"(v.x), "=r"(v.y), "=r"(v.z), "=r"(v.w) : "l"(p) : "memory");
  return v;
}
DEVINL void stg128(void* p, uint4 v) { asm volatile("st.global.v4.u32 [%0], {%1, %2, %3, %4};" ::"l"(p), "r"(v.x), "r"(v.y), "r"(v.z), "r"(v.w) : "memory"); }
DEVINL uint32_t landed(uint32_t readback, uint32_t zero) { return __reduce_or_sync(~0u, readback & zero); }
DEVINL uint32_t nonzero(uint32_t w) { return w ? w : 0x8000u; }
DEVINL uint32_t clk() { uint32_t c; asm volatile("mov.u32 %0, %%clock;" : "=r"(c)); return c; }
DEVINL void delay_until(uint32_t c0, uint32_t cycles) { while (clk() - c0 < cycles) {} }

#define TRACE(id)
#define TRACE_CLK(id)
#define FK_TTMASK 0x1111C1110101ull

DEVINL const char* piece_addr(const Ptrs& pp, int b, int i) {
  if (i >= 20) return pp.wdn + (size_t)b * 57344 + (i - 20) * 8192;
  if ((i >> 2) == 2) return (b < 64 ? pp.wd_re : pp.wd_im) + (size_t)(b & 63) * 32768 + (i & 3) * 8192;
  return (i < 4 || (i >> 2) == 3 ? pp.wg : pp.wu) + (size_t)((i < 8 ? ((i & 3) ^ 2) * 128 : 512 + (i & 3) * 128) + b) * (2 * F_);
}

DEVINL uint32_t dn_box(int i) { return i == 0 ? STAGE + 2 * SLOT : i == 3 ? SPARE : 2 * STAGE + i * SLOT; }
DEVINL int sibling(int m4, int r) {
  return r < 2 ? m4 ^ r : ((m4 & 2) ^ 2) + r - 2;
}

DEVINL uint32_t fkey(float v, int row) {
  const uint32_t u = __float_as_uint(v);
  return (((u & 0x80000000u) ? ~u : (u | 0x80000000u)) & ~2047u) | (uint32_t)(2047 - row);
}
DEVINL int key_row(uint32_t k) { return 2047 - (int)(k & 2047u); }
DEVINL float key_val(uint32_t k) { k = (k & ~2047u) | 1024u; return __uint_as_float((k & 0x80000000u) ? (k & 0x7FFFFFFFu) : ~k); }
DEVINL uint32_t redux_max(uint32_t v) { uint32_t r; asm volatile("redux.sync.max.u32 %0, %1, 0xffffffff;" : "=r"(r) : "r"(v)); return r; }
DEVINL void warp_top2(uint32_t ka, uint32_t kb, uint32_t& k1, uint32_t& k2) {
  k1 = redux_max(ka);
  k2 = redux_max(ka == k1 ? kb : ka);
}
DEVINL int sel_slot(uint2 sel, int n) {
  const int bA = key_row(sel.x) >> 6, bB = key_row(sel.y) >> 6;
  return n ? bB * 2 + (bA == bB ? 1 : 0) : bA * 2;
}

DEVINL void ln_stats(const uint4 (&w)[4], float (&v)[32], float& rstd, float& nmr) {
#pragma unroll
  for (int i = 0; i < 4; i++) {
    v[8 * i + 0] = bf_lo(w[i].x); v[8 * i + 1] = bf_hi(w[i].x); v[8 * i + 2] = bf_lo(w[i].y); v[8 * i + 3] = bf_hi(w[i].y);
    v[8 * i + 4] = bf_lo(w[i].z); v[8 * i + 5] = bf_hi(w[i].z); v[8 * i + 6] = bf_lo(w[i].w); v[8 * i + 7] = bf_hi(w[i].w);
  }
  float s[4] = {0.f, 0.f, 0.f, 0.f}, q[4] = {0.f, 0.f, 0.f, 0.f};
#pragma unroll
  for (int i = 0; i < 32; i++) { s[i & 3] += v[i]; q[i & 3] = fmaf(v[i], v[i], q[i & 3]); }
  rstd = (s[0] + s[1]) + (s[2] + s[3]); nmr = (q[0] + q[1]) + (q[2] + q[3]);
}
DEVINL void ln_apply(uint4 (&w)[4], const float (&v)[32], float sum, float sq) {
#pragma unroll
  for (int o = 16; o; o >>= 1) { sum += __shfl_xor_sync(~0u, sum, o); sq += __shfl_xor_sync(~0u, sq, o); }
  const float mean = sum * (1.f / D_);
  const float rstd = rsqrt_f(fmaxf(fmaf(-mean, mean, sq * (1.f / D_)), 0.f) + 1e-5f), nmr = -mean * rstd;
#pragma unroll
  for (int i = 0; i < 4; i++) {
    w[i].x = pack_bf16(fmaf(v[8 * i], rstd, nmr), fmaf(v[8 * i + 1], rstd, nmr)); w[i].y = pack_bf16(fmaf(v[8 * i + 2], rstd, nmr), fmaf(v[8 * i + 3], rstd, nmr));
    w[i].z = pack_bf16(fmaf(v[8 * i + 4], rstd, nmr), fmaf(v[8 * i + 5], rstd, nmr)); w[i].w = pack_bf16(fmaf(v[8 * i + 6], rstd, nmr), fmaf(v[8 * i + 7], rstd, nmr));
  }
}
DEVINL void ln_row(uint4 (&w)[4]) { float v[32], s, q; ln_stats(w, v, s, q); ln_apply(w, v, s, q); }
DEVINL float sum8(uint4 u) { return ((bf_lo(u.x) + bf_hi(u.x)) + (bf_lo(u.y) + bf_hi(u.y))) + ((bf_lo(u.z) + bf_hi(u.z)) + (bf_lo(u.w) + bf_hi(u.w))); }

template <int R> DEVINL void take_box(uint32_t (&wf)[128], uint32_t box, int lane) {
  const int kr = (lane & 7) + (lane >> 4) * 8;
  const uint32_t base = box + kr * 64, sw = (uint32_t)((kr >> 1) & 3), hb = (uint32_t)((lane >> 3) & 1);
#pragma unroll
  for (int mt = 0; mt < 2; mt++) {
    const uint32_t ad = base + (((mt * 2 + hb) ^ sw) << 4);
#pragma unroll
    for (int ks = 0; ks < 8; ks++) {
      const int o = (ks * 4 + R * 2 + mt) * 4;
      ldsm_x4_t(ad + ks * 1024, wf[o], wf[o + 1], wf[o + 2], wf[o + 3]);
    }
  }
}
DEVINL void gate_up(const Ptrs& pp, uint32_t (&wf)[128], uint32_t sb, uint32_t scr, int ksl, int lane) {
  const uint2 sel = lds64u(sb + SEL_OFF);
  const int gq = lane >> 2, q4 = lane & 3;
  const uint4* src = &pp.mail->rowh[sel_slot(sel, gq & 1) * 128 + ksl * 16 + q4];
  uint4 bf[4];
  int it = 0;
#pragma unroll
  for (int u = 0; u < 4; u++) bf[u] = FK_E3WEAK ? ldg128(src + u * 4) : ld_msg(src + u * 4);
  while (!__all_sync(~0u, bf[0].x != SENT && bf[1].x != SENT && bf[2].x != SENT && bf[3].x != SENT)) {
#pragma unroll
    for (int u = 0; u < 4; u++) bf[u] = ld_msg(src + u * 4);
    if (++it > SPIN_LIMIT) SPIN_FAIL(0x207);
  }
  if (lane == 0 && ksl == 4) TRACE(20);
  float acc[8][4];
#pragma unroll
  for (int i = 0; i < 8; i++) { acc[i][0] = acc[i][1] = acc[i][2] = acc[i][3] = 0.f; }
#pragma unroll
  for (int u = 0; u < 4; u++)
#pragma unroll
    for (int mt = 0; mt < 4; mt++) {
      const int o = (2 * u * 4 + mt) * 4;
      mma_16816(acc[mt], wf[o], wf[o + 1], wf[o + 2], wf[o + 3], bf[u].x, bf[u].y);
      mma_16816(acc[4 + mt], wf[o + 16], wf[o + 17], wf[o + 18], wf[o + 19], bf[u].z, bf[u].w);
    }
  {
    const bool h = q4 & 1, m = q4 & 2;
    float v[4][2];
#pragma unroll
    for (int mt = 0; mt < 4; mt++) {
      v[mt][0] = h ? acc[mt][2] + acc[4 + mt][2] : acc[mt][0] + acc[4 + mt][0];
      v[mt][1] = h ? acc[mt][3] + acc[4 + mt][3] : acc[mt][1] + acc[4 + mt][1];
    }
    sts128(scr + PART_REL + ksl * 512 + (q4 * 8 + gq) * 16, m ? v[1][0] : v[0][0], m ? v[1][1] : v[0][1], m ? v[3][0] : v[2][0], m ? v[3][1] : v[2][1]);
  }
  named_arrive<4, 384>();
}

struct OutTab { uint32_t A[4], S[4], G[4]; };
DEVINL void out_tab(OutTab& tb, uint4 cb, uint4 sv, uint4 gb) {
  tb.A[0] = add1_bf2(cb.x); tb.A[1] = add1_bf2(cb.y); tb.A[2] = add1_bf2(cb.z); tb.A[3] = add1_bf2(cb.w);
  tb.S[0] = sv.x; tb.S[1] = sv.y; tb.S[2] = sv.z; tb.S[3] = sv.w;
  tb.G[0] = gb.x; tb.G[1] = gb.y; tb.G[2] = gb.z; tb.G[3] = gb.w;
}
DEVINL void out_rows(const OutTab& tb, uint32_t sb, uint32_t scr, int r, uint32_t mask, int lane, char* dst) {
  const float4 st = lds128(scr + RST_REL + r * 8);
  uint4 v[2];
#pragma unroll
  for (int k = 0; k < 2; k++) v[k] = lds128u(sb + XST_OFF + (r + k) * 512 + ((lane ^ ((r + k) & 7)) << 4));
#pragma unroll
  for (int k = 0; k < 2; k++) {
    const float rs = k ? st.z : st.x, nm = k ? st.w : st.y;
    const uint32_t x4[4] = {v[k].x, v[k].y, v[k].z, v[k].w};
    uint32_t o[4];
#pragma unroll
    for (int u = 0; u < 4; u++)
      o[u] = fma_bf2(tb.G[u], fma_bf2(pack_bf16(fmaf(bf_lo(x4[u]), rs, nm), fmaf(bf_hi(x4[u]), rs, nm)), tb.A[u], tb.S[u]), x4[u]);
    if ((mask >> k) & 1) stg128(dst + (size_t)(r + k) * (2 * D_), make_uint4(o[0], o[1], o[2], o[3]));
  }
}
DEVINL int out_group(const OutTab& tb, uint32_t sb, uint32_t scr, int r0, uint32_t mask, int lane, char* dst, uint32_t pace, uint32_t stop) {
  int r = 0;
#pragma unroll 1
  for (; mask; r += 2, mask >>= 2) {
    if (!(mask & 3)) continue;
    const bool last = stop && mbar_test(stop, 0);
    if (last && !FK_OEXTRA) return r;
    const uint32_t cn = clk();
    out_rows(tb, sb, scr, r0 + r, mask, lane, dst);
    if (last) return r + 2;
    if (mask >> 2) delay_until(cn, pace);
  }
  return 16;
}
DEVINL uint32_t row_bit(uint32_t key, int g0) { const unsigned r = (unsigned)(key_row(key) - g0); return r < 16 ? 1u << r : 0u; }

template <int TB, int G0, int G1>
DEVINL void gemm_phase(const Ptrs& pp, float (&acc)[128], uint32_t sb, int cw, bool lag, bool elect, uint32_t rel) {
  const uint32_t bars = sb + BAR_OFF;
#pragma unroll 1
  for (int g = G0; g < G1; g++) {
    const int s = g & 3;
    mbar_wait(bars + (B_FULL + s) * 8, (g >> 2) & 1);
    const bool hold = lag && g == G1 - (TB ? FK_L1 : FK_L2) && !(TB && FK_H1);
    if (hold) {
      wg_wait<0>();
      if (rel) mbar_arrive_cluster(rel + ((g - 1) & 3) * 8);
      mbar_wait(bars + B_STAG * 8, TB ? 0 : 1);
    }
    const uint32_t sa = sb + s * STAGE;
    const uint64_t da = make_desc(sa + cw * 8192, 16, 1024), db = make_desc(sa + SLOT, TB ? 8192 : 16, 1024);
    constexpr int KB = TB ? 128 : 2;
    wg_fence();
    wgmma_n256<TB>(acc, da, db, g > G0);
    wgmma_n256<TB>(acc, da + 2, db + KB, 1);
    wg_commit();
    wg_wait<1>();
    if (rel && g > G0 && !hold) mbar_arrive_cluster(rel + ((g - 1) & 3) * 8);
    if (!TB && g == G1 - 1 && !lag && elect) mbar_arrive_cluster(mapa(bars + B_PEER * 8, cw));
    if (TB && FK_H1 && lag && g == G1 - FK_L1 - 1) mbar_wait(bars + B_STAG * 8, 0);
    wg_fence();
    wgmma_n256<TB>(acc, da + 4, db + 2 * KB, 1);
    wgmma_n256<TB>(acc, da + 6, db + 3 * KB, 1);
    wg_commit();
  }
  if (!lag) {
    wg_wait<1>();
    if (elect) mbar_arrive(bars + B_STAG * 8);
  }
}
DEVINL void gemm_finish(float (&acc)[128], uint32_t rel) {
  wg_wait<0>();
  reg_fence128(acc);
  if (rel) mbar_arrive_cluster(rel + 24);
}

__global__ void __launch_bounds__(384, 1)
fused_kernel(const Ptrs pp, const __grid_constant__ Maps maps) {
  extern __shared__ __align__(1024) uint8_t smem_raw[];
  const uint32_t c0 = clk();
  if (threadIdx.x == 0 && blockIdx.x >= NEXTRA) TRACE(0);
  const uint32_t sb = smem_u32(smem_raw);
  const int tid = threadIdx.x, lane = tid & 31;
  const int warp = __shfl_sync(~0u, tid >> 5, 0);
  const int rb = (int)blockIdx.x + pp.b0;
  const uint32_t bars = sb + BAR_OFF;
  auto BAR = [&](int i) { return bars + i * 8; };

  if (rb < 0) {
    const uint32_t ring = sb + warp * 16384, rbar = sb + MISC + warp * 64;
    const int row0 = FK_GX * 128 + ((rb + NEXTRA) * 12 + warp) * 2;
    if (lane == 0) {
#pragma unroll 1
      for (int i = 0; i < 4; i++) mbar_init(rbar + i * 8, 1);
      asm volatile("fence.mbarrier_init.release.cluster;" ::: "memory");
      delay_until(c0, FK_XDLY);
#pragma unroll 1
      for (int i = 0; i < FK_XDEPTH; i++) { mbar_expect_tx(rbar + i * 8, 4096); bulk_load(ring + i * 4096, pp.x + (size_t)(row0 + 96 * i) * (2 * D_), 4096, rbar + i * 8); }
    }
    __syncwarp();
    int row = row0;
#pragma unroll 1
    for (int it = 0; row < S_; it++, row += 96) {
      const uint32_t st = ring + (it & 3) * 4096;
      mbar_wait(rbar + (it & 3) * 8, (it >> 2) & 1);
      uint4 w[4], w2[4];
#pragma unroll
      for (int i = 0; i < 4; i++) { w[i] = lds128u(st + lane * 16 + i * 512); w2[i] = lds128u(st + 2048 + lane * 16 + i * 512); }
      ln_row(w);
      uint32_t rbk = 0;
      if (it) {
        if (lane == 0) bulk_wait<0>();
        __syncwarp();
        rbk = ld_rlx(pp.n + (size_t)(row - 96) * (2 * D_) + lane * 128);
      }
      ln_row(w2);
#pragma unroll
      for (int i = 0; i < 4; i++) { sts128u(st + lane * 16 + i * 512, w[i].x, w[i].y, w[i].z, w[i].w); sts128u(st + 2048 + lane * 16 + i * 512, w2[i].x, w2[i].y, w2[i].z, w2[i].w); }
      fence_async_smem();
      const uint32_t z = landed(rbk, pp.zero);
      if (lane == 0) {
        if (it) red_add(&pp.cnt[((row - 96) >> 7) * 32], 2 + z);
        bulk_store(pp.n + (size_t)row * (2 * D_), st, 4096); bulk_commit();
        if (row + 96 * FK_XDEPTH < S_) {
          const int sn = (it + FK_XDEPTH) & 3;
          mbar_expect_tx(rbar + sn * 8, 4096); bulk_load(ring + sn * 4096, pp.x + (size_t)(row + 96 * FK_XDEPTH) * (2 * D_), 4096, rbar + sn * 8);
        }
      }
      __syncwarp();
    }
    if (lane == 0) bulk_wait<0>();
    __syncwarp();
    const uint32_t z = landed(ld_rlx(pp.n + (size_t)(row - 96) * (2 * D_) + lane * 128), pp.zero);
    if (lane == 0) red_add(&pp.cnt[((row - 96) >> 7) * 32], 2 + z);
    return;
  }
  if (warp >= 4) {
    const int g = warp >> 3;
    const size_t ro = (size_t)(g * 128 + rb) * (2 * D_) + (tid & 127) * 16;
    if (g) delay_until(c0, FK_ROW1DLY);
    const uint4 w = ldg_nc(pp.x + ro);
    asm volatile("barrier.cluster.arrive.relaxed.aligned;" ::: "memory");
    const int g2 = g ? 2 + FK_GA + (warp & 3) : 2 + 3 - (warp & 3);
    const bool has2 = g2 < (g ? FK_G0 : 2 + FK_GA);
    const size_t ro2 = (size_t)(g2 * 128 + rb) * (2 * D_);
    uint4 w2[4];
    if (has2) {
      delay_until(c0, g ? FK_ROW4DLY : FK_ROW2DLY);
#pragma unroll
      for (int i = 0; i < 4; i++) w2[i] = ldg_nc(pp.x + ro2 + lane * 16 + i * 512);
    }
    if (!(tid & 127)) { red_add(&pp.cnt[g * 32], 1 + (w.x & pp.zero)); if (!g) TRACE(1); }
    const float v[8] = {bf_lo(w.x), bf_hi(w.x), bf_lo(w.y), bf_hi(w.y), bf_lo(w.z), bf_hi(w.z), bf_lo(w.w), bf_hi(w.w)};
    const float sum = ((v[0] + v[1]) + (v[2] + v[3])) + ((v[4] + v[5]) + (v[6] + v[7]));
    const float sq = (fmaf(v[0], v[0], v[1] * v[1]) + fmaf(v[2], v[2], v[3] * v[3])) + (fmaf(v[4], v[4], v[5] * v[5]) + fmaf(v[6], v[6], v[7] * v[7]));
    float r = (lane < 16 ? sum : sq) + __shfl_xor_sync(~0u, lane < 16 ? sq : sum, 16);
#pragma unroll
    for (int o = 8; o; o >>= 1) r += __shfl_xor_sync(~0u, r, o);
    const uint32_t ad = sb + T1_OFF + g * 32;
    if (!(lane & 15)) sts32(ad + lane + (warp & 3) * 4, r);
    asm volatile("bar.sync %0, 128;" ::"r"(10 + g) : "memory");
    const float4 s4 = lds128(ad), q4 = lds128(ad + 16);
    const float mean = ((s4.x + s4.y) + (s4.z + s4.w)) * (1.f / D_);
    const float rstd = rsqrt_f(fmaxf(fmaf(-mean, mean, ((q4.x + q4.y) + (q4.z + q4.w)) * (1.f / D_)), 0.f) + 1e-5f), nm = -mean * rstd;
    stg128(pp.n + ro, make_uint4(nonzero(pack_bf16(fmaf(v[0], rstd, nm), fmaf(v[1], rstd, nm))), pack_bf16(fmaf(v[2], rstd, nm), fmaf(v[3], rstd, nm)),
                                 pack_bf16(fmaf(v[4], rstd, nm), fmaf(v[5], rstd, nm)), pack_bf16(fmaf(v[6], rstd, nm), fmaf(v[7], rstd, nm))));
    if (tid == 128) TRACE(31);
    if (has2) {
      ln_row(w2);
#pragma unroll
      for (int i = 0; i < 4; i++) stg128(pp.n + ro2 + lane * 16 + i * 512, w2[i]);
      if (g) named_arrive<9, 32 * (FK_G0 - FK_GA - 1)>();
      else {
        const uint32_t z = landed(ld_rlx(pp.n + ro2 + (lane & 15) * 128), pp.zero);
        if (lane == 0) red_add(&pp.cnt[g2 * 32], 1 + z);
      }
      if (tid == 224) TRACE(61);
      if (tid == 256) TRACE(55);
    }
  }
  int m4, t;
  {
    const int c = (rb >> 1) - 2;
    int g = 8, i = c + 2;
    if (c >= 32) { i = ((c - 32) * 37) >> 8; g = c - 32 - 7 * i; g += g >= 2; i += 4; }
    else if (c >= 0) { g = c & 7; i = c >> 3; }
    if (g == 8) { g = 2; i += 6; } else if (i == 8) { i = 4 + g; g = 2; }
    m4 = (g >> 2) * 2 + (i & 1); t = (g & 3) * 4 + (i >> 1);
  }
  const int j = rb & 1, b = t * 8 + m4 * 2 + j;
  const int blk = t * 2 + j;
  const uint32_t scr = sb + 2 * STAGE + j * 8192;
  if (warp < 4) {
    uint32_t tag = ld_rlx(&pp.cnt[17 * 32]);
    auto ws_touch = [&](int o) {
      uint32_t v;
      asm volatile("ld.global.nc.L1::no_allocate.L2::128B.u32 %0, [%1];" : "=r"(v)
                   : "l"((j ? pp.ws_im : pp.ws_re) + (size_t)(t * 128 + m4 * 32 + lane) * (2 * S_) + o));
      return v;
    };
    uint32_t early = 0;
    if (warp == 1) { delay_until(c0, FK_WS0DLY); early = ws_touch(0); if (lane == 0) TRACE(126); }
    if (warp == 0) early = ld_rlx(&pp.cnt[(lane & 1) * 32]);
    if (lane == 0) {
      if (warp < 2) {
        if (warp == 0) {
          prefetch_tmap(&maps.ws[j]); prefetch_tmap(&maps.n);
          if (sb & 1023) __trap();
#pragma unroll
          for (int i = 0; i < 8; i++) mbar_init(BAR(i), bar_count(i));
        } else {
#pragma unroll
          for (int i = 8; i < 22; i++) mbar_init(BAR(i), bar_count(i));
        }
      } else if (warp == 2) {
#pragma unroll
        for (int i = 22; i < 36; i++) mbar_init(BAR(i), bar_count(i));
      } else {
#pragma unroll
        for (int i = 36; i < B_NUM; i++) mbar_init(BAR(i), bar_count(i));
#pragma unroll
        for (int i = 0; i < 4; i++) mbar_expect_tx(BAR(B_RECV + i), 8192);
      }
      asm volatile("fence.mbarrier_init.release.cluster;" ::: "memory");
    }
    named_bar<6, 128>();
    named_arrive<0, 256>(); named_arrive<3, 256>();
    asm volatile("barrier.cluster.arrive.relaxed.aligned;" ::: "memory");
    uint64_t pol_first;
    asm volatile("createpolicy.fractional.L2::evict_first.b64 %0, 1.0;" : "=l"(pol_first));
    const bool moe = b < NMOE;
    uint32_t wf[128];
    auto take = [&](auto R) {
      constexpr int r = decltype(R)::value;
      const uint32_t box = sb + SPARE + warp * 8192;
      if (moe || r == 0) mbar_wait(BAR(B_WB + warp), r);
      if (moe) take_box<r>(wf, box, lane);
      fence_async_smem();
      __syncwarp();
      if (lane == 0) {
        if (r) {
          mbar_arrive(BAR(B_XF));
        }
        else if (moe) { mbar_expect_tx(BAR(B_WB + warp), 8192); tma_2d_hint(box, &maps.wu, b * 32, warp * 128, BAR(B_WB + warp), pol_first); }
      }
      __syncwarp();
    };

    if (warp == 0) {
      auto loadA = [&](int g) {
        mbar_expect_tx(BAR(B_FULL + (g & 3)), SLOT);
        tma_2d_hint(sb + (g & 3) * STAGE, &maps.ws[j], g * 64, t * 128, BAR(B_FULL + (g & 3)), pol_first);
      };
      auto loadB = [&](int g, int bar) { mbar_expect_tx(BAR(bar + (g & 3)), 2 * SLOT); tma_3d(sb + (g & 3) * STAGE + SLOT, &maps.n, 0, g * 64, m4 * 4, BAR(bar + (g & 3))); };
      delay_until(c0, FK_ADLY);
      if (lane == 0) {
#pragma unroll 1
        for (int g = 0; g <= FK_AEARLY; g++) { loadA(g); if (g < FK_AEARLY) delay_until(c0, FK_ADLY + (g + 1) * FK_ASTEP); }
        TRACE(63);
      }
      __syncwarp();
      asm volatile("add.u32 %0, %0, 1;" : "+r"(tag)::"memory");
      delay_until(c0, FK_POLL0 + (early & pp.zero));
#pragma unroll 1
      for (int gi = 0; gi < 2; gi++) {
        int it = 0;
        const unsigned* cp = &pp.cnt[gi * 32];
        if (gi >= FK_NOHINT) while ((int)(ld_rlx(cp) - tag * 128u) < 0) { if (++it > SPIN_LIMIT) SPIN_FAIL(0x201); }
        if (gi && FK_NOHINT == 2) delay_until(c0, FK_POLL0 + 600);
        if (lane == 0) {
          if (gi == 0) TRACE(2);
          loadB(2 * gi, B_LAND);
          if (2 * gi > FK_AEARLY) loadA(2);
          if (2 * gi + 1 > FK_AEARLY) loadA(2 * gi + 1);
          loadB(2 * gi + 1, B_LAND);
        }
        __syncwarp();
      }
      if (lane == 0) { prefetch_tmap(&maps.p); prefetch_tmap(&maps.wd[j]); }
      const unsigned tgt = tag * 128u;
      unsigned pend = ld_rlx(&pp.cnt[2 * 32]);
      const char* pfa = piece_addr(pp, b, lane);
      const uint32_t pfn = (lane >> 2) == 2 || lane >= 20 ? 8192 : 7168;
      auto produce1 = [&](int g0, int g1) {
#pragma unroll 1
        for (int g = g0; g < g1; g++) {
          mbar_wait(BAR(B_EMPTYH + (g & 3)), ((g >> 2) - 1) & 1);
          mbar_wait(BAR(B_EMPTY + (g & 3)), ((g >> 2) - 1) & 1);
          if (!(g & 1)) {
            if ((int)(pend - tgt) < 0) {
              int it = 0;
              while ((int)(ld_rlx(&pp.cnt[(g >> 1) * 32]) - tgt) < 0) { if (++it > SPIN_LIMIT) SPIN_FAIL(0x20c); }
            }
            fence_async_global();
            pend = ld_rlx(&pp.cnt[((g >> 1) + 1) * 32]);
          }
          if (lane == 0) {
            loadA(g); loadB(g, B_FULL);
          }
          if (lane == g - FK_PF0 && lane >= FK_PFSKIP) pf_bulk(pfa, pfn);
          __syncwarp();
        }
      };
      {
        int it = 0;
        while ((int)(pend - tgt) < 0) { pend = ld_rlx(&pp.cnt[2 * 32]); if (++it > SPIN_LIMIT) SPIN_FAIL(0x20f); }
        if (lane == 0) TRACE(60);
      }
      produce1(4, FK_TG);
      take(IntC<0>{});
      produce1(FK_TG, FK_TU);
      take(IntC<1>{});
      produce1(FK_TU, 32);
      int sib = 0, pc = 0;
      auto produce2 = [&](int q0, int q1) {
#pragma unroll 1
        for (int q = q0; q < q1; q++) {
          const int s = q & 3, k0 = sibling(m4, sib) * 256 + pc * 64;
          const uint32_t sa = sb + s * STAGE;
          mbar_wait(BAR(B_EMPTY + s), ((q >> 2) + 1) & 1);
          if (lane == 0) {
            mbar_expect_tx(BAR(B_FULL + s), 2 * SLOT);
            tma_2d(sa + SLOT, &maps.wd[j], k0, m4 * 256, BAR(B_FULL + s));
            if (q < 4) mbar_arrive(BAR(B_FULL + s));
          }
          __syncwarp();
          if (q >= 4) {
            mbar_wait(BAR(B_PL + s), 0);
            if (lane == 0) { mbar_expect_tx(BAR(B_LAND + s), SLOT); tma_2d(sa, &maps.p, k0, j * S_ + t * 128, BAR(B_LAND + s)); }
            if (++sib == 4) { sib = 1; pc++; }
          } else if (++pc == 4) { pc = 0; sib = 1; }
          if (lane == 32 + q - FK_PF0 && lane < 27) pf_bulk(pfa, pfn);
          if (q >= FK_XQ && q < FK_XQ + 4 * FK_XS && (q - FK_XQ) % FK_XS == 0) {
            const int w = (q - FK_XQ) / FK_XS;
            mbar_wait(BAR(B_XF), 0);
            if (lane == 0) { mbar_expect_tx(BAR(B_X), 8192); tma_2d(sb + SPARE + w * 8192, &maps.x, m4 * 256 + w * 64, t * 128 + j * 64, BAR(B_X)); }
          }
          __syncwarp();
        }
      };
      produce2(0, 16);
      if (moe) {
        mbar_wait(BAR(B_EMPTY + 0), 1);
        if (lane == 0) {
          mbar_expect_tx(BAR(B_GU), 49152);
#pragma unroll 1
          for (int i = 0; i < 3; i++) {
            tma_2d(sb + i * SLOT, &maps.wg, b * 32, 512 + i * 128, BAR(B_GU));
            tma_2d(sb + i * SLOT + 8192, &maps.wu, b * 32, 512 + i * 128, BAR(B_GU));
          }
        }
        mbar_wait(BAR(B_EMPTY + 1), 1);
        if (FK_WGATE >= 0) mbar_wait(BAR(B_RECV + FK_WGATE), 0);
        if (lane == 0) {
          mbar_expect_tx(BAR(B_GU), 16384);
          tma_2d(sb + STAGE + SLOT, &maps.wg, b * 32, 896, BAR(B_GU));
          tma_2d(sb + STAGE + SLOT + 8192, &maps.wu, b * 32, 896, BAR(B_GU));
        }
#pragma unroll 1
        for (int i = 0; i < 4; i++) {
          if (i == 1) mbar_wait(BAR(B_EMPTY + 2), 1);
          if (i == 3) mbar_wait(BAR(B_XDONE), 0);
          if (i >= FK_DNWIN) mbar_wait(BAR(B_DN + i - FK_DNWIN), 0);
          if (lane == 0) {
            mbar_expect_tx(BAR(B_DN + i), 16384);
            tma_3d(sb + dn_box(i), &maps.wdn, 0, b * 32, i * 4, BAR(B_DN + i));
          }
        }
      }
      __syncwarp();
    } else if (warp == 1) {
      asm volatile("add.u32 %0, %0, 1;" : "+r"(tag)::"memory");
      if (lane == 0) prefetch_tmap(&maps.ps);
      delay_until(c0, FK_WS1DLY);
      float a0 = __uint_as_float(early & pp.zero), a1 = __uint_as_float(ws_touch(128) & pp.zero);
      auto rowsum = [&](int g0, int g1) {
        const uint32_t rb = sb + (m4 * 32 + lane) * 128 + ((lane & 7) << 4);
#pragma unroll 1
        for (int g = g0; g < g1; g++) {
          const int s = g & 3;
          mbar_wait(BAR(B_FULL + s), (g >> 2) & 1);
          uint4 u[8];
#pragma unroll
          for (int c = 0; c < 8; c++) u[c] = lds128u((rb ^ (uint32_t)(c << 4)) + s * STAGE);
#pragma unroll
          for (int c = 0; c < 8; c += 2) { a0 += sum8(u[c]); a1 += sum8(u[c + 1]); }
          if (lane == 0) mbar_arrive(BAR(B_EMPTYH + s) + ((__float_as_uint(a0) | __float_as_uint(a1)) & pp.zero));
        }
      };
      rowsum(0, FK_TG - 2);
      take(IntC<0>{});
      rowsum(FK_TG - 2, 28);
      mbar_wait(BAR(B_MODOK), 0);
      a0 += lds32(sb + RS_OFF + 256 + lane * 4);
      __syncwarp();
      uint2* rsp = &pp.mail->rs[(j * 16 + t) * 128 + lane];
      st_msg8(rsp + m4 * 32, __float_as_uint(a0 + a1), tag);
      {
        uint2 m[4]; int it = 0;
        while (true) {
#pragma unroll
          for (int i = 0; i < 4; i++) m[i] = ld_msg8(rsp + 32 * i);
          if (__all_sync(~0u, m[0].y == tag && m[1].y == tag && m[2].y == tag && m[3].y == tag)) break;
          if (++it > SPIN_LIMIT) SPIN_FAIL(0x208);
        }
#pragma unroll
        for (int i = 0; i < 4; i++) sts32u(sb + RS_OFF + (lane + 32 * i) * 4, pack_bf16(__uint_as_float(m[i].x), __uint_as_float(m[i].x)));
      }
      __syncwarp();
      if (lane == 0) { mbar_arrive(BAR(B_T1)); TRACE(11); }
      take(IntC<1>{});
      {
        uint32_t cn = 0;
#pragma unroll 1
        for (int i = 0; i < 8; i++) {
          const int q = i >> 1, half = (i & 1) ? j : 1 - j;
          if (i < 4) mbar_wait(BAR(B_PRDY + (i & 1) * 2 + (q | (!FK_LF && i == 0))), 0);
          if (i) delay_until(cn, FK_PPACE);
          cn = clk();
          if (lane == 0) {
            tma_store_2d(&maps.ps, sb + q * STAGE + half * 8192, m4 * 256 + q * 64, j * S_ + t * 128 + half * 64);
            bulk_commit();
            if (i && !(i & 1)) { bulk_wait_read<1>(); mbar_arrive(BAR(B_PL + q - 1)); }
          }
          __syncwarp();
        }
        if (lane == 0) { bulk_wait_read<0>(); mbar_arrive(BAR(B_PL + 3)); }
        if (lane == 0) TRACE(8);
      }
      named_bar<7, 64>();
      delay_until(clk(), FK_E2DLY);
      const uint2* cp = &pp.mail->cand[lane];
      auto select = [&](uint2 m) {
        if (!__all_sync(~0u, m.y != 0)) return false;
        uint32_t k1, k2;
        warp_top2(m.y, m.x, k1, k2);
        if (lane == 0) { sts64u(sb + SEL_OFF, k1, k2); mbar_arrive(BAR(B_SEL)); TRACE(19); }
        return true;
      };
      int it = 0;
      while (!select(ld_msg8(cp))) { delay_until(clk(), -(FK_E2GAP)); if (++it > SPIN_LIMIT) SPIN_FAIL(0x206); }
    } else {
      const int kh = warp - 2;
      const uint32_t reg = sb + SPARE + kh * 16384;
      const uint4 cw0 = ldg_nc(pp.c + (kh * 64 + lane) * 16), cw1 = ldg_nc(pp.c + (kh * 64 + lane + 32) * 16);
#pragma unroll 1
      for (int i = 0; i < 2; i++) {
        const uint4 cw4 = i ? cw1 : cw0;
        const uint32_t ad = reg + 12288 + (lane + 32 * i) * 32;
        sts128(ad, round_bf16(silu_f(bf_lo(cw4.x))), round_bf16(silu_f(bf_hi(cw4.x))), round_bf16(silu_f(bf_lo(cw4.y))), round_bf16(silu_f(bf_hi(cw4.y))));
        sts128(ad + 16, round_bf16(silu_f(bf_lo(cw4.z))), round_bf16(silu_f(bf_hi(cw4.z))), round_bf16(silu_f(bf_lo(cw4.w))), round_bf16(silu_f(bf_hi(cw4.w))));
      }
      asm volatile("add.u32 %0, %0, 1;" : "+r"(tag)::"memory");
      if (lane == 0) prefetch_tmap(&maps.wm);
      unsigned ph = 0;
      const size_t ro = (size_t)((FK_G0 + 1 - kh) * 128 + rb) * (2 * D_), rs = (size_t)2 * (128 * 2 * D_);
      auto rows = [&]() {
        if (lane == 0) {
          mbar_expect_tx(BAR(B_XR + kh), 4096);
          bulk_load(reg + 14336, pp.x + ro + rs, 2048, BAR(B_XR + kh)); bulk_load(reg + 6144, pp.x + ro, 2048, BAR(B_XR + kh));
        }
      };
      if (kh == 0) {
#pragma unroll 1
        for (int s = 0; s < 4; s++) {
          const uint32_t ra = sb + s * STAGE + SLOT + lane * 128 + ((lane & 7) << 4);
          int it = 0;
          while (true) {
            mbar_wait(BAR(B_LAND + s), (ph >> s) & 1);
            ph ^= 1u << s;
            if (lane == 0 && it == 0) TRACE(120 + s);
            uint32_t mn = ~0u;
#pragma unroll
            for (int u = 0; u < 8; u++) mn = min(mn, lds32u(ra + u * 4096));
            if (__all_sync(~0u, mn)) break;
            if (lane == 0) { mbar_expect_tx(BAR(B_LAND + s), 2 * SLOT); tma_3d(sb + s * STAGE + SLOT, &maps.n, 0, s * 64, m4 * 4, BAR(B_LAND + s)); TRACE(92 + s); }
            if (++it > (1 << 16)) SPIN_FAIL(0x203);
          }
          if (lane == 0) mbar_arrive(BAR(B_FULL + s));
          if (s == FK_RS) rows();
        }
      } else {
        named_bar<9, 32 * (FK_G0 - FK_GA - 1)>();
        uint32_t rbk = 0;
#pragma unroll
        for (int g = 2 + FK_GA; g < FK_G0; g += 2) rbk |= ld_rlx(pp.n + (size_t)(min(g + (lane >> 4), FK_G0 - 1) * 128 + rb) * (2 * D_) + (lane & 15) * 128);
        delay_until(c0, FK_ROW8DLY);
        rows();
        const uint32_t z = landed(rbk, pp.zero);
        if (lane >= 2 + FK_GA && lane < FK_G0) red_add(&pp.cnt[lane * 32], 1 + z);
        if (lane == 0) TRACE(56);
      }
      auto request0 = [&](int c) {
        mbar_expect_tx(BAR(B_WM + kh * 2 + c), 6144);
        tma_2d_hint(reg + c * 6144, &maps.wm, b * 48, kh * 512 + c * 64, BAR(B_WM + kh * 2 + c), pol_first);
      };
      mbar_wait(BAR(B_XR + kh), 0);
#pragma unroll 1
      for (int k = 0; k < 2; k++) {
        if (lane == 0) request0(k);
        uint4 w[4];
#pragma unroll
        for (int i = 0; i < 4; i++) w[i] = lds128u(reg + 6144 + k * 8192 + lane * 16 + i * 512);
        ln_row(w);
#pragma unroll
        for (int i = 0; i < 4; i++) stg128(pp.n + ro + k * rs + lane * 16 + i * 512, w[i]);
      }
      const uint32_t rbk2 = ld_rlx(pp.n + ro + (lane >> 4) * rs + (lane & 15) * 128);
      if (lane == 0) TRACE(58 + kh);
      {
        float acc[3][8];
        uint32_t sad[3];
#pragma unroll
        for (int a = 0; a < 3; a++) {
          sad[a] = reg + 12288 + ((32 * a + lane) / 6) * 4;
#pragma unroll
          for (int i = 0; i < 8; i++) acc[a][i] = 0.f;
        }
        const char* wsrc = (j ? pp.ws_im : pp.ws_re) + (size_t)(t * 128 + m4 * 32 + kh * 16 - 16) * (2 * S_) + 28 * 128 + lane * 16;
        uint32_t cn = c0 + FK_GSTART + (1 - kh) * (FK_PACE / 2);
        auto request = [&](int c) {
          mbar_expect_tx(BAR(B_WM + kh * 2 + (c & 1)), 6144 + ((__float_as_uint(acc[0][0]) | __float_as_uint(acc[1][0]) | __float_as_uint(acc[2][0])) & pp.zero));
          tma_2d_hint(reg + (c & 1) * 6144, &maps.wm, b * 48, kh * 512 + c * 64, BAR(B_WM + kh * 2 + (c & 1)), pol_first);
        };
        uint4 e[4];
#pragma unroll 1
        for (int c = 0; c < 8; c++) {
          while ((int)(clk() - cn) < 0) __nanosleep(40);
          cn += FK_PACE;
          if (c >= 4) {
            const float v0 = sum8(e[0]), v1 = sum8(e[1]), v2 = sum8(e[2]), v3 = sum8(e[3]);
            const bool u4 = lane & 16, u3 = lane & 8;
            const float w0 = (u4 ? v2 : v0) + __shfl_xor_sync(~0u, u4 ? v0 : v2, 16), w1 = (u4 ? v3 : v1) + __shfl_xor_sync(~0u, u4 ? v1 : v3, 16);
            float v = (u3 ? w1 : w0) + __shfl_xor_sync(~0u, u3 ? w0 : w1, 8);
            v += __shfl_xor_sync(~0u, v, 4); v += __shfl_xor_sync(~0u, v, 2); v += __shfl_xor_sync(~0u, v, 1);
            if (!(lane & 7)) sts32(sb + RS_OFF + 256 + (kh * 16 + c * 4 - 16 + (lane >> 3)) * 4, v);
          }
          if (c >= FK_ZC0) {
            constexpr int LPR = FK_ZB / 16, RPI = 8 / LPR, NI = 64 / RPI / (8 - FK_ZC0);
            char* pr = pp.P + (size_t)(j * S_ + t * 128 + kh * 64 + (c - FK_ZC0) * NI * RPI + lane / (4 * LPR)) * (2 * D_) + m4 * 512 + ((lane / LPR) & 3) * 128 + (lane % LPR) * 16;
#pragma unroll
            for (int i = 0; i < NI; i++) stg128(pr + (size_t)i * (RPI * 2 * D_), make_uint4(0, 0, 0, 0));
          }
          if (c >= 3 && c < 7) {
#pragma unroll
            for (int i = 0; i < 4; i++) e[i] = ldg_nc(wsrc + (size_t)(c * 4 + 4 + i) * (2 * S_));
          }
          mbar_wait(BAR(B_WM + kh * 2 + (c & 1)), (c >> 1) & 1);
#pragma unroll
          for (int u = 0; u < 12; u++) {
            const uint4 v = lds128u(reg + (c & 1) * 6144 + lane * 16 + u * 512);
            const float sc = lds32(sad[u % 3] + (u / 3) * 64);
            float (&ac)[8] = acc[u % 3];
            ac[0] = fmaf(sc, bf_lo(v.x), ac[0]); ac[1] = fmaf(sc, bf_hi(v.x), ac[1]);
            ac[2] = fmaf(sc, bf_lo(v.y), ac[2]); ac[3] = fmaf(sc, bf_hi(v.y), ac[3]);
            ac[4] = fmaf(sc, bf_lo(v.z), ac[4]); ac[5] = fmaf(sc, bf_hi(v.z), ac[5]);
            ac[6] = fmaf(sc, bf_lo(v.w), ac[6]); ac[7] = fmaf(sc, bf_hi(v.w), ac[7]);
          }
#pragma unroll
          for (int a = 0; a < 3; a++) sad[a] += 256;
          __syncwarp();
          if (lane == 0 && c < 6) request(c + 2);
          if (c == 0) {
            const uint32_t z = landed(rbk2, pp.zero);
            if (lane < 2) red_add(&pp.cnt[(FK_G0 + 1 - kh + 2 * lane) * 32], 1 + z);
          }
        }
        __syncwarp();
#pragma unroll
        for (int a = 0; a < 3; a++) {
          sts128(reg + (32 * a + lane) * 32, acc[a][0], acc[a][1], acc[a][2], acc[a][3]);
          sts128(reg + (32 * a + lane) * 32 + 16, acc[a][4], acc[a][5], acc[a][6], acc[a][7]);
        }
        __syncwarp();
        float s0 = 0.f, s1 = 0.f;
#pragma unroll 8
        for (int m = 0; m < 16; m++) { const float2 v = lds64(reg + (lane < 24 ? lane * 8 : 0) + m * 192); s0 += v.x; s1 += v.y; }
        if (kh == 0) sts64(sb + RS_OFF + lane * 8, s0, s1);
        if (lane == 0) TRACE(80 + kh);
        named_bar<5, 64>();
        if (kh == 1) {
          const float2 p = lds64(sb + RS_OFF + lane * 8);
          unsigned* dst = pp.mod + b * 24 + (lane < 24 ? lane : 0);
          if (lane < 24) st_rlx(dst, pack_bf16(s0 + p.x, s1 + p.y));
          uint32_t rbk = ld_rlx(dst);
          if (b == 0) { st_msg8(&pp.mail->cand[lane], 0, 0); rbk |= ld_rlx(&pp.mail->cand[lane]); }
          const uint32_t z = landed(rbk, pp.zero);
          if (lane == 0) { red_add(&pp.cnt[16 * 32], 1 + z); mbar_arrive(BAR(B_MODOK)); TRACE(9); }
          __syncwarp();
        }
      }
      if (kh == 0) {
#pragma unroll 1
        for (int i = 0; i < 4; i++) {
          const int w = i ^ 2;
          if (lane == 0) {
            if (moe) { mbar_expect_tx(BAR(B_WB + w), 8192); tma_2d_hint(sb + SPARE + w * 8192, &maps.wg, b * 32, w * 128, BAR(B_WB + w), pol_first); }
            else mbar_arrive(BAR(B_WB + w));
          }
          __nanosleep(FK_BSLEEP);
        }
        take(IntC<0>{});
        if (lane == 0) { fence_gpu(); mbar_arrive(BAR(B_MODOK)); TRACE(57); }
        __syncwarp();
        take(IntC<1>{});
        if (lane == 0) TRACE(98);
        int sib = 1, pc = 0;
#pragma unroll 1
        for (int q = 4; q < 16; q++) {
          const int s = q & 3;
          const uint32_t ra = sb + s * STAGE + lane * 128 + ((lane & 7) << 4);
          int it = 0;
          while (true) {
            mbar_wait(BAR(B_LAND + s), (ph >> s) & 1);
            ph ^= 1u << s;
            if (__all_sync(~0u, min(min(lds32u(ra), lds32u(ra + 4096)), min(lds32u(ra + 8192), lds32u(ra + 12288))))) break;
            if (lane == 0) {
              mbar_expect_tx(BAR(B_LAND + s), SLOT);
              tma_2d(sb + s * STAGE, &maps.p, sibling(m4, sib) * 256 + pc * 64, j * S_ + t * 128, BAR(B_LAND + s));
            }
            if (++it > (1 << 16)) SPIN_FAIL(0x202);
          }
          if (lane == 0) mbar_arrive(BAR(B_FULL + s));
          if (++sib == 4) { sib = 1; pc++; }
        }
        if (lane == 0) TRACE(99);
      } else {
        take(IntC<0>{});
        {
          const unsigned tgt = tag * 128u; int it = 0;
          while ((int)(ld_rlx(&pp.cnt[16 * 32]) - tgt) < 0) { __nanosleep(100); if (++it > SPIN_LIMIT) SPIN_FAIL(0x204); }
        }
        if (lane == 0) TRACE(10);
        st_rlx(reinterpret_cast<unsigned*>(pp.n + (size_t)((lane >> 4) * 128 + rb) * (2 * D_) + (lane & 15) * 128), 0);
        {
          const uint32_t sgn = j ? 0x80008000u : 0u;
          uint32_t sa[4], ca[4]; uint4 sv[4], cv[4], wr[4];
#pragma unroll
          for (int i = 0; i < 4; i++) {
            const int p = lane + 32 * i;
            sa[i] = ld_rlx(pp.mod + m4 * 128 + p); ca[i] = ld_rlx(pp.mod + 512 + m4 * 128 + p);
            sv[i] = ld_msg(reinterpret_cast<const uint4*>(pp.mod + 1536) + p); cv[i] = ld_msg(reinterpret_cast<const uint4*>(pp.mod + 2048) + p);
            wr[i] = ldg_nc(pp.wr + p * 16);
          }
          float c1 = 0.f, c2 = 0.f;
#pragma unroll
          for (int i = 0; i < 4; i++) {
            const int p = lane + 32 * i;
            sts64(sb + T1_OFF + ((p >> 3) * 4 + (p & 3)) * 16 + ((p >> 2) & 1) * 8, __uint_as_float(add1_bf2(ca[i]) ^ sgn), __uint_as_float(sa[i] ^ sgn));
            const uint32_t s4[4] = {sv[i].x, sv[i].y, sv[i].z, sv[i].w}, c4[4] = {cv[i].x, cv[i].y, cv[i].z, cv[i].w}, w4[4] = {wr[i].x, wr[i].y, wr[i].z, wr[i].w};
#pragma unroll
            for (int u = 0; u < 4; u++) {
              const uint32_t A = add1_bf2(c4[u]);
              c1 = fmaf(bf_lo(A), bf_lo(w4[u]), c1); c1 = fmaf(bf_hi(A), bf_hi(w4[u]), c1);
              c2 = fmaf(bf_lo(s4[u]), bf_lo(w4[u]), c2); c2 = fmaf(bf_hi(s4[u]), bf_hi(w4[u]), c2);
            }
          }
#pragma unroll
          for (int o = 16; o; o >>= 1) { c1 += __shfl_xor_sync(~0u, c1, o); c2 += __shfl_xor_sync(~0u, c2, o); }
          __syncwarp();
          if (lane == 0) { sts128(sb + CST_OFF, c1, c2, __uint_as_float(tag), 0.f); mbar_arrive(BAR(B_T1)); TRACE(30); }
        }
        take(IntC<1>{});
        const int G = lane >> 2, q = lane & 3, p0 = m4 * 128 + G * 16 + q;
        mbar_wait(BAR(B_PRDY + 1), 0);
        mbar_wait(BAR(B_PRDY + 3), 0);
        uint32_t ga[4], hi[4], lo[4];
#pragma unroll
        for (int u = 0; u < 4; u++) {
          ga[u] = ld_rlx(pp.mod + 1024 + p0 + 4 * u);
          const uint32_t cb = ld_rlx(pp.mod + 2048 + p0 + 4 * u), wr = __ldg(reinterpret_cast<const uint32_t*>(pp.wr) + p0 + 4 * u);
          const float w0 = bf_lo(add1_bf2(cb)) * bf_lo(wr), w1 = bf_hi(add1_bf2(cb)) * bf_hi(wr);
          hi[u] = pack_bf16(w0, w1);
          lo[u] = pack_bf16(w0 - bf_lo(hi[u]), w1 - bf_hi(hi[u]));
        }
        sts128u(sb + GA_OFF + lane * 16, ga[0], ga[1], ga[2], ga[3]);
        sts128u(sb + W_OFF + G * 144 + q * 16, hi[0], hi[1], hi[2], hi[3]);
        sts128u(sb + W_OFF + G * 144 + 64 + q * 16, lo[0], lo[1], lo[2], lo[3]);
        sts32u(sb + W_OFF + G * 144 + 128 + q * 4, 0x3F803F80u);
        mbar_wait(BAR(B_PL + 3), 0);
        __nanosleep(FK_RSLEEP);
        const uint4 sv = make_uint4(SENT, SENT, SENT, SENT);
#pragma unroll 1
        for (int i = 0; i < 7; i++) stg128(&pp.mail->part[(size_t)b * (NMOE * 2) + lane + 32 * i], sv);
#pragma unroll 1
        for (int i = 0; i < 2; i++) {
          stg128(&pp.mail->stats[(blk * 4 + m4) * 64 + lane + 32 * i], sv);
          stg128(&pp.mail->rowh[(blk * 2 + i) * 128 + m4 * 32 + lane], sv);
          stg128(&pp.mail->rowx[(blk * 2 + i) * 128 + m4 * 32 + lane], sv);
        }
        if (lane == 0) { red_max8(&pp.mail->cand[blk], 1, 0); red_add(&pp.cnt[18 * 32], 1); }
        __syncwarp();
        if (lane == 0) { fence_gpu(); mbar_arrive(BAR(B_T2)); TRACE(97); }
      }
    }
    mbar_wait(BAR(B_SEL), 0);
    if (moe) gate_up(pp, wf, sb, scr, warp, lane);
    if (warp == 1) {
      const uint2 sel = lds64u(sb + SEL_OFF);
      const int n = (lane >> 3) & 1;
      const int col = (b >> 4) * 128 + (lane & 1) * 64 + ((b >> 2) & 3) * 16 + (b & 3) * 2 + ((lane >> 1) & 1) + (lane >> 4) * 8;
      const int slot = sel_slot(sel, n) * 512, wofs = slot + ((col >> 5) * 4 + ((col >> 1) & 3)) * 4 + ((col >> 3) & 3);
      const uint32_t gbp = ld_rlx(pp.mod + 2560 + (col >> 1));
      uint32_t hp, xp; int it = 0;
      while (true) {
        hp = ld_rlx(reinterpret_cast<const uint32_t*>(pp.mail->rowh) + wofs); xp = ld_rlx(reinterpret_cast<const uint32_t*>(pp.mail->rowx) + slot + (col >> 1));
        if (__all_sync(~0u, hp != SENT && xp != SENT)) break;
        if (++it > SPIN_LIMIT) SPIN_FAIL(0x2ff);
      }
      const float sg = round_bf16(sigmoid_f(round_bf16(key_val(n ? sel.y : sel.x))));
      const bool odd = col & 1;
      float gbv = odd ? bf_hi(gbp) : bf_lo(gbp), hv = odd ? bf_hi(hp) : bf_lo(hp), xv = odd ? bf_hi(xp) : bf_lo(xp);
      char* optr = pp.out + ((size_t)key_row(n ? sel.y : sel.x) * D_ + col) * 2;
      asm volatile("" : "+f"(gbv), "+f"(hv), "+f"(xv), "+l"(optr));
      const int gq = lane >> 2;
      const uint32_t one = (lane & 1) == (gq >> 2) ? ((gq & 1) ? 0x3F800000u : 0x00003F80u) : 0u;
      const uint32_t s0 = (gq & 2) ? 0u : one, s1 = (gq & 2) ? one : 0u;
      const uint4* src = &pp.mail->part[(size_t)b * (NMOE * 2) + lane];
      uint4 m[7];
      it = 0;
      while ((int)(ld_rlx(&pp.cnt[18 * 32]) - tag * (NCTA + NMOE)) < 0) { if (++it > SPIN_LIMIT) SPIN_FAIL(0x20d); }
      delay_until(clk(), FK_E4DLY);
      it = 0;
      while (true) {
        bool ok = true;
#pragma unroll
        for (int i = 0; i < 7; i++) m[i] = ld_msg(src + 32 * i);
#pragma unroll
        for (int i = 0; i < 7; i++) ok &= m[i].x != SENT;
        if (__all_sync(~0u, ok)) break;
        if (++it > SPIN_LIMIT) SPIN_FAIL(0x20b);
      }
      if (lane == 0) TRACE(23);
      float c[3][4];
#pragma unroll
      for (int i = 0; i < 3; i++) { c[i][0] = c[i][1] = c[i][2] = c[i][3] = 0.f; }
#pragma unroll
      for (int i = 0; i < 7; i++) mma_16816(c[i % 3], m[i].x, m[i].y, m[i].z, m[i].w, s0, s1);
#pragma unroll
      for (int i = 0; i < 4; i++) c[0][i] += c[1][i] + c[2][i];
      const bool u4 = lane & 16, u3 = lane & 8;
      const float a0 = (u4 ? c[0][2] : c[0][0]) + __shfl_xor_sync(~0u, u4 ? c[0][0] : c[0][2], 16), a1 = (u4 ? c[0][3] : c[0][1]) + __shfl_xor_sync(~0u, u4 ? c[0][1] : c[0][3], 16);
      float y = (u3 ? a1 : a0) + __shfl_xor_sync(~0u, u3 ? a0 : a1, 8);
      y += __shfl_xor_sync(~0u, y, 4);
      const float upd = round_bf16(round_bf16(y) * sg);
      const uint32_t o = pack_bf16(fmaf(gbv, hv + upd, xv), 0.f);
      if (!(lane & 4)) asm volatile("st.global.u16 [%0], %1;" ::"l"(optr), "h"((unsigned short)o) : "memory");
      if (lane == 0) { TRACE(24); TRACE_CLK(54); if (b == 0) pp.cnt[17 * 32] = tag; }
    }
  } else {
    const int cw = (warp - 4) >> 2;
    const int wq = warp & 3;
    const int wtid = tid & 127;
    const int gq = lane >> 2, q4 = lane & 3;
    const bool lag = cw == j;
    const bool elect = wtid == 0;
    const uint32_t rel = wtid < 2 ? mapa(BAR(B_EMPTY), wtid) : 0;

    if (cw) named_bar<3, 256>(); else named_bar<0, 256>();
    if (tid == 128) TRACE(124);
    asm volatile("barrier.cluster.wait.acquire.aligned;" ::: "memory");
    if (tid == 128) TRACE(125);

    const int mrow = wq * 16 + (lane & 7) + ((lane >> 3) & 1) * 8;
    {
      float acc[128];
      gemm_phase<1, 0, 32>(pp, acc, sb, cw, lag, elect, rel);
      mbar_wait(BAR(B_T1), 0);
      const uint32_t tad = sb + T1_OFF + q4 * 16;
      uint4 tb[16];
#pragma unroll
      for (int c = 0; c < 4; c++) tb[c] = lds128u(tad + c * 64);
      const uint32_t rs0 = lds32u(sb + RS_OFF + (cw * 64 + wq * 16 + gq) * 4), rs1 = lds32u(sb + RS_OFF + (cw * 64 + wq * 16 + gq + 8) * 4);
      const uint32_t dst = sb + cw * 8192 + mrow * 128, pb = BAR(B_PRDY + (lag ? 2 : 0));
      gemm_finish(acc, rel);
      if (elect) { TRACE(lag ? 5 : 4); if (lag) TRACE_CLK(51); }
#pragma unroll
      for (int i = 0; i < 16; i++) {
        uint32_t r[4];
        const int o = 8 * i;
        r[0] = fma_bf2(pack_bf16(acc[o], acc[o + 1]), tb[i].x, mul_bf2(rs0, tb[i].y));
        r[1] = fma_bf2(pack_bf16(acc[o + 2], acc[o + 3]), tb[i].x, mul_bf2(rs1, tb[i].y));
        r[2] = fma_bf2(pack_bf16(acc[o + 4], acc[o + 5]), tb[i].z, mul_bf2(rs0, tb[i].w));
        r[3] = fma_bf2(pack_bf16(acc[o + 6], acc[o + 7]), tb[i].z, mul_bf2(rs1, tb[i].w));
        if (!(i & 3)) { r[0] = nonzero(r[0]); r[1] = nonzero(r[1]); }
        if (i < 12) tb[i + 4] = lds128u(tad + (i + 4) * 64);
        stsm_x4(dst + (i >> 2) * STAGE + (uint32_t)(((((2 * i) & 7) + (lane >> 4)) ^ (lane & 7)) << 4), r[0], r[1], r[2], r[3]);
        if ((i == 3 && (lag || FK_LF)) || i == 15) {
          fence_async_smem();
          __syncwarp();
          if (lane == 0) mbar_arrive(pb + (i >> 3) * 8);
        }
      }
      if (FK_WB) mbar_wait(pb + 8, 0);
    }
    if (elect) TRACE(lag ? 7 : 6);
    float acc[128];
    gemm_phase<0, 32, 48>(pp, acc, sb, cw, lag, elect, rel);

    if (!lag) {
      const uint32_t rdst = mapa(sb + STAGE + j * 8192 + wtid * 16, j ^ 1), rbar = mapa(BAR(B_RECV), j ^ 1);
      mbar_wait(BAR(B_PEER), 0);
      gemm_finish(acc, rel);
      if (elect) { mbar_arrive_cluster(rbar + (B_PEER + 1 - B_RECV) * 8); TRACE(12); }
#pragma unroll
      for (int i = 0; i < 16; i++) {
        const int o = 8 * i;
        if (i == 8) mbar_wait(BAR(B_PEER + 1), 0);
        if (i == 12) mbar_wait(BAR(B_EMPTY + 1), 1);
        asm volatile("st.async.weak.shared::cluster.mbarrier::complete_tx::bytes.v4.b32 [%0], {%1, %2, %3, %4}, [%5];"
                     ::"r"(i < 12 ? rdst + (i >> 2) * STAGE + (i & 3) * 2048 : rdst + (1 - 2 * j) * 8192 + (i & 3) * 2048),
                       "r"(pack_bf16(acc[o], acc[o + 1])), "r"(pack_bf16(acc[o + 2], acc[o + 3])), "r"(pack_bf16(acc[o + 4], acc[o + 5])),
                       "r"(pack_bf16(acc[o + 6], acc[o + 7])), "r"(rbar + (i >> 2) * 8) : "memory");
      }
      if (elect) TRACE(13);
      if (b < NMOE) {
        uint32_t wf[128];
        named_bar<1, 256>();
        mbar_wait(BAR(B_GU), 0);
        const uint32_t box = sb + (wq < 3 ? wq : 4) * SLOT;
        take_box<0>(wf, box, lane);
        take_box<1>(wf, box + 8192, lane);
        if (elect) TRACE(26);
        mbar_wait(BAR(B_SEL), 0);
        gate_up(pp, wf, sb, scr, 4 + wq, lane);
        if (elect) red_add(&pp.cnt[18 * 32], 1);
        if (FK_QUIET) named_bar<8, 256>();
      }
      OutTab tb;
      {
        const uint4* mp = reinterpret_cast<const uint4*>(pp.mod) + m4 * 32 + lane;
        out_tab(tb, ldg128(mp + 512), ldg128(mp + 384), ldg128(mp + 640));
      }
      mbar_wait(BAR(B_SEL), 0);
      const uint2 sel = lds64u(sb + SEL_OFF), cnd = lds64u(sb + TOP_OFF + 32);
      char* odst = pp.out + (size_t)blk * (64 * 2 * D_) + m4 * 512 + lane * 16;
      const int g0 = blk * 64 + wq * 16;
      mbar_wait(BAR(B_OUT), 0);
      const uint32_t done = lds32u(sb + TOP_OFF + 48 + wq * 4);
      out_group(tb, sb, scr, wq * 16, ((0xFFFFu & (0xFFFFu << done)) | row_bit(cnd.x, g0) | row_bit(cnd.y, g0)) & ~(row_bit(sel.x, g0) | row_bit(sel.y, g0)),
                lane, odst, FK_OPACE2, 0);
      if (elect) TRACE(28);
    } else {
      mbar_wait(BAR(B_T2), 0);
      uint32_t xa[64];
      float dl[2][4], dq[4][4];
#pragma unroll
      for (int i = 0; i < 4; i++) { dl[0][i] = dl[1][i] = dq[0][i] = dq[1][i] = dq[2][i] = dq[3][i] = 0.f; }
      {
        uint32_t wad = sb + W_OFF + ((gq & 2) ? 128 : (gq & 1) * 64 + q4 * 16), gad = sb + GA_OFF + q4 * 16;
        uint32_t rsrc = sb + STAGE + (1 - j) * 8192 + wtid * 16, xad = sb + SPARE + mrow * 128 + (uint32_t)(((lane >> 4) ^ (lane & 7)) << 4);
        asm volatile("" : "+r"(wad), "+r"(gad), "+r"(rsrc), "+r"(xad));
        uint4 rv[16], wb[8], ga[8];
        uint32_t xf[16][4];
        auto loadx = [&](int i) { ldsm_x4((xad ^ (uint32_t)((i & 3) << 5)) + (i >> 2) * 8192, xf[i][0], xf[i][1], xf[i][2], xf[i][3]); };
        auto loadr = [&](int i) { rv[i] = lds128u(i < 12 ? rsrc + (i >> 2) * STAGE + (i & 3) * 2048 : rsrc + (2 * j - 1) * 8192 + (i & 3) * 2048); };
        auto loadt = [&](int h) { loadx(2 * h); loadx(2 * h + 1); ga[h] = lds128u(gad + h * 64); wb[h] = lds128u(wad + h * 144); };
        mbar_wait(BAR(B_X), 0);
        mbar_wait(BAR(B_RECV), 0);
        loadx(0); loadr(0); ga[0] = lds128u(gad);
        mbar_wait(BAR(B_RECV + 1), 0);
        gemm_finish(acc, rel);
        if (elect) { TRACE(14); TRACE_CLK(53); }
#pragma unroll
        for (int u = 0; u < 8 * FK_PK; u++) {
          xa[u] = pack_bf16(acc[2 * u], acc[2 * u + 1]);
          if (u == 15) { loadx(1); loadr(1); wb[0] = lds128u(wad); }
        }
#pragma unroll
        for (int h = 0; h < 8; h++) {
          if (h == FK_W2 || h == 6) mbar_wait(BAR(B_RECV + (h == 6 ? 3 : 2)), 0);
          if (h == 6) { loadr(12); loadr(13); }
          if (h < 7) loadt(h + 1);
          if (h < 7 && h != 5) { loadr(2 * h + 2); loadr(2 * h + 3); }
          if (h + FK_PK < 8) {
#pragma unroll
            for (int u = 8 * (h + FK_PK); u < 8 * (h + FK_PK) + 8; u++) xa[u] = pack_bf16(acc[2 * u], acc[2 * u + 1]);
          }
#pragma unroll
          for (int i = 2 * h; i < 2 * h + 2; i++) {
            const uint32_t g0 = (i & 1) ? ga[h].z : ga[h].x, g1 = (i & 1) ? ga[h].w : ga[h].y;
            const uint32_t a0 = fma_bf2(g0, add_bf2(xa[4 * i], rv[i].x), xf[i][0]), a1 = fma_bf2(g0, add_bf2(xa[4 * i + 1], rv[i].y), xf[i][1]);
            const uint32_t a2 = fma_bf2(g1, add_bf2(xa[4 * i + 2], rv[i].z), xf[i][2]), a3 = fma_bf2(g1, add_bf2(xa[4 * i + 3], rv[i].w), xf[i][3]);
            xa[4 * i] = a0; xa[4 * i + 1] = a1; xa[4 * i + 2] = a2; xa[4 * i + 3] = a3;
            mma_1688(dq[0], a0, a1, a0); mma_1688(dq[1], a0, a1, a1);
            mma_1688(dq[2 % FK_NQ], a2, a3, a2); mma_1688(dq[3 % FK_NQ], a2, a3, a3);
            mma_16816(dl[i & (FK_NL - 1)], a0, a1, a2, a3, (i & 1) ? wb[h].z : wb[h].x, (i & 1) ? wb[h].w : wb[h].y);
          }
        }
      }
      const float4 cst = lds128(sb + CST_OFF);
      const uint32_t tag = __float_as_uint(cst.z);
      uint4 own;
      {
        const bool odd = q4 & 1;
        const float l0 = dl[0][0] + dl[1][0], l1 = dl[0][1] + dl[1][1], l2 = dl[0][2] + dl[1][2], l3 = dl[0][3] + dl[1][3];
        const float mine = odd ? l2 : l0 + l1;
        const float other = __shfl_xor_sync(~0u, odd ? l0 : l2 + l3, 1);
        const int dsrc = (lane & ~3) | (gq >> 1);
        const float qa = __shfl_sync(~0u, (gq & 1) ? dq[0][1] + dq[2][1] : dq[0][0] + dq[2][0], dsrc);
        const float qb = __shfl_sync(~0u, (gq & 1) ? dq[1][3] + dq[3][3] : dq[1][2] + dq[3][2], dsrc);
        own = make_uint4(__float_as_uint(odd ? mine : other), __float_as_uint(odd ? qb : qa), __float_as_uint(odd ? other : mine), tag);
        if (q4 < 2) st_msg(&pp.mail->stats[(blk * 4 + m4) * 64 + wq * 16 + gq + 8 * q4], own.x, own.y, own.z, tag);
      }
      if (lane == 0) mbar_arrive(BAR(B_XDONE));
      if (elect) TRACE(15);
      const int srow = wq * 16 + gq + 8 * (q4 & 1);
      const uint4* src0 = &pp.mail->stats[(blk * 4 + (m4 ^ (q4 | 1))) * 64 + srow];
      const uint4* src1 = &pp.mail->stats[(blk * 4 + (m4 ^ 2)) * 64 + srow];
      if (FK_E1DLY) delay_until(clk(), FK_E1DLY);
      uint4 m0 = ld_msg(src0), m1 = own;
      if (q4 >= 2) m1 = ld_msg(src1);
      mbar_wait(BAR(B_EMPTY + 3), 1);
#pragma unroll
      for (int i = 0; i < 16; i++)
        stsm_x4(sb + XST_OFF + mrow * 512 + (i >> 2) * 128 + (uint32_t)(((((2 * i) & 7) + (lane >> 4)) ^ (lane & 7)) << 4), xa[4 * i], xa[4 * i + 1], xa[4 * i + 2], xa[4 * i + 3]);
      uint4 cbv, sbv, gbv;
      const uint4* mp = reinterpret_cast<const uint4*>(pp.mod) + m4 * 32 + lane;
      cbv = ldg128(mp + 512); sbv = ldg128(mp + 384); gbv = ldg128(mp + 640);
      uint32_t k1, k2;
      uint2* cdst = &pp.mail->cand[blk];
      uint32_t tad = sb + TOP_OFF + (lane & 3) * 8, rad = scr + RST_REL + srow * 8, krow = 2047 - (blk * 64 + srow);
      asm volatile("" : "+l"(cdst), "+r"(tad), "+r"(rad), "+r"(krow));
      {
        int it = 0;
        while (!__all_sync(~0u, m0.w == tag && m1.w == tag)) {
          m0 = ld_msg(src0);
          if (q4 >= 2) m1 = ld_msg(src1);
          if (++it > SPIN_LIMIT) SPIN_FAIL(0x209);
        }
        if (elect) TRACE(16);
        float sa = __uint_as_float(m0.x) + __uint_as_float(m1.x), qa = __uint_as_float(m0.y) + __uint_as_float(m1.y), da = __uint_as_float(m0.z) + __uint_as_float(m1.z);
        sa += __shfl_xor_sync(~0u, sa, 2); qa += __shfl_xor_sync(~0u, qa, 2); da += __shfl_xor_sync(~0u, da, 2);
        const float mean = sa * (1.f / D_);
        const float rstd = rsqrt_f(fmaxf(fmaf(-mean, mean, qa * (1.f / D_)), 0.f) + 1e-5f);
        const float rme = fmaf(rstd, fmaf(-mean, cst.x, da), cst.y);
        warp_top2(fkey(rme, 2047 - krow), 0u, k1, k2);
        if (lane == wq) sts64u(tad, k1, k2);
        if (q4 < 2) sts64(rad, rstd, -mean * rstd);
        named_bar<2, 128>();
        const uint2 c = lds64u(tad);
        warp_top2(c.x, c.y, k1, k2);
        if (wq == 0) {
          if (lane == 0 && (FK_PUSHALL || m4 == (t & 3))) red_max8(cdst, k2, k1);
          if (lane == 0) sts64u(sb + TOP_OFF + 32, k1, k2);
          named_arrive<7, 64>();
        }
      }
      if (b < NMOE) named_arrive<1, 256>();
      if (elect) TRACE(17);
      const int c1 = key_row(k1) - blk * 64, c2 = key_row(k2) - blk * 64;
      if (wq >= 2) {
        const int r = wq == 2 ? c1 : c2;
        const uint4 v = lds128u(sb + XST_OFF + r * 512 + ((lane ^ (r & 7)) << 4));
        const float2 st = lds64(scr + RST_REL + r * 8);
        auto h2 = [&](uint32_t xv, uint32_t cv, uint32_t sv) {
          const uint32_t av = add1_bf2(cv);
          return pack_bf16(fmaf(fmaf(bf_lo(xv), st.x, st.y), bf_lo(av), bf_lo(sv)), fmaf(fmaf(bf_hi(xv), st.x, st.y), bf_hi(av), bf_hi(sv)));
        };
        const uint32_t sc = scr + SCR_REL + wq * 512;
        sts128u(sc + lane * 16, h2(v.x, cbv.x, sbv.x), h2(v.y, cbv.y, sbv.y), h2(v.z, cbv.z, sbv.z), h2(v.w, cbv.w, sbv.w));
        __syncwarp();
        const uint32_t fa = sc + gq * 64 + q4 * 4;
        const int o = (blk * 2 + wq - 2) * 128 + m4 * 32 + lane;
        st_msg(&pp.mail->rowh[o], lds32u(fa), lds32u(fa + 16), lds32u(fa + 32), lds32u(fa + 48));
        st_msg(&pp.mail->rowx[o], v.x, v.y, v.z, v.w);
        if (lane == 0 && wq == 3) TRACE(18);
      }
      {
        OutTab tb;
        out_tab(tb, cbv, sbv, gbv);
        char* odst = pp.out + (size_t)blk * (64 * 2 * D_) + m4 * 512 + lane * 16;
        const int g0 = blk * 64 + wq * 16;
        const int done = out_group(tb, sb, scr, wq * 16, 0xFFFFu & ~(row_bit(k1, g0) | row_bit(k2, g0)), lane, odst, FK_OPACE, b < NMOE ? BAR(B_SEL) : 0);
        if (lane == 0) { sts32u(sb + TOP_OFF + 48 + wq * 4, done); mbar_arrive(BAR(B_OUT)); }
      }
      if (elect) TRACE(25);
      if (b < NMOE) {
        uint32_t wd[128];
        mbar_wait(BAR(B_DN + wq), 0);
        {
          const int fr = (lane & 7) + (lane >> 4) * 8;
          const uint32_t base = sb + dn_box(wq) + fr * 128;
#pragma unroll
          for (int c = 0; c < 4; c++) {
            const uint32_t ad = base + (((uint32_t)(c * 2 + ((lane >> 3) & 1)) ^ (uint32_t)(lane & 7)) << 4);
#pragma unroll
            for (int gI = 0; gI < 4; gI++)
#pragma unroll
              for (int ks = 0; ks < 2; ks++) {
                const int o = ((gI * 4 + c) * 2 + ks) * 4;
                ldsm_x4_t(ad + gI * 4096 + ks * 2048, wd[o], wd[o + 1], wd[o + 2], wd[o + 3]);
              }
          }
        }
        uint4* dst = &pp.mail->part[((size_t)(wq * 32 + q4 * 4 + (gq >> 1)) * NMOE + b) * 2 + (gq & 1)];
        uint32_t pad = scr + PART_REL + lane * 16;
        asm volatile("" : "+l"(dst), "+r"(pad));
        if (lane == 0 && wq == 3) TRACE(27);
        named_bar<4, 384>();
        if (elect) TRACE(21);
        float4 ps[4];
#pragma unroll
        for (int w = 0; w < 4; w++) {
          const float4 p0 = lds128(pad + w * 1024), p1 = lds128(pad + w * 1024 + 512);
          ps[w] = make_float4(p0.x + p1.x, p0.y + p1.y, p0.z + p1.z, p0.w + p1.w);
        }
        const uint32_t gp = pack_bf16((ps[0].x + ps[1].x) + (ps[2].x + ps[3].x), (ps[0].y + ps[1].y) + (ps[2].y + ps[3].y));
        const uint32_t up = pack_bf16((ps[0].z + ps[1].z) + (ps[2].z + ps[3].z), (ps[0].w + ps[1].w) + (ps[2].w + ps[3].w));
        const uint32_t act = mul_bf2(pack_bf16(silu_f(bf_lo(gp)), silu_f(bf_hi(gp))), up);
        uint32_t ab[4];
#pragma unroll
        for (int u = 0; u < 4; u++) {
          const uint32_t v0 = __shfl_sync(~0u, act, 8 * u + 2 * q4), v1 = __shfl_sync(~0u, act, 8 * u + 2 * q4 + 1);
          ab[u] = __byte_perm(v0, v1, (gq & 1) ? 0x7632 : 0x5410);
        }
        if (FK_QUIET == 1) named_arrive<8, 256>();
        float c[4][4];
#pragma unroll
        for (int v = 0; v < 4; v++) { c[v][0] = c[v][1] = c[v][2] = c[v][3] = 0.f; }
#pragma unroll
        for (int q = 0; q < 4; q++) {
          const uint32_t mk = (gq >> 1) == q ? ~0u : 0u;
          const uint32_t b0 = ab[0] & mk, b1 = ab[1] & mk, b2 = ab[2] & mk, b3 = ab[3] & mk;
#pragma unroll
          for (int v = 0; v < 4; v++) { const int o = (4 * v + q) * 8; mma_16816(c[v], wd[o], wd[o + 1], wd[o + 2], wd[o + 3], b0, b1); }
#pragma unroll
          for (int v = 0; v < 4; v++) { const int o = (4 * v + q) * 8 + 4; mma_16816(c[v], wd[o], wd[o + 1], wd[o + 2], wd[o + 3], b2, b3); }
        }
#pragma unroll
        for (int u = 0; u < 2; u++)
          st_msg(dst + u * (16 * NMOE * 2), pack_bf16(c[2 * u][0], c[2 * u][1]), pack_bf16(c[2 * u][2], c[2 * u][3]),
                 pack_bf16(c[2 * u + 1][0], c[2 * u + 1][1]), pack_bf16(c[2 * u + 1][2], c[2 * u + 1][3]));
        if (FK_QUIET == 2) named_arrive<8, 256>();
        if (elect) TRACE(22);
      }
    }
  }
}

typedef CUresult (*PFN_encodeTiled)(CUtensorMap*, CUtensorMapDataType, cuuint32_t, void*, const cuuint64_t*, const cuuint64_t*,
                                    const cuuint32_t*, const cuuint32_t*, CUtensorMapInterleave, CUtensorMapSwizzle,
                                    CUtensorMapL2promotion, CUtensorMapFloatOOBfill);

static void map2d(PFN_encodeTiled enc, CUtensorMap* m, const void* p, uint64_t rows, uint64_t cols, uint32_t brows, uint32_t bcols, CUtensorMapSwizzle sw,
                  CUtensorMapL2promotion pr = CU_TENSOR_MAP_L2_PROMOTION_L2_128B) {
  cuuint64_t dims[2] = {cols, rows}; cuuint64_t str[1] = {cols * 2}; cuuint32_t box[2] = {bcols, brows}; cuuint32_t es[2] = {1, 1};
  enc(m, CU_TENSOR_MAP_DATA_TYPE_BFLOAT16, 2, (void*)p, dims, str, box, es, CU_TENSOR_MAP_INTERLEAVE_NONE, sw, pr,
      CU_TENSOR_MAP_FLOAT_OOB_FILL_NONE);
}
static void map3d(PFN_encodeTiled enc, CUtensorMap* m, const void* p, uint64_t rows, uint64_t cols, uint32_t brows, uint32_t bgroups) {
  cuuint64_t dims[3] = {64, rows, cols / 64}; cuuint64_t str[2] = {cols * 2, 128}; cuuint32_t box[3] = {64, brows, bgroups}; cuuint32_t es[3] = {1, 1, 1};
  enc(m, CU_TENSOR_MAP_DATA_TYPE_BFLOAT16, 3, (void*)p, dims, str, box, es, CU_TENSOR_MAP_INTERLEAVE_NONE, CU_TENSOR_MAP_SWIZZLE_128B,
      CU_TENSOR_MAP_L2_PROMOTION_L2_128B, CU_TENSOR_MAP_FLOAT_OOB_FILL_NONE);
}

}

extern "C" void kernel_launch(void* const* d_in, const int* in_sizes, int n_in, void* d_out, int out_size) {
  using namespace fk;
  (void)in_sizes; (void)n_in; (void)out_size;
  static PFN_encodeTiled enc = nullptr;
  static int maxClusters = -1;
  static void *pn = nullptr, *pP = nullptr, *pc = nullptr, *pm = nullptr, *pmod = nullptr;
  if (!enc) {
    void* fn = nullptr; cudaDriverEntryPointQueryResult qr;
    cudaGetDriverEntryPoint("cuTensorMapEncodeTiled", &fn, cudaEnableDefault, &qr);
    enc = (PFN_encodeTiled)fn;
    cudaGetSymbolAddress(&pn, g_n);
    cudaGetSymbolAddress(&pP, g_P);
    cudaGetSymbolAddress(&pc, g_cnt);
    cudaGetSymbolAddress(&pm, g_mail);
    cudaGetSymbolAddress(&pmod, g_mod);
    cudaFuncSetAttribute(fused_kernel, cudaFuncAttributeMaxDynamicSharedMemorySize, SMEM_BYTES);
  }
  Maps maps;
  map2d(enc, &maps.ws[0], d_in[1], S_, S_, 128, 64, CU_TENSOR_MAP_SWIZZLE_128B);
  map2d(enc, &maps.ws[1], d_in[2], S_, S_, 128, 64, CU_TENSOR_MAP_SWIZZLE_128B);
  map3d(enc, &maps.n, pn, S_, D_, 64, 4);
  map2d(enc, &maps.p, pP, 2 * S_, D_, 128, 64, CU_TENSOR_MAP_SWIZZLE_128B);
  map2d(enc, &maps.ps, pP, 2 * S_, D_, 64, 64, CU_TENSOR_MAP_SWIZZLE_128B);
  map2d(enc, &maps.wd[0], d_in[3], D_, D_, 256, 64, CU_TENSOR_MAP_SWIZZLE_128B);
  map2d(enc, &maps.wd[1], d_in[4], D_, D_, 256, 64, CU_TENSOR_MAP_SWIZZLE_128B);
  map2d(enc, &maps.x, d_in[0], S_, D_, 64, 64, CU_TENSOR_MAP_SWIZZLE_128B);
  map2d(enc, &maps.wg, d_in[7], D_, F_, 128, 32, CU_TENSOR_MAP_SWIZZLE_64B);
  map2d(enc, &maps.wu, d_in[8], D_, F_, 128, 32, CU_TENSOR_MAP_SWIZZLE_64B);
  map3d(enc, &maps.wdn, d_in[9], F_, D_, 32, 4);
  map2d(enc, &maps.wm, d_in[11], D_, 6 * D_, 64, 48, CU_TENSOR_MAP_SWIZZLE_NONE);

  cudaLaunchConfig_t cfg = {};
  cfg.gridDim = dim3(NCTA); cfg.blockDim = dim3(384); cfg.dynamicSmemBytes = SMEM_BYTES; cfg.stream = cudaStreamPerThread;
  cudaLaunchAttribute at[1];
  at[0].id = cudaLaunchAttributeClusterDimension; at[0].val.clusterDim.x = 2; at[0].val.clusterDim.y = 1; at[0].val.clusterDim.z = 1;
  cfg.attrs = at; cfg.numAttrs = 1;
  Ptrs pp{(const char*)d_in[0], (char*)pn, (unsigned*)pc, 0, 0, (Mail*)pm, (uint32_t*)pmod, (const char*)d_in[10], (const char*)d_in[1], (const char*)d_in[2],
          (const char*)d_in[3], (const char*)d_in[4], (const char*)d_in[6], (const char*)d_in[7], (const char*)d_in[8], (const char*)d_in[9], (char*)pP, (char*)d_out, nullptr};
  if (maxClusters < 0) {
    cfg.gridDim = dim3(NCTA + NEXTRA);
    if (cudaOccupancyMaxActiveClusters(&maxClusters, fused_kernel, &cfg) != cudaSuccess) maxClusters = 0;
  }
  pp.b0 = -NEXTRA;
  if (maxClusters >= (NCTA + NEXTRA) / 2) {
    cfg.gridDim = dim3(NCTA + NEXTRA);
  } else {
    cfg.gridDim = dim3(NEXTRA);
    cudaLaunchKernelEx(&cfg, fused_kernel, pp, maps);
    cfg.gridDim = dim3(NCTA); pp.b0 = 0;
  }
  cudaLaunchKernelEx(&cfg, fused_kernel, pp, maps);
}
```
